```python
import torch

def _softmax(x, axis=-1):
    return torch.softmax(x, dim=axis)

def _gelu(x):
    return torch.nn.functional.gelu(x, approximate='tanh')

def _silu(x):
    return torch.nn.functional.silu(x)

def _sigmoid(x):
    return torch.sigmoid(x)

def _layernorm(x, axis=-1, eps=1e-05):
    m = x.mean(dim=axis, keepdim=True)
    v = x.var(dim=axis, keepdim=True, unbiased=False)
    return (x - m) / torch.sqrt(v + eps)

def _scatter_add(tgt, idx, src, axis=0):
    return tgt.clone().index_add_(axis, idx, src)

def _segment_sum(src, seg, n):
    out = torch.zeros((n,) + src.shape[1:], dtype=src.dtype)
    return out.index_add_(0, seg, src)

def _pad(x, pw):
    flat = tuple((v for pair in reversed(pw) for v in pair))
    return torch.nn.functional.pad(x, flat)
kernel_name = 'concat_heads__memory_aug_recurrent_mem_tr__ssm_conv_s4d__prompt'

def setup_inputs():

    _w = lambda a: (lambda t: t.to(torch.bfloat16) if t.is_floating_point() else t)(torch.as_tensor(a))

    def _A_setup():
        B, S, Dm = (1, 2048, 576)
        H, Dh = (32, 128)
        M, seg = (8, 32)
        seg = min(seg, S)
        S = S // seg * seg
        return {'x': _w((lambda *s: torch.randn(*s, dtype=torch.bfloat16) * 0.05)(B, S, Dm)), 'mem0': _w((lambda *s: torch.randn(*s, dtype=torch.bfloat16) * 0.4)(B, M, Dm)), 'Wq': _w((lambda *s: torch.randn(*s, dtype=torch.bfloat16) * 6.4)(Dm, H, Dh) * Dm ** (-0.5)), 'Wk': _w((lambda *s: torch.randn(*s, dtype=torch.bfloat16) * 6.4)(Dm, H, Dh) * Dm ** (-0.5)), 'Wv': _w((lambda *s: torch.randn(*s, dtype=torch.bfloat16) * 0.4)(Dm, H, Dh) * Dm ** (-0.5)), 'Wo': _w((lambda *s: torch.randn(*s, dtype=torch.bfloat16) * 0.4)(H, Dh, Dm) * (H * Dh) ** (-0.5)), 'seg_len': seg}
    _A_in = _A_setup()

    def _B_setup():
        Bsz, L, D, N = (1, 2048, 576, 128)
        return {'u': _w((lambda *s: torch.randn(*s, dtype=torch.bfloat16) * 0.05)(Bsz, L, D)), 'log_A_real': _w((lambda *s: torch.randn(*s, dtype=torch.bfloat16) * 3.2)(D, N) * 0.5), 'A_imag': _w((lambda *s: torch.randn(*s, dtype=torch.bfloat16) * 0.05)(D, N) * 3.14), 'C_real': _w((lambda *s: torch.randn(*s, dtype=torch.bfloat16) * 0.4)(D, N) / N ** 0.5), 'C_imag': _w((lambda *s: torch.randn(*s, dtype=torch.bfloat16) * 0.4)(D, N) / N ** 0.5), 'log_dt': _w((lambda *s: torch.randn(*s, dtype=torch.bfloat16) * 0.05)(D) * 0.5 - 4.0), 'D_skip': _w((lambda *s: torch.randn(*s, dtype=torch.bfloat16) * 0.05)(D))}
    _B_in = _B_setup()
    return {'A_x': _A_in['x'], 'A_mem0': _A_in['mem0'], 'A_Wq': _A_in['Wq'], 'A_Wk': _A_in['Wk'], 'A_Wv': _A_in['Wv'], 'A_Wo': _A_in['Wo'], 'A_seg_len': _A_in['seg_len'], 'B_u': _B_in['u'], 'B_log_A_real': _B_in['log_A_real'], 'B_A_imag': _B_in['A_imag'], 'B_C_real': _B_in['C_real'], 'B_C_imag': _B_in['C_imag'], 'B_log_dt': _B_in['log_dt'], 'B_D_skip': _B_in['D_skip']}

def reference(A_x, A_mem0, A_Wq, A_Wk, A_Wv, A_Wo, A_seg_len, B_u, B_log_A_real, B_A_imag, B_C_real, B_C_imag, B_log_dt, B_D_skip):

    def _A_ref(x, mem0, Wq, Wk, Wv, Wo, seg_len):
        B, S, Dm = x.shape
        H, Dh = (Wq.shape[1], Wq.shape[2])
        M = mem0.shape[1]
        scale = Dh ** (-0.5)
        n_seg = S // seg_len
        L = M + seg_len
        idx = torch.arange(L)
        mask = (idx[:, None] < M) | (idx[:, None] >= idx[None, :])
        mem = mem0
        outs = []
        for s in range(n_seg):
            xs = x[:, s * seg_len:(s + 1) * seg_len, :].clone()
            h = torch.concatenate([mem, xs], axis=1)
            q = torch.einsum('btd,dhe->bhte', h, Wq)
            k = torch.einsum('btd,dhe->bhte', h, Wk)
            v = torch.einsum('btd,dhe->bhte', h, Wv)
            scores = torch.einsum('bhqe,bhke->bhqk', q, k) * scale
            scores = torch.where(mask[None, None], scores, -1000000000.0)
            p = _softmax(scores, axis=-1)
            o = torch.einsum('bhqk,bhke->bhqe', p, v)
            o = torch.einsum('bhte,hed->btd', o, Wo)
            mem = o[:, :M, :].clone()
            outs.append(o[:, M:, :])
        return torch.concatenate(outs, axis=1)

    def _B_ref(u, log_A_real, A_imag, C_real, C_imag, log_dt, D_skip):
        L = u.shape[1]
        dt = torch.exp(log_dt)
        A = -torch.exp(log_A_real) + 1j * A_imag
        C = (C_real + 1j * C_imag) * dt[:, None]
        pos = (lambda x, dt: x.to(dt))(torch.arange(L), log_dt.dtype)
        P = torch.exp((A * dt[:, None])[:, :, None] * pos[None, None, :])
        K = 2.0 * torch.einsum('dn,dnl->dl', C, P).real
        L2 = 2 * L
        u_t = (lambda x, *d: x.permute(*d))(u, 0, 2, 1)
        Kf = (lambda x, *a, **k: torch.fft.rfft(x.float(), *a, **k))(K, L2)
        Uf = (lambda x, *a, **k: torch.fft.rfft(x.float(), *a, **k))(u_t, L2)
        y = (lambda x, *a, **k: torch.fft.irfft(x, *a, **k).to(torch.bfloat16))(Uf * Kf[None, :, :], L2)[:, :, :L]
        y = (lambda x, *d: x.permute(*d))(y, 0, 2, 1)
        return y + u * D_skip[None, None, :]
    a = _A_ref(A_x, A_mem0, A_Wq, A_Wk, A_Wv, A_Wo, A_seg_len)
    b = _B_ref(B_u, B_log_A_real, B_A_imag, B_C_real, B_C_imag, B_log_dt, B_D_skip)
    return torch.concatenate([a, b], axis=-1)
```

```cpp
#include <cuda_runtime.h>
#include <cuda_bf16.h>
#include <cuda_fp16.h>
#include <cuda.h>
#include <stdint.h>

#define DEVI __device__ __forceinline__

#define NEG __int_as_float(0xff800000)
constexpr int DM = 576, NSEG = 64, HD = 4096, OUTW = 1152;

#define HM 7
#define QW 4000
#define NPROBE 4
#define CT 1500
#define FE 85
#define DL 0
#define DMIN 150
#define DMAX 4000
#define BACKOFF 200
#define LW 4
#define TIE 0
#define C2ADJ 80
#define DST 260
#define VFE 0
#define EW 0
#define LB 12
#define NTR 3
#define RP 176
#define NW2 3
#define KT 4
#define DDUMP 520
#define DPUSH 300
#define GOE 1
#define LDM 0
#define XD 150
#define G1T 0
#define F0T 14
#define F1T 16
#define SUMV 0
#define N1 8

__device__ __align__(1024) __nv_bfloat16 g_o[2048 * HD];
__device__ __align__(65536) uint32_t g_acc[16384];
__device__ __align__(128) unsigned g_pub[96];
__device__ __align__(128) float4 g_part[4][9][4][4][128];
__device__ __align__(1024) unsigned char g_qkv[(size_t)NSEG * 32 * 30720];
__device__ __align__(128) unsigned g_qflag[NSEG][32][32];
__device__ __align__(128) unsigned g_oflag[NSEG][32][8];
__device__ unsigned g_epoch[36 + 96];
#define EV(i)
#define EVV(i, v)
#define EVX(i) 0
#define EVADD(i, v)
#define HS(i)
#define HEV(i)
#define GT(b, i)

#define TRAP(code) __trap()
#define LOC(v)
DEVI uint32_t smem_u32(const void* p) { return (uint32_t)__cvta_generic_to_shared(p); }
DEVI uint32_t clk() { uint64_t t; asm volatile("mov.u64 %0, %%clock64;" : "=l"(t) :: "memory"); return (uint32_t)t; }
DEVI uint32_t gtime() { uint64_t t; asm volatile("mov.u64 %0, %%globaltimer;" : "=l"(t) :: "memory"); return (uint32_t)t; }
DEVI void spin_until(uint32_t t) { while ((int)(clk() - t) < 0) {} }
DEVI void jit() {}
DEVI uint32_t mapa(uint32_t a, uint32_t r) { uint32_t o; asm("mapa.shared::cluster.u32 %0, %1, %2;" : "=r"(o) : "r"(a), "r"(r)); return o; }
DEVI void mbar_init(uint32_t b, uint32_t n) { asm volatile("mbarrier.init.shared::cta.b64 [%0], %1;" :: "r"(b), "r"(n) : "memory"); }
DEVI void mbar_expect(uint32_t b, uint32_t bytes) { asm volatile("mbarrier.arrive.expect_tx.shared::cta.b64 _, [%0], %1;" :: "r"(b), "r"(bytes) : "memory"); }
DEVI void mbar_arrive(uint32_t b) { asm volatile("mbarrier.arrive.shared::cta.b64 _, [%0];" :: "r"(b) : "memory"); }
DEVI bool mbar_try(uint32_t b, uint32_t parity) {
    uint32_t ok;
    asm volatile("{.reg .pred p; mbarrier.try_wait.parity.shared::cta.b64 p, [%1], %2; selp.u32 %0, 1, 0, p;}" : "=r"(ok) : "r"(b), "r"(parity) : "memory");
    return ok;
}
DEVI void mbar_wait(uint32_t b, uint32_t parity) {
    LOC(0x100 | (b & 0xff) | (parity << 12));
    asm volatile("{.reg .pred p, q; .reg .u32 n; mov.u32 n, 0;\n W: mbarrier.try_wait.parity.shared::cta.b64 p, [%0], %1;\n"
                 "add.u32 n, n, 1; setp.lt.and.u32 q, n, 0x40000, !p; @q bra W;}" :: "r"(b), "r"(parity) : "memory");
    LOC(0x300 | (b & 0xff));
    jit();
}
DEVI void bar_sync(int id, int n) { jit(); LOC(0x200 | id); asm volatile("bar.sync %0, %1;" :: "r"(id), "r"(n) : "memory"); LOC(0x400 | id); jit(); }
DEVI void bar_arrive(int id, int n) { jit(); asm volatile("bar.arrive %0, %1;" :: "r"(id), "r"(n) : "memory"); jit(); }
DEVI void cluster_sync() { asm volatile("barrier.cluster.arrive.release.aligned; barrier.cluster.wait.acquire.aligned;" ::: "memory"); }
DEVI void cluster_arrive_rlx() { asm volatile("barrier.cluster.arrive.relaxed.aligned;" ::: "memory"); }
DEVI void cluster_wait() { asm volatile("barrier.cluster.wait.aligned;" ::: "memory"); }
DEVI void fence_async() { asm volatile("fence.proxy.async;" ::: "memory"); }
DEVI void cp16(uint32_t dst, const void* src) { asm volatile("cp.async.cg.shared.global [%0], [%1], 16;" :: "r"(dst), "l"(src) : "memory"); }
DEVI void cp_commit() { asm volatile("cp.async.commit_group;" ::: "memory"); }
template <int N> DEVI void cp_wait() { asm volatile("cp.async.wait_group %0;" :: "n"(N) : "memory"); }
DEVI void ldsm4(uint32_t* r, uint32_t a) {
    asm volatile("ldmatrix.sync.aligned.m8n8.x4.shared.b16 {%0,%1,%2,%3}, [%4];" : "=r"(r[0]), "=r"(r[1]), "=r"(r[2]), "=r"(r[3]) : "r"(a) : "memory");
}
DEVI uint32_t tab1(uint32_t a) { uint32_t r; asm volatile("ldmatrix.sync.aligned.m8n8.x1.shared.b16 {%0}, [%1];" : "=r"(r) : "r"(a) : "memory"); return r; }
DEVI uint2 tab2(uint32_t a) { uint2 r; asm volatile("ldmatrix.sync.aligned.m8n8.x2.shared.b16 {%0,%1}, [%2];" : "=r"(r.x), "=r"(r.y) : "r"(a) : "memory"); return r; }
DEVI void ldsm4t(uint32_t* r, uint32_t a) {
    asm volatile("ldmatrix.sync.aligned.m8n8.x4.trans.shared.b16 {%0,%1,%2,%3}, [%4];" : "=r"(r[0]), "=r"(r[1]), "=r"(r[2]), "=r"(r[3]) : "r"(a) : "memory");
}
DEVI void mma16(float* d, uint32_t a0, uint32_t a1, uint32_t a2, uint32_t a3, uint32_t b0, uint32_t b1) {
    asm volatile("mma.sync.aligned.m16n8k16.row.col.f32.bf16.bf16.f32 {%0,%1,%2,%3}, {%4,%5,%6,%7}, {%8,%9}, {%0,%1,%2,%3};"
                 : "+f"(d[0]), "+f"(d[1]), "+f"(d[2]), "+f"(d[3]) : "r"(a0), "r"(a1), "r"(a2), "r"(a3), "r"(b0), "r"(b1));
}
DEVI void mma8(float* d, uint32_t a0, uint32_t a1, uint32_t b0) {
    asm volatile("mma.sync.aligned.m16n8k8.row.col.f32.bf16.bf16.f32 {%0,%1,%2,%3}, {%4,%5}, {%6}, {%0,%1,%2,%3};"
                 : "+f"(d[0]), "+f"(d[1]), "+f"(d[2]), "+f"(d[3]) : "r"(a0), "r"(a1), "r"(b0));
}
DEVI void mma_tf32(float* d, uint32_t a0, uint32_t a1, uint32_t a2, uint32_t a3, uint32_t b0, uint32_t b1) {
    asm volatile("mma.sync.aligned.m16n8k8.row.col.f32.tf32.tf32.f32 {%0,%1,%2,%3}, {%4,%5,%6,%7}, {%8,%9}, {%0,%1,%2,%3};"
                 : "+f"(d[0]), "+f"(d[1]), "+f"(d[2]), "+f"(d[3]) : "r"(a0), "r"(a1), "r"(a2), "r"(a3), "r"(b0), "r"(b1));
}
template <int ACC> DEVI void wgmma32(float* d, const uint32_t* a, uint64_t desc) {
    asm volatile("wgmma.mma_async.sync.aligned.m64n32k16.f32.bf16.bf16 "
                 "{%0,%1,%2,%3,%4,%5,%6,%7,%8,%9,%10,%11,%12,%13,%14,%15}, {%16,%17,%18,%19}, %20, %21, 1, 1, 0;"
                 : "+f"(d[0]), "+f"(d[1]), "+f"(d[2]), "+f"(d[3]), "+f"(d[4]), "+f"(d[5]), "+f"(d[6]), "+f"(d[7]),
                   "+f"(d[8]), "+f"(d[9]), "+f"(d[10]), "+f"(d[11]), "+f"(d[12]), "+f"(d[13]), "+f"(d[14]), "+f"(d[15])
                 : "r"(a[0]), "r"(a[1]), "r"(a[2]), "r"(a[3]), "l"(desc), "n"(ACC));
}
template <int ACC> DEVI void wgmma32_ss(float* d, uint64_t adesc, uint64_t desc) {
    asm volatile("wgmma.mma_async.sync.aligned.m64n32k16.f32.bf16.bf16 "
                 "{%0,%1,%2,%3,%4,%5,%6,%7,%8,%9,%10,%11,%12,%13,%14,%15}, %16, %17, %18, 1, 1, 1, 0;"
                 : "+f"(d[0]), "+f"(d[1]), "+f"(d[2]), "+f"(d[3]), "+f"(d[4]), "+f"(d[5]), "+f"(d[6]), "+f"(d[7]),
                   "+f"(d[8]), "+f"(d[9]), "+f"(d[10]), "+f"(d[11]), "+f"(d[12]), "+f"(d[13]), "+f"(d[14]), "+f"(d[15])
                 : "l"(adesc), "l"(desc), "n"(ACC));
}
DEVI void wg_fence() { asm volatile("wgmma.fence.sync.aligned;" ::: "memory"); }
DEVI void wg_commit() { asm volatile("wgmma.commit_group.sync.aligned;" ::: "memory"); }
DEVI void wg_wait0() { asm volatile("wgmma.wait_group.sync.aligned 0;" ::: "memory"); }
DEVI uint64_t desc_sw128(uint32_t saddr) { return ((uint64_t)1 << 62) | ((uint64_t)64 << 32) | ((uint64_t)1 << 16) | (uint64_t)((saddr & 0x3FFFF) >> 4); }
DEVI uint32_t desc_lo(uint32_t saddr) { return (1u << 16) | ((saddr & 0x3FFFF) >> 4); }
DEVI uint64_t desc_of(uint32_t lo) { uint64_t d; asm("mov.b64 %0, {%1, 0x40000040};" : "=l"(d) : "r"(lo)); return d; }
DEVI uint32_t pack2(float lo, float hi) { uint32_t r; asm("cvt.rn.bf16x2.f32 %0, %1, %2;" : "=r"(r) : "f"(hi), "f"(lo)); return r; }
DEVI void sts32(uint32_t a, uint32_t v) { asm volatile("st.shared.u32 [%0], %1;" :: "r"(a), "r"(v) : "memory"); }
DEVI void sts64f(uint32_t a, float x, float y) { asm volatile("st.shared.v2.f32 [%0], {%1,%2};" :: "r"(a), "f"(x), "f"(y) : "memory"); }
DEVI void sts128f(uint32_t a, float x, float y, float z, float w) { asm volatile("st.shared.v4.f32 [%0], {%1,%2,%3,%4};" :: "r"(a), "f"(x), "f"(y), "f"(z), "f"(w) : "memory"); }
DEVI float2 lds64f(uint32_t a) { float2 v; asm volatile("ld.shared.v2.f32 {%0,%1}, [%2];" : "=f"(v.x), "=f"(v.y) : "r"(a) : "memory"); return v; }
DEVI float4 lds128f(uint32_t a) { float4 v; asm volatile("ld.shared.v4.f32 {%0,%1,%2,%3}, [%4];" : "=f"(v.x), "=f"(v.y), "=f"(v.z), "=f"(v.w) : "r"(a) : "memory"); return v; }
DEVI uint4 lds128(uint32_t a) { uint4 v; asm volatile("ld.shared.v4.u32 {%0,%1,%2,%3}, [%4];" : "=r"(v.x), "=r"(v.y), "=r"(v.z), "=r"(v.w) : "r"(a) : "memory"); return v; }
DEVI uint4 ldm128(uint32_t a) {
    uint4 v;
    asm volatile("ld.shared.v4.u32 {%0,%1,%2,%3}, [%4];" : "=r"(v.x), "=r"(v.y), "=r"(v.z), "=r"(v.w) : "r"(a) : "memory");
    return v;
}
DEVI void sta32(uint32_t a, uint32_t v, uint32_t bar) { asm volatile("st.async.weak.shared::cluster.mbarrier::complete_tx::bytes.b32 [%0], %1, [%2];" :: "r"(a), "r"(v), "r"(bar) : "memory"); }
DEVI void sta64f(uint32_t a, float x, float y, uint32_t bar) { asm volatile("st.async.weak.shared::cluster.mbarrier::complete_tx::bytes.v2.f32 [%0], {%1,%2}, [%3];" :: "r"(a), "f"(x), "f"(y), "r"(bar) : "memory"); }
DEVI void sta128f(uint32_t a, float x, float y, float z, float w, uint32_t bar) {
    asm volatile("st.async.weak.shared::cluster.mbarrier::complete_tx::bytes.v4.f32 [%0], {%1,%2,%3,%4}, [%5];" :: "r"(a), "f"(x), "f"(y), "f"(z), "f"(w), "r"(bar) : "memory");
}
DEVI void stg_rlx(uint32_t* p, uint32_t v) { asm volatile("st.relaxed.gpu.global.u32 [%0], %1;" :: "l"(p), "r"(v) : "memory"); }
DEVI void stg_release(unsigned* p, unsigned v) { asm volatile("st.release.gpu.global.u32 [%0], %1;" :: "l"(p), "r"(v) : "memory"); }
DEVI uint32_t ldg_rlx(const uint32_t* p) { uint32_t v; asm volatile("ld.relaxed.gpu.global.u32 %0, [%1];" : "=r"(v) : "l"(p) : "memory"); return v; }
DEVI void bulk_g2s(uint32_t dst, const void* src, uint32_t bytes, uint32_t bar) {
    asm volatile("cp.async.bulk.shared::cluster.global.mbarrier::complete_tx::bytes [%0], [%1], %2, [%3];" :: "r"(dst), "l"(src), "r"(bytes), "r"(bar) : "memory");
}
DEVI void bulk_s2c(uint32_t dst, uint32_t src, uint32_t bytes, uint32_t bar) {
    asm volatile("cp.async.bulk.shared::cluster.shared::cta.mbarrier::complete_tx::bytes [%0], [%1], %2, [%3];" :: "r"(dst), "r"(src), "r"(bytes), "r"(bar) : "memory");
}
DEVI float ex2(float x) { float y; asm("ex2.approx.ftz.f32 %0, %1;" : "=f"(y) : "f"(x)); return y; }
DEVI float bf2f(__nv_bfloat16 v) { return __bfloat162float(v); }

DEVI uint32_t pin(uint32_t v) { return __shfl_sync(0xffffffffu, v, threadIdx.x & 31); }
template <typename T> DEVI T* pinp(T* p) { const uint64_t v = (uint64_t)p; return (T*)(((uint64_t)pin((uint32_t)(v >> 32)) << 32) | pin((uint32_t)v)); }
DEVI uint32_t fresh(uint32_t v) { uint32_t r; asm volatile("mov.u32 %0, %1;" : "=r"(r) : "r"(v)); return r; }
DEVI uint64_t fresh64(uint64_t v) { uint64_t r; asm volatile("mov.u64 %0, %1;" : "=l"(r) : "l"(v)); return r; }
DEVI uint32_t or3(uint32_t a, uint32_t b, uint32_t c) { uint32_t d; asm("lop3.b32 %0, %1, %2, %3, 0xfe;" : "=r"(d) : "r"(a), "r"(b), "r"(c)); return d; }
DEVI uint32_t and3(uint32_t a, uint32_t b, uint32_t c) { uint32_t d; asm("lop3.b32 %0, %1, %2, %3, 0x80;" : "=r"(d) : "r"(a), "r"(b), "r"(c)); return d; }
DEVI uint32_t diff2(uint32_t a, uint32_t b, uint32_t p) { uint32_t d; asm("lop3.b32 %0, %1, %2, %3, 0x7e;" : "=r"(d) : "r"(a), "r"(b), "r"(p)); return d; }
DEVI int lds32(uint32_t a) { int v; asm volatile("ld.volatile.shared.s32 %0, [%1];" : "=r"(v) : "r"(a) : "memory"); return v; }
DEVI uint2 lds64(uint32_t a) { uint2 v; asm volatile("ld.shared.v2.u32 {%0,%1}, [%2];" : "=r"(v.x), "=r"(v.y) : "r"(a) : "memory"); return v; }
DEVI void sts64(uint32_t a, uint32_t x, uint32_t y) { asm volatile("st.shared.v2.u32 [%0], {%1,%2};" :: "r"(a), "r"(x), "r"(y) : "memory"); }
DEVI void sta64(uint32_t a, uint32_t x, uint32_t y, uint32_t bar) { asm volatile("st.async.weak.shared::cluster.mbarrier::complete_tx::bytes.v2.b32 [%0], {%1,%2}, [%3];" :: "r"(a), "r"(x), "r"(y), "r"(bar) : "memory"); }
DEVI float rcp_fast(float x) { float y; asm("rcp.approx.ftz.f32 %0, %1;" : "=f"(y) : "f"(x)); return y; }
DEVI uint4 ldg_rlx4(const void* p) { uint4 v; asm volatile("ld.relaxed.gpu.global.v4.u32 {%0,%1,%2,%3}, [%4];" : "=r"(v.x), "=r"(v.y), "=r"(v.z), "=r"(v.w) : "l"(p) : "memory"); return v; }
DEVI void sts128(uint32_t a, uint32_t x, uint32_t y, uint32_t z, uint32_t w) { asm volatile("st.shared.v4.u32 [%0], {%1,%2,%3,%4};" :: "r"(a), "r"(x), "r"(y), "r"(z), "r"(w) : "memory"); }
DEVI void stsm4(uint32_t a, uint32_t x, uint32_t y, uint32_t z, uint32_t w) { asm volatile("stmatrix.sync.aligned.m8n8.x4.shared.b16 [%0], {%1,%2,%3,%4};" :: "r"(a), "r"(x), "r"(y), "r"(z), "r"(w) : "memory"); }
DEVI void stsm2(uint32_t a, uint32_t x, uint32_t y) { asm volatile("stmatrix.sync.aligned.m8n8.x2.shared.b16 [%0], {%1,%2};" :: "r"(a), "r"(x), "r"(y) : "memory"); }
DEVI void fence_smem_async() { asm volatile("fence.proxy.async.shared::cta;" ::: "memory"); }
DEVI uint32_t packh2(float lo, float hi) { uint32_t r; asm("cvt.rn.f16x2.f32 %0, %1, %2;" : "=r"(r) : "f"(hi), "f"(lo)); return r; }
DEVI uint32_t h2_to_bf2(uint32_t w) {
    uint32_t r;
    asm("{.reg .f16 l, h; .reg .f32 a, b; mov.b32 {l, h}, %1; cvt.f32.f16 a, l; cvt.f32.f16 b, h; cvt.rn.bf16x2.f32 %0, b, a;}" : "=r"(r) : "r"(w));
    return r;
}
DEVI uint32_t amax2(uint32_t m, uint32_t w) { return __vmaxu2(m, w & 0x7fff7fffu); }
DEVI uint32_t amax_fold(uint32_t m) { return __reduce_max_sync(0xffffffffu, max(m & 0xffffu, m >> 16)); }
DEVI float bflo(uint32_t w) { return __uint_as_float(w << 16); }
DEVI float bfhi(uint32_t w) { return __uint_as_float(w & 0xffff0000u); }
DEVI void red_b8(void* p, uint32_t a, uint32_t b, uint32_t c, uint32_t d) {
    asm volatile("red.relaxed.gpu.global.add.noftz.v4.bf16x2 [%0], {%1,%2,%3,%4};" :: "l"(p), "r"(a), "r"(b), "r"(c), "r"(d) : "memory");
}
DEVI void red_h8_if(bool on, void* p, uint32_t a, uint32_t b, uint32_t c, uint32_t d) {
    asm volatile("{.reg .pred p; setp.ne.u32 p, %5, 0; @p red.relaxed.gpu.global.add.noftz.v4.bf16x2 [%0], {%1,%2,%3,%4};}" :: "l"(p), "r"(a), "r"(b), "r"(c), "r"(d), "r"((uint32_t)on) : "memory");
}
DEVI void mbar_arrive_warp(uint32_t b) { asm volatile("{.reg .pred p; elect.sync _|p, 0xffffffff; @p mbarrier.arrive.shared::cta.b64 _, [%0];}" :: "r"(b) : "memory"); }
DEVI void bulk_s2c_warp(uint32_t dst, uint32_t src, uint32_t bytes, uint32_t bar) {
    asm volatile("{.reg .pred p; elect.sync _|p, 0xffffffff; @p cp.async.bulk.shared::cluster.shared::cta.mbarrier::complete_tx::bytes [%0], [%1], %2, [%3];}" :: "r"(dst), "r"(src), "r"(bytes), "r"(bar) : "memory");
}
DEVI char* mkptr(uint32_t lo, uint32_t hi) { uint64_t p; asm("mov.b64 %0, {%1, %2};" : "=l"(p) : "r"(lo), "r"(hi)); return (char*)p; }
DEVI void bulk_s2g(void* dst, uint32_t src, uint32_t bytes) { asm volatile("cp.async.bulk.global.shared::cta.bulk_group [%0], [%1], %2;" :: "l"(dst), "r"(src), "r"(bytes) : "memory"); }
DEVI void x_tma(uint32_t dst, const CUtensorMap* m, uint32_t xb, int row, int chunk) {
    asm volatile("cp.async.bulk.tensor.3d.shared::cluster.global.mbarrier::complete_tx::bytes.multicast::cluster [%0], [%1, {%3, %4, %5}], [%2], %6;"
                 :: "r"(dst), "l"(m), "r"(xb), "r"(0), "r"(row), "r"(chunk), "h"((uint16_t)7) : "memory");
}
#define RUNG_(A, B, PA, PB) "mov.u64 " A ", %%clock64;\n cvt.u32.u64 l, " B ";\n sub.s32 l, l, %0;\n setp.ge.s32 " PB ", l, 0;\n @" PA " bra.uni DONE;\n"
DEVI void fine_until(uint32_t t) {
    asm volatile("{.reg .pred p0, p1; .reg .b64 t0, t1; .reg .b32 l;\n setp.ne.u32 p0, 0, 0;\n mov.u64 t1, %%clock64;\n LOOP:\n"
                 RUNG_("t0", "t1", "p0", "p1") RUNG_("t1", "t0", "p1", "p0") RUNG_("t0", "t1", "p0", "p1") RUNG_("t1", "t0", "p1", "p0")
                 RUNG_("t0", "t1", "p0", "p1") RUNG_("t1", "t0", "p1", "p0") RUNG_("t0", "t1", "p0", "p1") RUNG_("t1", "t0", "p1", "p0")
                 "bra.uni LOOP;\n DONE:\n}" :: "r"(t) : "memory");
}
DEVI uint32_t clock_offset() {
    const uint32_t g0 = gtime();
    uint32_t e = clk();
#pragma unroll
    for (int i = 0; i < 7; i++) { const uint32_t g = gtime(), t = clk(); e = g == g0 ? t : e; }
    return ((((g0 >> 5) + 1) * 3686u) >> 6) - e;
}
DEVI uint32_t probe_rtt(uint32_t* a) {
    uint32_t best = 0xffffffffu;
#pragma unroll 1
    for (int r = 0; r < NPROBE; r++) {
        uint32_t v = 0, t0 = clk();
        if ((threadIdx.x & 31) == 0) asm volatile("atom.relaxed.gpu.global.exch.b32 %0, [%1], 0;" : "=r"(v) : "l"(a) : "memory");
        const uint32_t t1 = __shfl_sync(0xffffffffu, v, 0) == 0x9e3779b9u ? 0 : clk();
        best = min(best, t1 - t0);
    }
    return best;
}

constexpr int R_X0 = 0;
constexpr int R_WO = 36864;
constexpr int R_DBG = 110592;
constexpr int R_K = 114688 + 3072;
constexpr int R_V = R_K + 4608;
constexpr int R_VM = R_V + 8192;
constexpr int PAR = 17920;
constexpr int R_QM = R_VM + 2048 + PAR;
constexpr int R_SC = R_QM + 1536;
constexpr int R_O8 = R_SC + 2048;
constexpr int R_PX = R_O8 + 2048;
constexpr int R_PV = R_PX + 8192;
constexpr int R_Z = R_PV + 4096;
constexpr int R_T0 = R_Z + 512;
constexpr int R_T1 = R_T0 + 2048;
constexpr int R_T2 = R_T1 + 8192;
constexpr int R_T3 = R_T2 + 512;
constexpr int R_T4 = R_T3 + 2048;
constexpr int R_END = R_T4 + 4096;
constexpr int R_STAGE = 86016;
constexpr int R_MEM = 217088;
constexpr int R_BAR = R_MEM + 12288;
constexpr int R_MISC = R_BAR + 128;
constexpr int R_SMEM = R_MISC + 128;
static_assert(R_END <= R_STAGE + 7 * 16384, "smem");
enum { BX0 = 0  , BSC = 24, BME = 32, BVX = 40  , BML = 56 };
enum { NB_F1 = 1, NB_K = 5, NB_G1 = 6, NB_E0 = 7, NB_GO = 8, NB_W1 = 9, NB_H1 = 10, NB_TOK = 11, NB_W2 = 12, NB_F0 = 13, NB_L0 = 14   };
enum { M_EPOCH = 0, M_SINK = 4, M_PROBE = 8  , M_TGT = 16  , M_REF = 24  , M_ONE = 32 };
constexpr uint32_t EMPTY = 0xc200u;
constexpr float QS = 0.08838834764831845f * 1.4426950408889634f;

DEVI uint32_t acc_slot(uint32_t s) { return (s & 1) * 128 + (s & 2) * 16384; }
DEVI uint32_t acc_blk(uint32_t m, uint32_t l) { return (((l >> 1) << 2) | ((l & 1) << 1) | ((l & 1) ^ m)) * 4096; }
DEVI uint32_t acc_line(uint32_t i, uint32_t q, uint32_t l) { return acc_blk(q & 1, l) + (q >> 1) * 256 + (i < 4 ? i * 1024 : i * 1024 - 1536); }
DEVI uint32_t acc_stamp(uint32_t m, uint32_t n) { return acc_blk(m, n >> 5) + 512 + (n & 31) * 4; }

#define LOAD_TRANSIENT(LA) { _Pragma("unroll") for (int i_ = 0; i_ < NTR; i_++) ldsm4t(w[i_ & 1][i_ >> 1], (LA) + (i_ & 1) * 4096 + (i_ >> 1) * 2048); }
#define MMAW(D, T, K, B0, B1) mma16(D, w[T][K][0], w[T][K][1], w[T][K][2], w[T][K][3], B0, B1)

DEVI void proj_loop(uint32_t (&w)[2][18][4], unsigned char* smem, const uint32_t sb, const uint32_t c, const int wg, const int q, const uint32_t lane0) {
    const uint32_t bar = sb + R_BAR;
    const int p = q ^ (2 * wg);
    const bool c2 = c == 2, both = !c2 && p < 2, aq = c2 ? p < 2 : p != 2;
    const uint32_t lp = pin(sb + lane0 * 16 + p * 1024), ma = pin(sb + lane0 * 16 + wg * 1024);
    {
        const uint32_t l16 = sb + lane0 * 16;
        const int ia = c2 ? p & 1 : min(p, 2), vt = c2 ? 4 + p : 2 * c + p - 2;
        const uint32_t dtok = l16 + (wg ? (aq ? R_K - ((c2 ? 2 : 3) - ia) * 1024 : R_K + ia * 1536) : (both ? R_K + p * 1536 : R_V + vt * 1024));
        const uint32_t la = sb + R_STAGE + 7 * 16384 + wg * 8192 + (((lane0 >> 4) << 3) + (lane0 & 7)) * 128 + (((2 * q + ((lane0 >> 3) & 1)) ^ (lane0 & 7)) << 4);
        const bool lo = lane0 < 16, mq = aq && lo, mv = !both && !lo;
        const uint32_t dmem = sb + (mq ? R_QM + ia * 512 + (lane0 & 8) * 32 + wg * 128 : (mv ? R_PV + p * 1024 : R_K + ia * 1536 + 1024) + wg * 256 + (lane0 & 8) * 16) + (lane0 & 7) * 16;
        stsm4(lp + R_T4 + wg * 512, dtok, la, dmem, dmem + (mq || mv ? 0 : PAR));
        const uint32_t p0 = mapa(sb, c2 ? 0 : c + 1), p1 = mapa(sb, c == 0 ? 2 : c - 1), d = R_VM + vt * 256 + lane0 * 4;
        sts128(lp + R_PV + 512, p0 + d, p0 + R_BAR + BSC, p1 + d, p1 + R_BAR + BSC);
        __syncwarp();
        mbar_wait(bar + BX0, 0);
    }
#define PUBLISH(S) { asm volatile("cp.async.bulk.wait_group 0;" ::: "memory"); stg_rlx(&g_qflag[S][blockIdx.x / 3][c * 8], lds32(sb + R_MISC + M_EPOCH)); }
#pragma unroll 1
    for (int s = 0; s < NSEG; s++) {
        const int xi = s - 3 * ((s * 43) >> 7);
        {
            float d[16];
#define TOKEN(WG, T, I0, I1, ZERO)                                                                                          \
    {                                                                                                                       \
    const uint32_t xd = fresh(desc_lo(sb + xi * 36864)), ad = fresh(desc_lo(sb + R_STAGE + 7 * 16384));                     \
    wg_fence();                                                                                                             \
    _Pragma("unroll") for (int i = I0; i < I1; i++) {                                                                       \
        const int j = i < 10 ? i + 2 : (i < 12 ? i - 10 : i), g = 18 * WG + j;                                              \
        const uint64_t bd = desc_of(xd + (g >> 2) * 256 + (g & 3) * 2);                                                     \
        if (2 * j + (T) < NTR) wgmma32_ss<1>(d, desc_of(ad + ((WG * 8192 + (T) * 4096 + j * 2048) >> 4)), bd);                          \
        else if (i == 0 && ZERO) wgmma32<0>(d, w[T][j], bd);                                                                \
        else wgmma32<1>(d, w[T][j], bd);                                                                                    \
    }                                                                                                                       \
    wg_commit();                                                                                                            \
    }
#define HANDOVER(WG)                                                                                                        \
    {                                                                                                                       \
        const uint32_t xa = lp + R_PX + WG * 4096;                                                                          \
        sts128(xa, pack2(d[0], d[1]), pack2(d[2], d[3]), pack2(d[4], d[5]), pack2(d[6], d[7]));                             \
        sts128(xa + 512, pack2(d[8], d[9]), pack2(d[10], d[11]), pack2(d[12], d[13]), pack2(d[14], d[15]));                 \
    }
            if (wg == 0) {
                bar_sync(NB_G1, 256);
                TOKEN(0, 0, 0, 18, 1)
                const uint32_t la = tab1(lp + R_T4 + 128);
                wg_wait0();
                EV(3);
                if (q == 1 && s > 0) {
                    const uint2 tt = tab2(lp + R_T2 - 1024);
                    const uint32_t tag = s << 22;
                    const char* const sp = mkptr(tt.x + acc_slot(s - 1), tt.y);
                    uint4 v = ldg_rlx4(sp);
                    bar_sync(NB_E0, 256);
                    HANDOVER(0)
                    bar_arrive(NB_GO, 384);
                    LOAD_TRANSIENT(la)
                    const uint2 tr = lds64(sb + R_MISC + M_REF);
                    int n = 0;
                    while (__any_sync(0xffffffffu, (diff2(v.x, v.y, tag) | diff2(v.z, v.w, tag)) >> 22)) {
                        v = ldg_rlx4(sp);
                        if (++n > (1 << 22)) TRAP(1002);
                    }
                    const int m = __reduce_max_sync(0xffffffffu, max(max((int)((v.x - tr.y) << 10), (int)((v.y - tr.y) << 10)), max((int)((v.z - tr.y) << 10), (int)((v.w - tr.y) << 10)))) >> 10;
                    sts64(sb + R_MISC + M_TGT, tr.x + min(m, DMAX) + (CT - 65), s);
                    EV(0);
                    if (EVX(0)) EVV(11, m);
                } else {
                    bar_sync(NB_E0, 256);
                    HANDOVER(0)
                    bar_arrive(NB_GO, 384);
                    LOAD_TRANSIENT(la)
                }
                bar_sync(NB_F0, 256);
                TOKEN(0, 1, 0, F1T, 1)
                bar_arrive(NB_F1, 256);
                TOKEN(0, 1, F1T, 18, 0)
                const uint32_t dtok = tab1(lp + R_T4) + (s & 1) * PAR;
                bar_sync(NB_H1, 256);
                const uint4 oa = lds128(lp + R_PX + 4096);
                wg_wait0();
                const uint32_t u0 = pack2(d[0] + bflo(oa.x), d[1] + bfhi(oa.x)), u1 = pack2(d[2] + bflo(oa.y), d[3] + bfhi(oa.y));
                const uint4 ob = lds128(lp + R_PX + 4608);
                stsm4(dtok, u0, u1, pack2(d[4] + bflo(oa.z), d[5] + bfhi(oa.z)), pack2(d[6] + bflo(oa.w), d[7] + bfhi(oa.w)));
                stsm4(dtok + 512, pack2(d[8] + bflo(ob.x), d[9] + bfhi(ob.x)), pack2(d[10] + bflo(ob.y), d[11] + bfhi(ob.y)),
                      pack2(d[12] + bflo(ob.z), d[13] + bfhi(ob.z)), pack2(d[14] + bflo(ob.w), d[15] + bfhi(ob.w)));
                bar_arrive(NB_TOK, 384);
            } else {
                const uint2 tw = tab2(lp + R_T4 + 512);
                bar_sync(NB_GO, 384);
                TOKEN(1, 1, 0, F0T, 1)
                bar_arrive(NB_F0, 256);
                TOKEN(1, 1, F0T, 18, 0)
                const uint4 oa = lds128(lp + R_PX), ob = lds128(lp + R_PX + 512);
                wg_wait0();
                HANDOVER(1)
                bar_arrive(NB_H1, 256);
                {
                    const uint32_t ox[8] = {oa.x, oa.y, oa.z, oa.w, ob.x, ob.y, ob.z, ob.w};
#pragma unroll
                    for (int j = 0; j < 8; j++) { d[2 * j] = bflo(ox[j]); d[2 * j + 1] = bfhi(ox[j]); }
                }
                LOAD_TRANSIENT(tw.y)
                bar_sync(NB_F1, 256);
                TOKEN(1, 0, 0, 18, 0)
                if (q == 3 && s > 0) PUBLISH(s - 1)
                const float qs = aq ? QS : 1.f;
                const uint32_t dtok = tw.x + (s & 1) * PAR;
                wg_wait0();
                EV(13);
#pragma unroll
                for (int hf = 0; hf < 2; hf++) {
                    const float* e = d + 8 * hf;
                    stsm4(dtok + hf * 512, pack2(e[0] * qs, e[1] * qs), pack2(e[2] * qs, e[3] * qs), pack2(e[4] * qs, e[5] * qs), pack2(e[6] * qs, e[7] * qs));
                }
                EV(12);
                bar_arrive(NB_TOK, 384);
            }
#undef TOKEN
#undef HANDOVER
        }
        uint4 b[12];
        float a[4][4];
        int pass = 0;
      redo:
        mbar_wait(bar + BME, s & 1);
#pragma unroll
        for (int j = 0; j < 4; j++) a[0][j] = a[1][j] = a[2][j] = a[3][j] = 0.f;
#pragma unroll
        for (int i = 0; i < 4; i++) b[i] = ldm128(ma + R_MEM + (i >> 1) * 2048 + (i & 1) * 512);
#define BK0(k) ((k) % 3 == 2 ? b[(k) / 3 * 2].z : b[(k) / 3 * 2 + (k) % 3].x)
#define BK1(k) ((k) % 3 == 2 ? b[(k) / 3 * 2].w : b[(k) / 3 * 2 + (k) % 3].y)
#define KS(T, k) MMAW(a[2 * (T) + ((k) & 1)], T, k, BK0(k), BK1(k));
#define JOIN(g) { chk = or3(chk, b[2 * (g)].w, b[2 * (g) + 1].w); b[2 * (g)].w = b[2 * (g) + 1].z | chk; }
        uint32_t chk = 0;
#pragma unroll
        for (int k = 0; k < LW; k++) { if (k % 3 == 2) JOIN(k / 3) KS(0, k) KS(1, k) }
#pragma unroll
        for (int i = 4; i < 12; i++) b[i] = ldm128(ma + R_MEM + (i >> 1) * 2048 + (i & 1) * 512);
        const uint32_t dmem = tab1(lp + fresh(wg * 512 + (s & 1) * 128) + R_T4 + 256);
#pragma unroll
        for (int k = LW; k < 18; k++) { if (k % 3 == 2) JOIN(k / 3) KS(0, k) KS(1, k) }
        float r[4];
        {
            const float s0 = aq ? QS : 1.f;
#pragma unroll
            for (int j = 0; j < 4; j++) r[j] = a[3][j] + a[2][j];
            stsm4(dmem, pack2(fmaf(a[1][0], s0, a[0][0] * s0), fmaf(a[1][1], s0, a[0][1] * s0)), pack2(fmaf(a[1][2], s0, a[0][2] * s0), fmaf(a[1][3], s0, a[0][3] * s0)),
                  pack2(r[0], r[1]), pack2(r[2], r[3]));
            const uint32_t bad = __any_sync(0xffffffffu, chk);
            asm volatile("{.reg .pred p; setp.eq.u32 p, %0, 0; @p bar.arrive %1, 384;}" :: "r"(bad | wg), "n"((int)NB_K) : "memory");
            asm volatile("{.reg .pred p; setp.eq.u32 p, %0, 0; @p bar.sync %1, 384;}" :: "r"(bad | (wg ^ 1)), "n"((int)NB_K) : "memory");
            if (__builtin_expect(bad, 0)) goto repair;
        }
#undef JOIN
#undef KS
#undef BK0
#undef BK1
        if (wg == 0) { EV(1); continue; }
        if (!both) {
            const uint2 o = tab2(lp + R_PV);
            const uint4 tv = lds128(lp + R_PV + 512);
            const uint32_t lo = pack2(r[0] + bflo(o.x), r[1] + bfhi(o.x)), hi = pack2(r[2] + bflo(o.y), r[3] + bfhi(o.y));
            const uint32_t v0 = tv.x + (s & 1) * PAR, v1 = tv.z + (s & 1) * PAR, v2 = v0 - tv.y + bar + BSC;
            sta32(v0, lo, tv.y); sta32(v0 + 128, hi, tv.y);
            sta32(v1, lo, tv.w); sta32(v1 + 128, hi, tv.w);
            sts32(v2, lo); sts32(v2 + 128, hi);
            EV(2);
        }
        {
            if (q != 3) bar_arrive(NB_W1, 256);
            if (q == 3) {
                bar_sync(NB_W1, 256);
                unsigned char* const dst = g_qkv + (size_t)(s * 32 + blockIdx.x / 3) * 30720;
                const uint32_t so = sb + (s & 1) * PAR;
                fence_smem_async();
                asm volatile("{.reg .pred p; elect.sync _|p, 0xffffffff;\n"
                             "@p cp.async.bulk.global.shared::cta.bulk_group [%0], [%1], %2;\n"
                             "@p cp.async.bulk.global.shared::cta.bulk_group [%3], [%4], %5;\n"
                             "@p cp.async.bulk.global.shared::cta.bulk_group [%6], [%7], %8;\n"
                             "@p cp.async.bulk.commit_group;}"
                             :: "l"(dst + c * 7680), "r"(so + R_K - (c2 ? 2048 : 3072)), "r"(c2 ? 5120 : 7680),
                                "l"(dst + 20480 + c * 2048), "r"(so + R_V + c * 2048), "r"(c2 ? 4096 : 2048),
                                "l"(dst + 28672 + c * 512), "r"(so + R_VM + c * 512), "r"(c2 ? 1024 : 512) : "memory");
            } else if (q == 2) {
                const uint4 tz = lds128(lp + R_T0 + 1536);
                uint32_t z;
                asm volatile("atom.relaxed.gpu.global.exch.b32 %0, [%1], %2;" : "=r"(z) : "l"(mkptr(tz.x + acc_slot(s + 2), tz.y)), "r"(tz.w) : "memory");
                sts32(sb + R_MISC + M_SINK, z);
            }
        }
        continue;
      repair:
        {
            if (++pass > (1 << 20)) TRAP(1000);
#pragma unroll 1
            for (int i = 0; i < 2; i++) {
                const uint2 tb = tab2(ma + fresh(i * 512) + R_T1 + 256 + ((s - 1) & 3) * 2048);
                const uint32_t md = ma + (ma & 256) + R_MEM + i * 2048;
                const char* const ga = mkptr(tb.x, tb.y);
                cp16(md, ga); cp16(md + 256, ga + 1024); cp16(md + 4096, ga + 2048); cp16(md + 4352, ga + 3072);
                cp16(md + 8192, ga + 2560); cp16(md + 8448, ga + 3584);
            }
            asm volatile("cp.async.wait_all;" ::: "memory");
            __syncwarp();
            const uint32_t la = tab1(lp + fresh(wg * 512) + R_T4 + 128);
            LOAD_TRANSIENT(la)
            goto redo;
        }
    }
    if (wg == 1 && q == 3) PUBLISH(NSEG - 1)
#undef PUBLISH
}

DEVI void attn_loop(const uint32_t (&wo)[3][8][4], const CUtensorMap* xmap, const CUtensorMap* amap, unsigned char* smem, const uint32_t sb, const uint32_t c, const int q,
                    const uint32_t lane0, const uint32_t side, const uint32_t jw) {
    const uint32_t bar = sb + R_BAR;
    const bool c2 = c == 2;
    const uint32_t l16 = pin(sb + lane0 * 16);
    {
        const uint32_t lane = lane0, n = blockIdx.x, gl = (uint32_t)(uint64_t)(void*)g_acc, gh = (uint32_t)((uint64_t)(void*)g_acc >> 32);
        const uint32_t p0 = mapa(sb, c2 ? 0 : c + 1), p1 = mapa(sb, c == 0 ? 2 : c - 1), so = R_SC + lane * 4;
        if (q < 3) sts128(l16 + R_T0 + q * 512, p0 + so + (q == 2 ? 1536 : 512 + q * 256), p0 + R_BAR + BSC, p1 + so + (q == 2 ? 1664 : 1024 + q * 256), p1 + R_BAR + BSC);
        else {
            sts128(l16 + R_T0 + q * 512, gl + acc_line(n >> 4, (n >> 2) & 3, n & 3) + lane * 4, gh, gl + acc_stamp(lane & 1, n), (lane & 3) == 3 ? EMPTY : 0);
            stsm2(l16 + R_T2, gl + acc_stamp(side, (lane < 24 ? lane : 0) * 4), gh);
        }
        for (int i = 0; i < 4; i++)
            stsm4(l16 + R_T1 + i * 2048 + q * 512, gl + acc_slot(i) + acc_line(2 * jw, q, (lane >> 4) * 2 + ((lane >> 1) & 1)) + ((lane & 1) * 4 + ((lane >> 2) & 3)) * 16, gh,
                   gl + acc_slot(i) + acc_line(0, q, lane >> 3) + (lane & 7) * 16, gh);
        __syncwarp();
    }
    const uint32_t ls = pin(sb + (lane0 & 3) * 32);
#define UA(x) (l16 + fresh(x))
#pragma unroll 1
    for (int s = 0; s < NSEG - 1; s++) {
        const uint32_t par = (s & 1) * PAR;
        bar_sync(NB_TOK, 384);
#define SCORES()                                                                                                   \
    float x[2][3][4];                                                                                              \
    _Pragma("unroll") for (int t = 0; t < 3; t++) {                                                                \
        _Pragma("unroll") for (int j = 0; j < 4; j++) x[0][t][j] = x[1][t][j] = 0.f;                               \
        mma16(x[0][t], qf[t][0], qf[t][1], qf[t][2], qf[t][3], kf[t][0], kf[t][1]);                                \
        mma16(x[1][t], qf[t][0], qf[t][1], qf[t][2], qf[t][3], kf[t][2], kf[t][3]);                                \
    }                                                                                                              \
    bar_arrive(NB_G1 + (__float_as_uint(x[0][G1T][0]) & (l16 >> 31)), 256);                                         \
    const uint4 ta = lds128(UA(q * 512) + R_T0);                                                                            \
    float y[4];                                                                                                    \
    _Pragma("unroll") for (int j = 0; j < 4; j++)                                                                  \
        y[j] = ((x[j >> 1][0][j & 1] + x[j >> 1][0][2 + (j & 1)]) + (x[j >> 1][1][j & 1] + x[j >> 1][1][2 + (j & 1)])) + (x[j >> 1][2][j & 1] + x[j >> 1][2][2 + (j & 1)]);
        if (q < 2) {
            uint32_t qf[3][4], kf[3][4];
#pragma unroll
            for (int t = 0; t < 3; t++) ldsm4t(kf[t], UA(q * 512 + par) + R_K + t * 1536);
            bar_sync(NB_K, 384);
#pragma unroll
            for (int t = 0; t < 3; t++) ldsm4t(qf[t], l16 + R_QM + t * 512);
            SCORES()
            const uint32_t u0 = pack2(y[0], y[1]), u1 = pack2(y[2], y[3]);
            sta32(ta.x, u0, ta.y); sta32(ta.z, u0, ta.w);
            sta32(ta.x + 128, u1, ta.y); sta32(ta.z + 128, u1, ta.w);
            stsm2(UA(q * 256) + R_SC, u0, u1);
        } else if (q == 2) {
            if (s > 0 && s + 2 < NSEG) {
                const int xi = s - 1 - 3 * (((s - 1) * 43) >> 7);
                mbar_wait(bar + BME, s & 1);
                spin_until(clk() + XD);
                asm volatile("{.reg .pred p; elect.sync _|p, 0xffffffff;\n"
                             "@p mbarrier.arrive.expect_tx.shared::cta.b64 _, [%2], 36864;\n"
                             "@p cp.async.bulk.tensor.3d.shared::cluster.global.mbarrier::complete_tx::bytes.multicast::cluster [%0], [%1, {%3, %4, %5}], [%2], %6;}"
                             :: "r"(sb + xi * 36864 + c * 12288), "l"(xmap), "r"(bar + BX0 + xi * 8), "r"(0), "r"((s + 2) * 32), "r"(c * 3), "h"((uint16_t)7) : "memory");
            }
            uint32_t qf[3][4], kf[3][4];
            bar_sync(NB_K, 384);
#pragma unroll
            for (int t = 0; t < 3; t++) { ldsm4t(qf[t], l16 + R_QM + t * 512); ldsm4t(kf[t], UA(q * 512 + par) + R_K + t * 1536); }
            SCORES()
            const uint32_t u0 = pack2(y[0] + y[2], y[1] + y[3]);
            sta32(ta.x, u0, ta.y);
            sta32(ta.z, u0, ta.w);
            EV(4);
            stsm2(l16 + R_SC + 1792, u0, u0);
        } else {
            const uint4 ta = lds128(UA(q * 512) + R_T0);
            {
                const uint32_t vt = R_V + par + c * 2048, p0 = mapa(sb, c2 ? 0 : c + 1), p1 = mapa(sb, c == 0 ? 2 : c - 1);
                fence_smem_async();
                bulk_s2c_warp(p0 + vt, sb + vt, c2 ? 4096 : 2048, p0 + R_BAR + BVX + (s & 1) * 8);
                bulk_s2c_warp(p1 + vt, sb + vt, c2 ? 4096 : 2048, p1 + R_BAR + BVX + (s & 1) * 8);
            }
            {
                const int s3 = ((s + 1) * 43) >> 7;
                mbar_wait(bar + BX0 + (s + 1 - 3 * s3) * 8, s3 & 1);
                bar_arrive(NB_G1, 256);
            }
            sts32(sb + R_MISC + M_REF + 4, clock_offset());
            bar_sync(NB_K, 384);
            const uint32_t off = lds32(sb + R_MISC + M_REF + 4);
            const uint32_t t = off == 0x9e3779b9u ? 0u : clk();
            sts64(sb + R_MISC + M_REF, t, t + off);
            stg_rlx((uint32_t*)mkptr(ta.z + acc_slot(s), ta.y), ((t + off) & 0x3fffffu) | ((s + 1) << 22));
            mbar_wait(bar + BVX + (s & 1) * 8, (s >> 1) & 1);
        }
#undef SCORES
        bar_sync(NB_W1, 256);
        uint32_t vf[4][4];
        const uint32_t vo = par + q * 2048;
        float o0[4], o1[4], sum;
        uint2 tb;
        {
            uint32_t aw[5], bw[5], cw[5];
            ldsm4(aw, l16 + R_SC); aw[4] = tab1(l16 + R_SC + 1792);
            sts32(sb + R_MISC + M_SINK, aw[0] | aw[4]);
            mbar_wait(bar + BSC, s & 1);
            ldsm4(bw, l16 + R_SC + 512); ldsm4(cw, l16 + R_SC + 1024);
            { const uint2 t = tab2(l16 + R_SC + 1536); bw[4] = t.x; cw[4] = t.y; }
            EV(5);
            float x[10];
#pragma unroll
            for (int i = 0; i < 5; i++) { x[2 * i] = (bflo(aw[i]) + bflo(bw[i])) + bflo(cw[i]); x[2 * i + 1] = (bfhi(aw[i]) + bfhi(bw[i])) + bfhi(cw[i]); }
            float mx = fmaxf(fmaxf(fmaxf(fmaxf(x[0], x[1]), fmaxf(x[2], x[3])), fmaxf(fmaxf(x[4], x[5]), fmaxf(x[6], x[7]))), fmaxf(x[8], x[9]));
            const float m1 = __shfl_xor_sync(0xffffffffu, mx, 1), m2 = __shfl_xor_sync(0xffffffffu, mx, 2), m3 = __shfl_xor_sync(0xffffffffu, mx, 3);
            uint32_t vm[4];
            const uint32_t lv = l16 | (__float_as_uint(mx) & (l16 >> 31));
            ldsm4(vf[0], lv + fresh(vo) + R_V); ldsm4(vf[2], lv + fresh(vo) + R_V + 1024);
            ldsm4(vf[3], lv + fresh(vo) + R_V + 1536); ldsm4(vm, lv + fresh(q * 512 + par) + R_VM);
            tb = tab2(lv + fresh(q * 512 + (s & 3) * 2048) + R_T1);
            bar_arrive(NB_E0, 256);
            ldsm4(vf[1], lv + fresh(vo) + R_V + 512);
            mx = fmaxf(fmaxf(mx, m1), fmaxf(m2, m3));
            uint32_t pb[5];
            sum = 0.f;
#pragma unroll
            for (int i = 0; i < 5; i++) {
                const float e0 = ex2(x[2 * i] - mx), e1 = ex2(x[2 * i + 1] - mx);
                pb[i] = pack2(e0, e1);
                sum += e0 + e1;
            }
#pragma unroll
            for (int j = 0; j < 4; j++) o0[j] = o1[j] = 0.f;
            mma16(o0, vf[0][0], vf[0][1], vf[0][2], vf[0][3], pb[0], pb[1]);
            mma16(o1, vf[2][0], vf[2][1], vf[2][2], vf[2][3], pb[0], pb[1]);
            mma16(o0, vf[1][0], vf[1][1], vf[1][2], vf[1][3], pb[2], pb[3]);
            mma16(o1, vf[3][0], vf[3][1], vf[3][2], vf[3][3], pb[2], pb[3]);
            mma8(o0, vm[0], vm[1], pb[4]);
            mma8(o1, vm[2], vm[3], pb[4]);
        }
        asm volatile("stmatrix.sync.aligned.m8n8.x1.shared.b16 [%0], {%1};" :: "r"(l16 + R_Z), "r"(__float_as_uint(sum)) : "memory");
        const float4 s0 = lds128f(ls + R_Z), s1 = lds128f(ls + R_Z + 16);
        stsm4(UA(q * 512) + R_O8, pack2(o0[0], o0[1]), pack2(o0[2], o0[3]), pack2(o1[0], o1[1]), pack2(o1[2], o1[3]));
        EV(6);
        bar_sync(NB_W2, 128);
        uint32_t of[4][4];
#pragma unroll
        for (int i = 0; i < 4; i++) ldsm4t(of[i], l16 + R_O8 + i * 512);
        const float f0 = rcp_fast((s0.x + s0.y) + (s0.z + s0.w)), f1 = rcp_fast((s1.x + s1.y) + (s1.z + s1.w));
        float acc[3][2][4];
        uint32_t tie;
#pragma unroll
        for (int m = 0; m < 3; m++)
#pragma unroll
            for (int j = 0; j < 4; j++) acc[m][0][j] = acc[m][1][j] = 0.f;
#pragma unroll
        for (int i = 0; i < 4; i++)
#pragma unroll
            for (int m = 0; m < 3; m++)
#pragma unroll
                for (int e = 0; e < 2; e++) {
                    const int p = i ? 1 + (i + m + 2) % 3 : 0, kk = 2 * p + e;
                    if (i == 3 && m == 0 && e == 0)
                        tie = or3(or3(__float_as_uint(acc[0][0][0]), __float_as_uint(acc[0][1][0]), __float_as_uint(acc[1][0][0])),
                                  or3(__float_as_uint(acc[1][1][0]), __float_as_uint(acc[2][0][0]), __float_as_uint(acc[2][1][0])), __float_as_uint(f0) | __float_as_uint(f1));
                    mma16(acc[m][e], wo[m][kk][0], wo[m][kk][1], wo[m][kk][2], wo[m][kk][3], of[p][e * 2], of[p][e * 2 + 1]);
                }
        char* const gw = mkptr(tb.x, tb.y);
        bar_arrive(NB_GO + (tie & (l16 >> 31)), 384);
        const uint32_t one = lds32(sb + R_MISC + M_ONE);
        uint32_t wa[3], wb[3];
#pragma unroll
        for (int m = 0; m < 3; m++) {
            wa[m] = pack2(fmaf(acc[m][1][0], f0, acc[m][0][0] * f0), fmaf(acc[m][1][2], f0, acc[m][0][2] * f0));
            wb[m] = pack2(fmaf(acc[m][1][1], f1, acc[m][0][1] * f1), fmaf(acc[m][1][3], f1, acc[m][0][3] * f1));
        }
        red_b8(gw, wa[0], wa[1], wa[2], one); red_b8(gw + 1024, wb[0], wb[1], wb[2], one);
        const uint32_t t0 = clk();
        if (EVX(0)) EVV(7, t0);
        if (q < 2) {
            uint2 tg = lds64(sb + R_MISC + M_TGT);
            for (int n = 0; tg.y != s + 1; tg = lds64(sb + R_MISC + M_TGT)) if (++n > (1 << 26)) TRAP(1003);
            fine_until(t0 + max((int)(tg.x - t0), DMIN) - (q != side ? FE : 0) + (c ? DL : 0));
            asm volatile("{.reg .pred p; elect.sync _|p, 0xffffffff;\n"
                         "@p cp.async.bulk.tensor.5d.shared::cluster.global.mbarrier::complete_tx::bytes.multicast::cluster [%0], [%1, {%3, %4, %4, %4, %5}], [%2], %6;}"
                         :: "r"(sb + R_MEM + c * 4096 + q * 2048), "l"(amap + q), "r"(bar + (DL && c ? BML : BME)), "r"((s & 1) * 64), "r"(0), "r"((s & 2) * 64 + (c ? 6 + 2 * c : 0)), "h"((uint16_t)7) : "memory");
            EV(8);
        } else if (q == 2) {
            if (l16 == sb) {
                mbar_expect(bar + BME, DL ? 4096 : 12288);
                if (DL) mbar_expect(bar + BML, 8192);
                mbar_expect(bar + BSC, (c2 ? 1024 : 1536) + (s < NSEG - 2 ? 1280 : 0));
                mbar_expect(bar + BVX + 8 - (s & 1) * 8, c2 ? 4096 : 6144);
            }
        }
        EV(10);
    }
    bar_sync(NB_TOK, 384);
    bar_arrive(NB_K, 384);
    bar_arrive(NB_W1, 256);
    mbar_wait(bar + BSC, 1);
}

struct Maps { CUtensorMap x, acc[2]; };

__global__ void __launch_bounds__(384, 1)
rk_kernel(const __grid_constant__ Maps maps, const __nv_bfloat16* __restrict__ xraw, const __nv_bfloat16* __restrict__ mem0, const __nv_bfloat16* __restrict__ Wq,
          const __nv_bfloat16* __restrict__ Wk, const __nv_bfloat16* __restrict__ Wv, const __nv_bfloat16* __restrict__ Wo) {
    extern __shared__ __align__(1024) unsigned char smem[];
    const uint32_t sb = smem_u32(smem);
    const int tid = threadIdx.x;
    const int warp = __shfl_sync(0xffffffffu, tid >> 5, 0), q = warp & 3;
    const int h = blockIdx.x / 3;
    const uint32_t c = blockIdx.x - 3 * h;
    const uint32_t bar = sb + R_BAR;
    asm volatile("griddepcontrol.launch_dependents;");
    GT(0, 0);

    if (warp < 8) {
        asm volatile("setmaxnreg.inc.sync.aligned.u32 %0;" :: "n"(RP));
        const int wg = warp >> 2;
        const uint32_t lane = pin(tid & 31);
        uint32_t w[2][18][4];
        const uint32_t st = sb + R_STAGE + wg * 8192;
        const uint32_t la = st + (((lane >> 4) << 3) + (lane & 7)) * 128 + (((2 * q + ((lane >> 3) & 1)) ^ (lane & 7)) << 4);
        {
            const int t = tid & 127;
            const int r0 = t >> 3, ch = t & 7, p = (ch >> 1) ^ (2 * wg);
            const __nv_bfloat16* ta = c == 2 ? (p < 2 ? Wq : Wk) + 96 + (p & 1) * 16 : (p == 2 ? Wk : Wq) + c * 48 + min(p, 2) * 16;
            const __nv_bfloat16* tb = c == 2 ? Wv + 64 + p * 16 : (p >= 2 ? Wv + c * 32 + (p - 2) * 16 : Wk + c * 48 + p * 16);
            const size_t so = (size_t)(wg * 288 + r0) * HD + h * 128 + (ch & 1) * 8;
            const __nv_bfloat16* sp0 = ta + so;
            const __nv_bfloat16* sp1 = tb + so;
            const uint32_t dp = st + r0 * 128 + ((ch ^ (r0 & 7)) << 4);
#define ISSUE(KC, SLOT)                                                                                         \
    cp16(dp + (SLOT) * 16384, sp0 + (size_t)((KC) * 32) * HD); cp16(dp + (SLOT) * 16384 + 2048, sp0 + (size_t)((KC) * 32 + 16) * HD);               \
    cp16(dp + (SLOT) * 16384 + 4096, sp1 + (size_t)((KC) * 32) * HD); cp16(dp + (SLOT) * 16384 + 6144, sp1 + (size_t)((KC) * 32 + 16) * HD);        \
    cp_commit();
#pragma unroll
            for (int kc = 1; kc < 8; kc++) { ISSUE(kc, kc - 1) }
            ISSUE(0, 7)
            cluster_arrive_rlx(); cluster_wait();
#define LOADCHUNK(KC, SLOT, NWAIT)                                                   \
    cp_wait<NWAIT>(); bar_sync(NB_L0 + wg, 128);                                      \
    _Pragma("unroll") for (int i = 0; i < 4; i++) ldsm4t(w[i >> 1][(KC) * 2 + (i & 1)], la + (SLOT) * 16384 + i * 2048);
            LOADCHUNK(1, 0, 7)
            bar_sync(NB_L0 + wg, 128);
            ISSUE(8, 0)
            LOADCHUNK(2, 1, 7) LOADCHUNK(3, 2, 6) LOADCHUNK(4, 3, 5) LOADCHUNK(5, 4, 4) LOADCHUNK(6, 5, 3) LOADCHUNK(7, 6, 2) LOADCHUNK(0, 7, 1) LOADCHUNK(8, 0, 0)
#undef LOADCHUNK
#undef ISSUE
            fence_smem_async();
        }
        bar_sync(0, 384);
        cluster_arrive_rlx(); cluster_wait();

        GT(0, 1);
        if (c == 2) sts128(sb + (q == 3 ? R_QM + 1024 : R_K + 3072 + q * 512 + wg * PAR) + lane * 16, 0, 0, 0, 0);
        proj_loop(w, smem, sb, c, wg, q, lane);
    } else {
        asm volatile("setmaxnreg.dec.sync.aligned.u32 %0;" :: "n"(504 - 2 * RP));
        const uint32_t lane0 = pin(tid & 31);
        const uint32_t lane = lane0, n = blockIdx.x;
        volatile uint32_t* const misc = (volatile uint32_t*)(smem + R_MISC);
        const unsigned epoch = g_epoch[36 + n] + 1;
        uint32_t* const pa = (uint32_t*)((char*)g_acc + acc_blk(q & 1, n & 3) + 1536 + ((n >> 2) & 3) * 128 + ((n >> 4) & 1) * 32768 + (n >> 5) * 32);
        {
            const int t = tid - 256;
            if (t == 0) {
                mbar_init(bar + BX0, 1); mbar_init(bar + BX0 + 8, 1); mbar_init(bar + BX0 + 16, 1);
                mbar_init(bar + BSC, 1); mbar_init(bar + BME, 1); mbar_init(bar + BML, 1); mbar_arrive(bar + BME); mbar_arrive(bar + BML);
                mbar_init(bar + BVX, 1); mbar_init(bar + BVX + 8, 1);
                mbar_expect(bar + BSC, c == 2 ? 2304 : 2816); mbar_expect(bar + BVX, c == 2 ? 4096 : 6144);
                misc[M_TGT / 4 + 1] = 0; misc[M_ONE / 4] = 0x3f80u;
                misc[M_EPOCH / 4] = epoch; g_epoch[36 + n] = epoch;
                asm volatile("fence.mbarrier_init.release.cluster;" ::: "memory");
            }
            __syncwarp();
            cluster_arrive_rlx();
            uint32_t z;
            asm volatile("atom.relaxed.gpu.global.exch.b32 %0, [%1], %2;" : "=r"(z) : "l"((char*)g_acc + acc_slot(q) + acc_line(n >> 4, (n >> 2) & 3, n & 3) + lane * 4), "r"((lane & 3) == 3 ? EMPTY : 0) : "memory");
            if (lane < 2) stg_rlx((uint32_t*)((char*)g_acc + acc_slot(q) + acc_stamp(lane, n)), 0u);
            if (q < 2 && lane < 8) stg_rlx(pa + lane, 0u);
            uint32_t m0[3][6];
#pragma unroll
            for (int i = 0; i < 18; i++) m0[i / 6][i % 6] = __ldg((const uint32_t*)mem0 + (lane >> 2) * 288 + (q * 18 + i) * 4 + (lane & 3));
            const __nv_bfloat16* src = Wo + (size_t)h * 128 * DM;
#pragma unroll 4
            for (int i = 0; i < 24; i++) {
                const int idx = i * 128 + t, r = idx / 24, ch = idx - r * 24, qq = ch / 6, jq = (c + 3 - qq % 3) % 3;
                cp16(sb + R_WO + r * 384 + ((ch ^ ((r >> 1) & 3) * 2) << 4), src + r * DM + ((qq >> 1) * 36 + jq * 12 + (qq & 1) * 6 + ch - qq * 6) * 8);
            }
            cp_commit();
            cluster_wait();
            if (t == 0) {
                mbar_expect(bar + BX0, 36864);
                x_tma(sb + R_X0 + c * 12288, &maps.x, bar + BX0, 0, c * 3);
            }
            __syncwarp();
            {
                const uint32_t a = sb + R_MEM + (q & 1) * 6144 + (q >> 1) * 1024 + lane * 16;
#pragma unroll
                for (int i = 0; i < 6; i++) sts128(a + (i >> 1) * 2048 + (i & 1) * 512, m0[i >> 1][(i & 1) * 2], m0[i >> 1][(i & 1) * 2 + 1], m0[i >> 1][4 + (i & 1)], z & (lane >> 5));
            }
            asm volatile("fence.acq_rel.gpu;" ::: "memory");
            cp_wait<0>();
            bar_sync(NB_W2, 128);
            if (t == 0) stg_rlx(&g_pub[n], epoch);
            if (t == 32) asm volatile("cp.async.bulk.prefetch.L2.global [%0], 24576;" :: "l"((const char*)xraw + n * 24576) : "memory");
        }
        uint32_t wo[3][8][4];
        {
            const uint32_t g = lane >> 2, tq = lane & 3;
#pragma unroll
            for (int m = 0; m < 3; m++) {
                const uint32_t ch = 6 * q + (m < 2 ? (g >> 2) * 2 + m : 4 + (g >> 2));
                const uint32_t a = sb + R_WO + tq * 768 + ((ch ^ tq * 2) << 4) + (g & 3) * 4;
#pragma unroll
                for (int kk = 0; kk < 16; kk++) {
                    const uint32_t x = lds32(a + kk * 3072), y = lds32(a + kk * 3072 + 384);
                    wo[m][kk >> 1][(kk & 1) * 2] = __byte_perm(x, y, 0x5410);
                    wo[m][kk >> 1][(kk & 1) * 2 + 1] = __byte_perm(x, y, 0x7632);
                }
            }
        }
        bar_sync(0, 384);
        cluster_arrive_rlx(); cluster_wait();
        bar_arrive(NB_G1, 256);
        bar_arrive(NB_E0, 256);
        bar_arrive(NB_GO, 384);
        if (q >= 2 && lane == 0) {
            mbar_expect(bar + BX0 + (q - 1) * 8, 36864);
            x_tma(sb + (q - 1) * 36864 + c * 12288, &maps.x, bar + BX0 + (q - 1) * 8, (q - 1) * 32, c * 3);
        }
        __syncwarp();
        if (q < 2) { const uint32_t r = probe_rtt(pa); if (lane == 0) misc[M_PROBE / 4 + q] = r; }
        if (q == 3) {
            int it = 0;
            while (!__all_sync(0xffffffffu, ldg_rlx(&g_pub[lane]) == epoch && ldg_rlx(&g_pub[32 + lane]) == epoch && ldg_rlx(&g_pub[64 + lane]) == epoch))
                if (++it > (1 << 22)) TRAP(2000 + __LINE__);
        }
        bar_sync(NB_W2, 128);
        const uint32_t side = __shfl_sync(0xffffffffu, misc[M_PROBE / 4 + 1] < misc[M_PROBE / 4], 0);
        attn_loop(wo, &maps.x, maps.acc, smem, sb, c, q, lane0, side, (c + 3 - q % 3) % 3);
    }
    cluster_arrive_rlx(); cluster_wait();
    GT(0, 2);
}

constexpr int H_USTR = 32 * 144;
constexpr int H_U = 0;
constexpr int H_Z = H_U + 16 * H_USTR;
constexpr int H_W = H_Z + 256;
constexpr int H_WSTR = (2048 + 64) * 4;
constexpr int H_PAR = H_W + 8 * H_WSTR;
constexpr int H_KD = H_PAR + 4 * 2048;
constexpr int H_S4END = H_KD + 4 * 648 * 4;
constexpr int H_RING = 0;
constexpr int H_XCH = 131072;
constexpr int H_SX = 182272;
constexpr int H_QKV = 192512;
constexpr int H_AO = H_QKV + 30720;
constexpr int H_BAR = H_AO + 8192;
constexpr int H_SMEM = H_BAR + 256;
static_assert(H_S4END <= H_SX && H_SMEM <= 232448, "smem");
enum { HB_FULL = 0  , HB_XF = 64  , HB_XE = 80  , HB_QKV = 96  , HB_BUSY = 112, HB_TICK = 116, HB_WF = 128  , HB_WE = 192   };

#define WAIT_QUIET() for (int i_ = 0; i_ < 200; i_++) { const uint32_t a_ = __shfl_sync(0xffffffffu, gtime() - lds32(bar + HB_TICK), 0); if (a_ < QW || a_ > 3500) break; }
#define YIELD_TO_ATTENTION() for (int i_ = 0; i_ < 40 && __shfl_sync(0xffffffffu, lds32(bar + HB_BUSY), 0); i_++) {}
#define LOAD_U(T)                                                                                                                      \
    _Pragma("unroll 8") for (int i = (T); i < 4096; i += 256) {                                                                         \
        const int tt = i >> 1, hf = i & 1;                                                                                              \
        const uint4 v = __ldg((const uint4*)(u + (size_t)tt * DM + d0 + hf * 8));                                                       \
        unsigned char* p = smem + H_U + hf * 8 * H_USTR + (tt >> 6) * 144 + (tt & 63) * 2;                                              \
        const uint32_t ww[4] = {v.x, v.y, v.z, v.w};                                                                                    \
        _Pragma("unroll") for (int j = 0; j < 4; j++) {                                                                                 \
            *(uint16_t*)(p + (2 * j) * H_USTR) = (uint16_t)ww[j];                                                                       \
            *(uint16_t*)(p + (2 * j + 1) * H_USTR) = (uint16_t)(ww[j] >> 16);                                                           \
        }                                                                                                                               \
    }
#define WRITE_Y()                                                                                                                      \
    _Pragma("unroll 1") for (int i = tid, n_ = 0; i < 4096; i += 384, n_++) {                                                           \
        if ((n_ & 3) == 0) WAIT_QUIET()                                                                                                 \
        const int tt = i >> 1, hf = i & 1;                                                                                              \
        const unsigned char* p = smem + H_U + hf * 8 * H_USTR + (tt >> 6) * 144 + (tt & 63) * 2;                                       \
        uint32_t ww[4];                                                                                                                 \
        _Pragma("unroll") for (int j = 0; j < 4; j++)                                                                                   \
            ww[j] = (uint32_t)*(const uint16_t*)(p + (2 * j) * H_USTR) | ((uint32_t)*(const uint16_t*)(p + (2 * j + 1) * H_USTR) << 16); \
        *(uint4*)(out + (size_t)tt * OUTW + DM + d0 + hf * 8) = make_uint4(ww[0], ww[1], ww[2], ww[3]);                                 \
    }
DEVI void csq(float& x, float& y) { const float a = fmaf(x, x, -y * y), b = 2.f * x * y; x = a; y = b; }
DEVI uint32_t tf(float x) { return __float_as_uint(x) + 0x1000u; }
DEVI void cexp_turns(float l2mag, float turns, float& x, float& y) {
    const float m = ex2(l2mag), a = (turns - rintf(turns)) * 6.283185307179586f;
    x = m * __cosf(a); y = m * __sinf(a);
}

__global__ void __launch_bounds__(512, 1)
hk_kernel(const __nv_bfloat16* __restrict__ Wo, const __nv_bfloat16* __restrict__ u,
          const __nv_bfloat16* __restrict__ logA, const __nv_bfloat16* __restrict__ Aim, const __nv_bfloat16* __restrict__ Cre,
          const __nv_bfloat16* __restrict__ Cim, const __nv_bfloat16* __restrict__ logdt, const __nv_bfloat16* __restrict__ Dsk,
          __nv_bfloat16* __restrict__ out) {
    extern __shared__ __align__(1024) unsigned char smem[];
    const uint32_t sb = smem_u32(smem);
    const int tid = threadIdx.x, lane = tid & 31, warp = __shfl_sync(0xffffffffu, tid >> 5, 0), g = lane >> 2, tq = lane & 3;
    const int cta = blockIdx.x, nt = cta % 9, kg = cta / 9;
    const uint32_t bar = sb + H_BAR;
    const int d0 = cta * 16;
    if (tid == 0) {
        for (int i = 0; i < 8; i++) mbar_init(bar + HB_FULL + i * 8, 1);
        for (int i = 0; i < 2; i++) { mbar_init(bar + HB_XF + i * 8, 8); mbar_init(bar + HB_XE + i * 8, 4); }
        for (int i = 0; i < 16; i++) mbar_init(bar + HB_WF + i * 8, 1);
        mbar_init(bar + HB_QKV, 1); mbar_init(bar + HB_QKV + 8, 1); sts32(bar + HB_BUSY, 0); sts32(bar + HB_TICK, gtime() - 1000000);
        asm volatile("fence.proxy.async.shared::cta;" ::: "memory");
    }
    const unsigned epoch = g_epoch[cta] + 1;
    __syncthreads();
    if (tid == 0) g_epoch[cta] = epoch;
    if (warp < 8) {
        asm volatile("setmaxnreg.inc.sync.aligned.u32 176;");
        HEV(0); GT(96, 0);
        const int pr = warp & 3;
        float4* par = (float4*)(smem + H_PAR + pr * 2048);
        float* kd = (float*)(smem + H_KD + pr * 648 * 4);
        for (int i = lane; i < 64; i += 32) ((uint32_t*)(smem + H_W + (pr * 2 + (warp >> 2)) * H_WSTR))[i] = 0;
        HEV(1);
        if (!(HM & 1)) bar_sync(1, 384);
#pragma unroll 1
        for (int it = 0; it < ((HM & 1) ? (warp < 4 ? 3 : 5) : 0); it++) {
            const int rnd = min(it, 3), ch = rnd * 4 + pr, d = d0 + ch;
            uint32_t* wz = (uint32_t*)(smem + H_W + (pr * 2 + (rnd & 1)) * H_WSTR);
            if (warp >= 4 && it < 4) {
            const float dt = bf2f(__float2bfloat16(expf(bf2f(logdt[d]))));
#pragma unroll
            for (int n = lane; n < 128; n += 32) {
                const float ar = -bf2f(__float2bfloat16(expf(bf2f(logA[d * 128 + n])))) * dt, ai = bf2f(Aim[d * 128 + n]) * dt;
                par[n] = make_float4(ar * 1.4426950408889634f, ai * 0.15915494309189535f, 2.f * bf2f(Cre[d * 128 + n]) * dt, 2.f * bf2f(Cim[d * 128 + n]) * dt);
            }
            __syncwarp();
            float kacc[5][4], klast = 0.f;
#pragma unroll
            for (int i = 0; i < 5; i++) kacc[i][0] = kacc[i][1] = kacc[i][2] = kacc[i][3] = 0.f;
            const float fa = (float)g, fb = (float)(g + 8);
            float4 pn[4];
#pragma unroll
            for (int i = 0; i < 4; i++) pn[i] = par[4 * i + tq];
#pragma unroll 4
            for (int ks = 0; ks < 32; ks++) {
                const float4 p = pn[ks & 3];
                pn[ks & 3] = par[(4 * ks + 16 + tq) & 127];
                float ax, ay, bx, by;
                cexp_turns(p.x * fa, p.y * fa, ax, ay);
                cexp_turns(p.x * fb, p.y * fb, bx, by);
                uint32_t F[4][4];
#pragma unroll
                for (int r = 0; r < 4; r++) {
                    F[r][0] = tf(ax); F[r][1] = tf(bx); F[r][2] = tf(ay); F[r][3] = tf(by);
                    csq(ax, ay); csq(bx, by);
                }
                mma_tf32(kacc[0], F[0][0], F[0][1], F[0][2], F[0][3], tf(fmaf(p.z, ax, -p.w * ay)), tf(-fmaf(p.z, ay, p.w * ax)));
#pragma unroll
                for (int r = 0; r < 4; r++) {
                    mma_tf32(kacc[r + 1], F[r][0], F[r][1], F[r][2], F[r][3], tf(fmaf(p.z, bx, -p.w * by)), tf(-fmaf(p.z, by, p.w * bx)));
                    csq(bx, by);
                }
                klast += fmaf(p.z, bx, -p.w * by);
            }
#pragma unroll
            for (int i = 0; i < 5; i++) {
                kd[i * 128 + 32 * tq + g] = kacc[i][0]; kd[i * 128 + 32 * tq + 16 + g] = kacc[i][1];
                kd[i * 128 + 32 * tq + g + 8] = kacc[i][2]; kd[i * 128 + 32 * tq + 24 + g] = kacc[i][3];
            }
            klast += __shfl_xor_sync(0xffffffffu, klast, 1);
            klast += __shfl_xor_sync(0xffffffffu, klast, 2);
            if (lane == 0) kd[640] = klast;
            __syncwarp();
            if (rnd >= 2) mbar_wait(bar + HB_WE + (pr * 2 + (rnd & 1)) * 8, 0);
#define RIDX(l, r) ((r) * 128 + (((l) + (1 << (r) >> 1) - 1 + (((l) >> (r)) & 1)) >> (r)))
#pragma unroll
            for (int x0 = 0; x0 < 256; x0 += 32) wz[64 + x0 + lane] = pack2(kd[x0 + lane], x0 + lane ? kd[x0 + lane - 1] : 0.f);
#pragma unroll
            for (int r = 1; r < 4; r++) {
                const int l0 = (128 << r) + lane;
                const float* k0 = kd + RIDX(l0, r);
                const float* k1 = kd + RIDX(l0 - 1, r);
#pragma unroll 8
                for (int i = 0; i < (4 << r); i++) wz[64 + l0 + 32 * i] = pack2(k0[i * (32 >> r)], k1[i * (32 >> r)]);
            }
#undef RIDX
            __syncwarp();
            if (lane == 0) wz[64 + 256] = pack2(kd[256], kd[255]);
            __syncwarp();
            if (lane == 0) mbar_arrive(bar + HB_WF + (pr * 2 + (rnd & 1)) * 8);
            if (rnd == 0) bar_sync(1, 384);
            continue;
            }
            if (it == 0) { LOAD_U(tid) bar_sync(1, 384); }
            mbar_wait(bar + HB_WF + (pr * 2 + (rnd & 1)) * 8, rnd >> 1);
            if (it == 0) HEV(2);
            float acc[4][4][4];
#pragma unroll
            for (int G = 0; G < 4; G++)
#pragma unroll
                for (int i = 0; i < 4; i++) acc[G][i][0] = acc[G][i][1] = acc[G][i][2] = acc[G][i][3] = 0.f;
            const uint32_t ub = sb + H_U + ch * H_USTR + (lane >> 3) * 16, zb = sb + H_Z + (lane >> 3) * 16;
            const uint32_t* wp = wz + 64 - 56 + g - 2 * tq;
            uint32_t Pn[15];
#pragma unroll
            for (int k = 0; k < 15; k++) Pn[k] = wp[8 * k];
            uint32_t bn[2][4];
            ldsm4(bn[0], ub + (24 + (lane & 7)) * 144); ldsm4(bn[1], ub + (24 + (lane & 7)) * 144 + 64);
#define CONV_RANGE(G0)                                                                                                  \
    _Pragma("unroll 1") for (int s = 8 * (G0); s < 8 * (G0) + 8; s++) {                                                  \
        uint32_t P[15], b[4][2][4];                                                                                      \
        _Pragma("unroll") for (int k = 0; k < 4; k++) { b[3][0][k] = bn[0][k]; b[3][1][k] = bn[1][k]; }                  \
        _Pragma("unroll") for (int G = 2; G >= (G0); G--) {                                                              \
            const int cidx = 8 * G + (lane & 7) - s;                                                                     \
            const uint32_t ba = (G > (G0) || cidx >= 0) ? ub + cidx * 144 : zb;                                          \
            ldsm4(b[G][0], ba); ldsm4(b[G][1], ba + 64);                                                                 \
        }                                                                                                                \
        {                                                                                                                \
            const int cidx = 23 + (lane & 7) - s;                                                                        \
            const uint32_t ba = cidx >= 0 ? ub + cidx * 144 : zb;                                                        \
            ldsm4(bn[0], ba); ldsm4(bn[1], ba + 64);                                                                     \
        }                                                                                                                \
        _Pragma("unroll") for (int k = 0; k < 15; k++) P[k] = Pn[k];                                                     \
        _Pragma("unroll") for (int k = 0; k < 7; k++) Pn[k] = P[k + 8];                                                  \
        _Pragma("unroll") for (int k = 7; k < 15; k++) Pn[k] = wp[64 * min(s + 1, 31) + 8 * k];                          \
        _Pragma("unroll") for (int G = 3; G >= (G0); G--)                                                                \
            _Pragma("unroll") for (int j = 0; j < 4; j++)                                                                \
                _Pragma("unroll") for (int i = 0; i < 4; i++) {                                                          \
                    const int k = 2 * (i - j) + 7;                                                                       \
                    mma16(acc[G][i], P[k], P[k + 1], P[k - 1], P[k], b[G][j >> 1][(j & 1) * 2], b[G][j >> 1][(j & 1) * 2 + 1]); \
                }                                                                                                        \
    }
            CONV_RANGE(0) CONV_RANGE(1) CONV_RANGE(2) CONV_RANGE(3)
#undef CONV_RANGE
            __syncwarp();
            if (lane == 0) mbar_arrive(bar + HB_WE + (pr * 2 + (rnd & 1)) * 8);
            if (it == 0) HEV(3);
            const float dsk = bf2f(Dsk[d]);
#pragma unroll
            for (int G = 0; G < 4; G++)
#pragma unroll
                for (int i = 0; i < 4; i++)
#pragma unroll
                    for (int j = 0; j < 4; j++) {
                        __nv_bfloat16* p = (__nv_bfloat16*)(smem + H_U + ch * H_USTR + (8 * G + 2 * tq + (j & 1)) * 144 + (16 * i + g + (j >> 1) * 8) * 2);
                        const float y = bf2f(__float2bfloat16(acc[G][i][j])), sk = bf2f(__float2bfloat16(bf2f(*p) * dsk));
                        *p = __float2bfloat16(y + sk);
                    }
        }
        bar_sync(2, 384);
        WRITE_Y()
        bar_sync(2, 384);
        HEV(4); GT(96, 1);
        const int wg = warp >> 2, q = warp & 3, t = tid & 127;
        uint32_t w[32][4];
        {
            const __nv_bfloat16* src = Wo + (size_t)(kg * 1024 + wg * 512) * DM + nt * 64;
            const uint32_t st = sb + H_RING + wg * 65536;
            const int r0 = t >> 3, ch = t & 7;
            WAIT_QUIET()
#pragma unroll 4
            for (int i = 0; i < 32; i++) cp16(st + (i * 16 + r0) * 128 + ((ch ^ ((r0 >> 3) * 2 + (i & 1) * 4 + (r0 & 1))) << 4), src + (size_t)(i * 16 + r0) * DM + ch * 8);
            cp_commit();
            cp_wait<0>();
            bar_sync(5 + wg, 128);
#pragma unroll
            for (int i = 0; i < 32; i++) {
                const int tt = (i & 1) * 2 + (lane >> 4), row = (i >> 1) * 32 + ((lane >> 1) & 3) * 8 + 2 * tt + (lane & 1);
                ldsm4t(w[i], st + row * 128 + (((2 * q + ((lane >> 3) & 1)) ^ (lane & 7)) << 4));
            }
        }
        asm volatile("fence.proxy.async.shared::cta;" ::: "memory");
        bar_sync(3, 384);
        HEV(5);
#pragma unroll 1
        for (int s = 0; s < ((HM & 4) ? NSEG : 0); s++) {
            const int stg = s & 1, ph = (s >> 1) & 1;
            if (warp == 0) HS(0);
            float d[16];
            const uint64_t desc = desc_sw128(sb + H_RING + stg * 65536 + wg * 32768);
            mbar_wait(bar + HB_FULL + (stg * 4 + wg * 2) * 8, ph);
            YIELD_TO_ATTENTION()
            if (warp == 0) HS(1);
            wg_fence();
            wgmma32<0>(d, w[0], desc);
#pragma unroll
            for (int i = 1; i < 16; i++) wgmma32<1>(d, w[i], desc + (uint64_t)(((i >> 2) * 4096 + (i & 3) * 32) >> 4));
            wg_commit();
            mbar_wait(bar + HB_FULL + (stg * 4 + wg * 2 + 1) * 8, ph);
            YIELD_TO_ATTENTION()
            wg_fence();
#pragma unroll
            for (int i = 16; i < 32; i++) wgmma32<1>(d, w[i], desc + (uint64_t)(((i >> 2) * 4096 + (i & 3) * 32) >> 4));
            wg_commit();
            if (s >= 2) mbar_wait(bar + HB_XE + (s & 1) * 8, ((s >> 1) - 1) & 1);
            wg_wait0();
            if (warp == 0) HS(2);
#pragma unroll
            for (int j = 0; j < 4; j++) sts128f(sb + H_XCH + (s & 1) * 16384 + wg * 8192 + j * 2048 + t * 16, d[4 * j], d[4 * j + 1], d[4 * j + 2], d[4 * j + 3]);
            __syncwarp();
            if (lane == 0) mbar_arrive(bar + HB_XF + (s & 1) * 8);
        }
    } else if (warp < 12) {
        asm volatile("setmaxnreg.dec.sync.aligned.u32 56;");
        const int t2 = tid - 256;
        if (t2 < 64) ((uint32_t*)(smem + H_Z))[t2] = 0;
        LOAD_U(t2 + 128)
        bar_arrive(1, 384);
        bar_sync(2, 384);
        WRITE_Y()
        bar_arrive(2, 384);
        bar_sync(3, 384);
        {
            const int q = warp & 3, t = tid & 127;
            int issued = 0, ready = 0;
#pragma unroll 1
            for (int s = 0; s < ((HM & 4) ? NSEG : 0); s++) {
                if (q == 0) {
                    int it = 0;
                    while (issued < min(s + 2, NSEG)) {
                        if (ready <= issued) {
                            unsigned v = epoch;
                            if (issued + (lane >> 3) < NSEG)
                                asm volatile("ld.acquire.gpu.global.u32 %0, [%1];" : "=r"(v) : "l"(&g_oflag[issued + (lane >> 3)][kg * 8 + (lane & 7)][0]) : "memory");
                            ready = issued + (__ffs(~__ballot_sync(0xffffffffu, v == epoch) | 0) ? (__ffs(~__ballot_sync(0xffffffffu, v == epoch)) - 1) >> 3 : 4);
                            if (++it > (1 << 24)) TRAP(2000 + __LINE__);
                        }
                        if (ready > issued) {
                            if (issued > s) { const uint32_t a_ = __shfl_sync(0xffffffffu, gtime() - lds32(bar + HB_TICK), 0); if (a_ >= QW && a_ <= 3500) break; }
                            else WAIT_QUIET()
                            if (lane == 0) {
                                asm volatile("fence.proxy.async.global;" ::: "memory");
#pragma unroll
                                for (int i = 0; i < 4; i++) {
                                    const int p = (i & 1) * 2 + (i >> 1);
                                    const uint32_t fb = bar + HB_FULL + ((issued & 1) * 4 + p) * 8;
                                    mbar_expect(fb, 16384);
                                    bulk_g2s(sb + H_RING + (issued & 1) * 65536 + p * 16384, (const char*)g_o + (size_t)(issued * 64 + kg * 16 + p * 4) * 4096, 16384, fb);
                                }
                            }
                            __syncwarp();
                            issued++;
                        } else if (issued > s) break;
                    }
                }
                const uint32_t tag = s + 1, xa = sb + H_XCH + (s & 1) * 16384 + t * 16;
                mbar_wait(bar + HB_XF + (s & 1) * 8, (s >> 1) & 1);
                float4 keep;
#pragma unroll
                for (int i = 0; i < 4; i++) {
                    const int j = (kg + 1 + i) & 3;
                    const float4 a = lds128f(xa + j * 2048), b = lds128f(xa + 8192 + j * 2048);
                    keep = make_float4(a.x + b.x, a.y + b.y, a.z + b.z, a.w + b.w);
                    if (i < 3)
                        asm volatile("st.relaxed.gpu.global.v4.u32 [%0], {%1,%2,%3,%4};" :: "l"(&g_part[s & 3][nt][j][kg][t]),
                                     "r"((__float_as_uint(keep.x) & ~127u) | tag), "r"((__float_as_uint(keep.y) & ~127u) | tag),
                                     "r"((__float_as_uint(keep.z) & ~127u) | tag), "r"((__float_as_uint(keep.w) & ~127u) | tag) : "memory");
                }
                __syncwarp();
                if (lane == 0) mbar_arrive(bar + HB_XE + (s & 1) * 8);
                if (warp == 8) HS(3);
                uint4 v[3];
                int it = 0;
                while (true) {
                    uint32_t bad = 0;
#pragma unroll
                    for (int i = 0; i < 3; i++) v[i] = ldg_rlx4(&g_part[s & 3][nt][kg][(kg + 1 + i) & 3][t]);
#pragma unroll
                    for (int i = 0; i < 3; i++) bad |= (v[i].x ^ tag) | (v[i].y ^ tag) | (v[i].z ^ tag) | (v[i].w ^ tag);
                    if (!__any_sync(0xffffffffu, bad & 127u)) break;
                    if (++it > (1 << 24)) TRAP(2000 + __LINE__);
                }
#pragma unroll
                for (int i = 0; i < 3; i++) {
                    keep.x += __uint_as_float(v[i].x); keep.y += __uint_as_float(v[i].y);
                    keep.z += __uint_as_float(v[i].z); keep.w += __uint_as_float(v[i].w);
                }
                if (warp == 8) HS(4);
                uint32_t a, b;
                asm volatile("movmatrix.sync.aligned.m8n8.trans.b16 %0, %1;" : "=r"(a) : "r"(pack2(keep.x, keep.y)));
                asm volatile("movmatrix.sync.aligned.m8n8.trans.b16 %0, %1;" : "=r"(b) : "r"(pack2(keep.z, keep.w)));
                const uint32_t x = __shfl_sync(0xffffffffu, a, (lane & 28) | ((tq & 1) * 2)), y = __shfl_sync(0xffffffffu, a, (lane & 28) | ((tq & 1) * 2 + 1));
                const uint32_t z = __shfl_sync(0xffffffffu, b, (lane & 28) | ((tq & 1) * 2)), w_ = __shfl_sync(0xffffffffu, b, (lane & 28) | ((tq & 1) * 2 + 1));
                *(uint2*)(out + (size_t)(s * 32 + kg * 8 + g) * OUTW + nt * 64 + q * 16 + tq * 4) = tq < 2 ? make_uint2(x, y) : make_uint2(z, w_);
            }
        }
        asm volatile("griddepcontrol.wait;" ::: "memory");
    } else {
        asm volatile("setmaxnreg.dec.sync.aligned.u32 104;");
        const int hd = kg * 8 + (nt & 7), mt = warp & 1, ch = (warp >> 1) & 1;
        const uint32_t qk = sb + H_QKV, vb = qk + 20480 + ch * 4096;
        const int dg = 16 * mt + g - 2 * tq;
        unsigned nextv = 0;
#pragma unroll 1
        for (int s = 0; s < NSEG && (HM & 2); s++) {
            if (warp == 12) {
                int it = 0;
                while (!__all_sync(0xffffffffu, nextv == epoch)) {
                    asm volatile("ld.acquire.gpu.global.u32 %0, [%1];" : "=r"(nextv) : "l"(&g_qflag[s][hd][(lane % 3) * 8]) : "memory");
                    if (++it > (1 << 24)) TRAP(2000 + __LINE__);
                }
                HS(5);
                if (lane == 0 && nt < 8) {
                    asm volatile("fence.proxy.async.global;" ::: "memory");
                    mbar_expect(bar + HB_QKV, 20480);
                    bulk_g2s(qk, g_qkv + (size_t)(s * 32 + hd) * 30720, 20480, bar + HB_QKV);
                    mbar_expect(bar + HB_QKV + 8, 10240);
                    bulk_g2s(qk + 20480, g_qkv + (size_t)(s * 32 + hd) * 30720 + 20480, 10240, bar + HB_QKV + 8);
                }
                if (it > 1 || s >= NSEG - 2) sts32(bar + HB_TICK, gtime() - (s >= NSEG - 2 ? 1000000 : 0));
                nextv = 0;
                if (s + 1 < NSEG) asm volatile("ld.acquire.gpu.global.u32 %0, [%1];" : "=r"(nextv) : "l"(&g_qflag[s + 1][hd][(lane % 3) * 8]) : "memory");
                if (nt < 8) sts32(bar + HB_BUSY, 1);
            }
            if (nt == 8) continue;
            mbar_wait(bar + HB_QKV, s & 1);
            float x[6][4];
            {
                const uint32_t l16 = qk + lane * 16;
#pragma unroll
                for (int b = 0; b < 6; b++) x[b][0] = x[b][1] = x[b][2] = x[b][3] = 0.f;
#pragma unroll
                for (int i = 0; i < 4; i++) {
                    constexpr int QO[8] = {0, 1024, 2048, 7680, 8704, 9728, 15360, 16384}, KO[8] = {3072, 4608, 6144, 10752, 12288, 13824, 17408, 18944};
                    uint32_t qf[4], kf[3][4];
                    ldsm4t(qf, l16 + (ch ? QO[4 + i] : QO[i]) + mt * 512);
                    const uint32_t ka = l16 + (ch ? KO[4 + i] : KO[i]);
#pragma unroll
                    for (int b = 0; b < 3; b++) ldsm4t(kf[b], ka + b * 512);
#pragma unroll
                    for (int b = 0; b < 6; b++) mma16(x[b], qf[0], qf[2], qf[1], qf[3], kf[b >> 1][(b & 1) * 2], kf[b >> 1][(b & 1) * 2 + 1]);
                }
#pragma unroll
                for (int j = 0; j < 4; j++) x[4][j] += x[5][j];
                const uint32_t xa = sb + H_SX + lane * 16;
#pragma unroll
                for (int b = 0; b < 5; b++) sts128f(xa + (warp & 3) * 2560 + b * 512, x[b][0], x[b][1], x[b][2], x[b][3]);
                bar_sync(8, 128);
#pragma unroll
                for (int b = 0; b < 5; b++) {
                    const float4 u = lds128f(xa + ((warp & 3) ^ 2) * 2560 + b * 512);
                    x[b][0] += u.x; x[b][1] += u.y; x[b][2] += u.z; x[b][3] += u.w;
                }
            }
            mbar_wait(bar + HB_QKV + 8, s & 1);
            uint32_t vm[2][4], vx[4][4];
            ldsm4(vm[0], qk + 28672 + ch * 1024 + lane * 16); ldsm4(vm[1], qk + 28672 + ch * 1024 + 512 + lane * 16);
#pragma unroll
            for (int j = 0; j < 4; j++) ldsm4(vx[j], vb + (j >> 1) * 1024 + (lane >> 3) * 256 + (j & 1) * 128 + (lane & 7) * 16);
            float m0 = fmaxf(x[4][0], x[4][1]), m1 = fmaxf(x[4][2], x[4][3]);
#pragma unroll
            for (int b = 0; b < 4; b++) {
                if (8 * b > dg) x[b][0] = NEG;
                if (8 * b + 1 > dg) x[b][1] = NEG;
                if (8 * b - 8 > dg) x[b][2] = NEG;
                if (8 * b - 7 > dg) x[b][3] = NEG;
                m0 = fmaxf(m0, fmaxf(x[b][0], x[b][1])); m1 = fmaxf(m1, fmaxf(x[b][2], x[b][3]));
            }
            m0 = fmaxf(m0, __shfl_xor_sync(0xffffffffu, m0, 1)); m1 = fmaxf(m1, __shfl_xor_sync(0xffffffffu, m1, 1));
            m0 = fmaxf(m0, __shfl_xor_sync(0xffffffffu, m0, 2)); m1 = fmaxf(m1, __shfl_xor_sync(0xffffffffu, m1, 2));
            float l0 = 0.f, l1 = 0.f;
            uint32_t pa[5][2];
#pragma unroll
            for (int b = 0; b < 5; b++) {
                const float e0 = ex2(x[b][0] - m0), e1 = ex2(x[b][1] - m0), e2 = ex2(x[b][2] - m1), e3 = ex2(x[b][3] - m1);
                l0 += e0 + e1; l1 += e2 + e3;
                pa[b][0] = pack2(e0, e1); pa[b][1] = pack2(e2, e3);
            }
            l0 += __shfl_xor_sync(0xffffffffu, l0, 1); l1 += __shfl_xor_sync(0xffffffffu, l1, 1);
            l0 += __shfl_xor_sync(0xffffffffu, l0, 2); l1 += __shfl_xor_sync(0xffffffffu, l1, 2);
            l0 = rcp_fast(l0); l1 = rcp_fast(l1);
            float o[8][4];
#pragma unroll
            for (int j = 0; j < 8; j++) { o[j][0] = o[j][1] = o[j][2] = o[j][3] = 0.f; mma8(o[j], pa[4][0], pa[4][1], vm[j >> 2][j & 3]); }
#pragma unroll
            for (int grp = 0; grp < 2; grp++) {
                uint32_t vy[4][4];
                if (grp == 0) {
#pragma unroll
                    for (int j = 0; j < 4; j++) ldsm4(vy[j], vb + 2048 + (j >> 1) * 1024 + (lane >> 3) * 256 + (j & 1) * 128 + (lane & 7) * 16);
                }
#pragma unroll
                for (int j = 0; j < 4; j++) mma16(o[4 * grp + j], pa[0][0], pa[0][1], pa[1][0], pa[1][1], vx[j][0], vx[j][1]);
#pragma unroll
                for (int j = 0; j < 4; j++) mma16(o[4 * grp + j], pa[2][0], pa[2][1], pa[3][0], pa[3][1], vx[j][2], vx[j][3]);
                if (grp == 0) {
#pragma unroll
                    for (int j = 0; j < 4; j++) { vx[j][0] = vy[j][0]; vx[j][1] = vy[j][1]; vx[j][2] = vy[j][2]; vx[j][3] = vy[j][3]; }
                }
            }
#pragma unroll
            for (int grp = 0; grp < 2; grp++) {
                const uint32_t oa = sb + H_AO + ch * 4096 + (16 * mt + g) * 128 + (((grp * 4 + tq) ^ g) << 4);
                const float (*p)[4] = &o[4 * grp];
                sts128(oa, pack2(p[0][0] * l0, p[0][1] * l0), pack2(p[1][0] * l0, p[1][1] * l0), pack2(p[2][0] * l0, p[2][1] * l0), pack2(p[3][0] * l0, p[3][1] * l0));
                sts128(oa + 1024, pack2(p[0][2] * l1, p[0][3] * l1), pack2(p[1][2] * l1, p[1][3] * l1), pack2(p[2][2] * l1, p[2][3] * l1), pack2(p[3][2] * l1, p[3][3] * l1));
            }
            if (warp == 12) sts32(bar + HB_BUSY, 0);
            asm volatile("fence.proxy.async.shared::cta;" ::: "memory");
            bar_sync(8, 128);
            if (warp == 13) {
                if (lane == 0) {
                    asm volatile("cp.async.bulk.global.shared::cta.bulk_group [%0], [%1], 8192;" :: "l"((char*)g_o + (size_t)(s * 64 + hd * 2) * 4096), "r"(sb + H_AO) : "memory");
                    asm volatile("cp.async.bulk.commit_group;" ::: "memory");
                    asm volatile("cp.async.bulk.wait_group 0;" ::: "memory");
                    stg_rlx(&g_oflag[s][hd][0], epoch);
                }
                __syncwarp();
                HS(6);
            }
        }
    }
}

typedef CUresult (*EncodeFn)(CUtensorMap*, CUtensorMapDataType, cuuint32_t, void*, const cuuint64_t*, const cuuint64_t*, const cuuint32_t*,
                             const cuuint32_t*, CUtensorMapInterleave, CUtensorMapSwizzle, CUtensorMapL2promotion, CUtensorMapFloatOOBfill);

static void make_map(EncodeFn enc, CUtensorMap* m, void* base, int width, int boxchunks) {
    cuuint64_t dims[3] = {64, 2048, (cuuint64_t)(width / 64)};
    cuuint64_t strides[2] = {(cuuint64_t)width * 2, 128};
    cuuint32_t box[3] = {64, 32, (cuuint32_t)boxchunks};
    cuuint32_t es[3] = {1, 1, 1};
    enc(m, CU_TENSOR_MAP_DATA_TYPE_BFLOAT16, 3, base, dims, strides, box, es, CU_TENSOR_MAP_INTERLEAVE_NONE, CU_TENSOR_MAP_SWIZZLE_128B,
        CU_TENSOR_MAP_L2_PROMOTION_L2_256B, CU_TENSOR_MAP_FLOAT_OOB_FILL_NONE);
}

extern "C" void kernel_launch(void* const* d_in, const int* in_sizes, int n_in, void* d_out, int out_size) {
    typedef const __nv_bfloat16* P;
    static EncodeFn enc = nullptr;
    if (!enc) {
        void* fn = nullptr;
        cudaDriverEntryPointQueryResult st;
        cudaGetDriverEntryPoint("cuTensorMapEncodeTiled", &fn, cudaEnableDefault, &st);
        enc = (EncodeFn)fn;
        cudaFuncSetAttribute(rk_kernel, cudaFuncAttributeMaxDynamicSharedMemorySize, R_SMEM);
        cudaFuncSetAttribute(hk_kernel, cudaFuncAttributeMaxDynamicSharedMemorySize, H_SMEM);
    }
    Maps maps;
    make_map(enc, &maps.x, d_in[0], DM, 3);
    {
        void* acc = nullptr;
        cudaGetSymbolAddress(&acc, g_acc);
        for (int m = 0; m < 2; m++) {
            cuuint64_t dims[5] = {128, 2, 2, 2, 144};
            cuuint64_t strides[4] = {(cuuint64_t)(m ? 4096 : 12288), 1024, 16384, 256};
            cuuint32_t box[5] = {64, 2, 2, 2, 2}, es[5] = {1, 1, 1, 1, 1};
            enc(&maps.acc[m], CU_TENSOR_MAP_DATA_TYPE_BFLOAT16, 5, (char*)acc + m * 4096, dims, strides, box, es, CU_TENSOR_MAP_INTERLEAVE_NONE,
                CU_TENSOR_MAP_SWIZZLE_NONE, CU_TENSOR_MAP_L2_PROMOTION_NONE, CU_TENSOR_MAP_FLOAT_OOB_FILL_NONE);
        }
    }

    cudaLaunchConfig_t cfg = {};
    cudaLaunchAttribute at[1];
    cfg.gridDim = dim3(96); cfg.blockDim = dim3(384); cfg.dynamicSmemBytes = R_SMEM; cfg.stream = cudaStreamPerThread;
    at[0].id = cudaLaunchAttributeClusterDimension; at[0].val.clusterDim.x = 3; at[0].val.clusterDim.y = 1; at[0].val.clusterDim.z = 1;
    cfg.attrs = at; cfg.numAttrs = 1;
    cudaLaunchKernelEx(&cfg, rk_kernel, maps, (P)d_in[0], (P)d_in[1], (P)d_in[2], (P)d_in[3], (P)d_in[4], (P)d_in[5]);

    cfg.gridDim = dim3(36); cfg.blockDim = dim3(512); cfg.dynamicSmemBytes = H_SMEM;
    at[0].id = cudaLaunchAttributeProgrammaticStreamSerialization; at[0].val.programmaticStreamSerializationAllowed = 1;
    cudaLaunchKernelEx(&cfg, hk_kernel, (P)d_in[5], (P)d_in[7], (P)d_in[8], (P)d_in[9], (P)d_in[10], (P)d_in[11], (P)d_in[12], (P)d_in[13],
                       (__nv_bfloat16*)d_out);
}
```

```cpp
#include <cuda_runtime.h>
#include <cuda_bf16.h>
#include <cuda_fp16.h>
#include <cuda.h>
#include <stdint.h>

#define DEVI __device__ __forceinline__

#define NEG __int_as_float(0xff800000)
constexpr int DM = 576, NSEG = 64, HD = 4096, OUTW = 1152;

#define HM 7
#define QW 4000
#define NPROBE 4
#define CT 1500
#define FE 85
#define DL 0
#define DMIN 150
#define DMAX 4000
#define BACKOFF 200
#define LW 4
#define TIE 0
#define C2ADJ 80
#define DST 260
#define VFE 0
#define EW 0
#define LB 12
#define NTR 3
#define RP 176
#define NW2 3
#define KT 4
#define DDUMP 520
#define DPUSH 300
#define GOE 1
#define LDM 0
#define XD 150
#define G1T 0
#define F0T 14
#define F1T 16
#define SUMV 0
#define UDLY 6000
#define YDLY 300
#define PPT 28
#define N1 8

__device__ __align__(1024) __nv_bfloat16 g_o[2048 * HD];
__device__ __align__(65536) uint32_t g_acc[16384];
__device__ __align__(128) unsigned g_pub[96];
__device__ __align__(128) uint2 g_part[4][9][4][4][128];
__device__ __align__(1024) unsigned char g_qkv[(size_t)NSEG * 32 * 30720];
__device__ __align__(128) unsigned g_qflag[NSEG][32][32];
__device__ __align__(128) unsigned g_oflag[NSEG][32][8];
__device__ unsigned g_epoch[36 + 96];
#define EV(i)
#define EVV(i, v)
#define EVX(i) 0
#define EVADD(i, v)
#define HS(i)
#define HEV(i)
#define GT(b, i)

#define TRAP(code) __trap()
#define LOC(v)
DEVI uint32_t smem_u32(const void* p) { return (uint32_t)__cvta_generic_to_shared(p); }
DEVI uint32_t clk() { uint64_t t; asm volatile("mov.u64 %0, %%clock64;" : "=l"(t) :: "memory"); return (uint32_t)t; }
DEVI uint32_t gtime() { uint64_t t; asm volatile("mov.u64 %0, %%globaltimer;" : "=l"(t) :: "memory"); return (uint32_t)t; }
DEVI void spin_until(uint32_t t) { while ((int)(clk() - t) < 0) {} }
DEVI void jit() {}
DEVI uint32_t mapa(uint32_t a, uint32_t r) { uint32_t o; asm("mapa.shared::cluster.u32 %0, %1, %2;" : "=r"(o) : "r"(a), "r"(r)); return o; }
DEVI void mbar_init(uint32_t b, uint32_t n) { asm volatile("mbarrier.init.shared::cta.b64 [%0], %1;" :: "r"(b), "r"(n) : "memory"); }
DEVI void mbar_expect(uint32_t b, uint32_t bytes) { asm volatile("mbarrier.arrive.expect_tx.shared::cta.b64 _, [%0], %1;" :: "r"(b), "r"(bytes) : "memory"); }
DEVI void mbar_arrive(uint32_t b) { asm volatile("mbarrier.arrive.shared::cta.b64 _, [%0];" :: "r"(b) : "memory"); }
DEVI bool mbar_try(uint32_t b, uint32_t parity) {
    uint32_t ok;
    asm volatile("{.reg .pred p; mbarrier.try_wait.parity.shared::cta.b64 p, [%1], %2; selp.u32 %0, 1, 0, p;}" : "=r"(ok) : "r"(b), "r"(parity) : "memory");
    return ok;
}
DEVI void mbar_wait(uint32_t b, uint32_t parity) {
    LOC(0x100 | (b & 0xff) | (parity << 12));
    asm volatile("{.reg .pred p, q; .reg .u32 n; mov.u32 n, 0;\n W: mbarrier.try_wait.parity.shared::cta.b64 p, [%0], %1;\n"
                 "add.u32 n, n, 1; setp.lt.and.u32 q, n, 0x40000, !p; @q bra W;}" :: "r"(b), "r"(parity) : "memory");
    LOC(0x300 | (b & 0xff));
    jit();
}
DEVI void bar_sync(int id, int n) { jit(); LOC(0x200 | id); asm volatile("bar.sync %0, %1;" :: "r"(id), "r"(n) : "memory"); LOC(0x400 | id); jit(); }
DEVI void bar_arrive(int id, int n) { jit(); asm volatile("bar.arrive %0, %1;" :: "r"(id), "r"(n) : "memory"); jit(); }
DEVI void cluster_sync() { asm volatile("barrier.cluster.arrive.release.aligned; barrier.cluster.wait.acquire.aligned;" ::: "memory"); }
DEVI void cluster_arrive_rlx() { asm volatile("barrier.cluster.arrive.relaxed.aligned;" ::: "memory"); }
DEVI void cluster_wait() { asm volatile("barrier.cluster.wait.aligned;" ::: "memory"); }
DEVI void fence_async() { asm volatile("fence.proxy.async;" ::: "memory"); }
DEVI void cp16(uint32_t dst, const void* src) { asm volatile("cp.async.cg.shared.global [%0], [%1], 16;" :: "r"(dst), "l"(src) : "memory"); }
DEVI void cp_commit() { asm volatile("cp.async.commit_group;" ::: "memory"); }
template <int N> DEVI void cp_wait() { asm volatile("cp.async.wait_group %0;" :: "n"(N) : "memory"); }
DEVI void ldsm4(uint32_t* r, uint32_t a) {
    asm volatile("ldmatrix.sync.aligned.m8n8.x4.shared.b16 {%0,%1,%2,%3}, [%4];" : "=r"(r[0]), "=r"(r[1]), "=r"(r[2]), "=r"(r[3]) : "r"(a) : "memory");
}
DEVI uint32_t tab1(uint32_t a) { uint32_t r; asm volatile("ldmatrix.sync.aligned.m8n8.x1.shared.b16 {%0}, [%1];" : "=r"(r) : "r"(a) : "memory"); return r; }
DEVI uint2 tab2(uint32_t a) { uint2 r; asm volatile("ldmatrix.sync.aligned.m8n8.x2.shared.b16 {%0,%1}, [%2];" : "=r"(r.x), "=r"(r.y) : "r"(a) : "memory"); return r; }
DEVI void ldsm4t(uint32_t* r, uint32_t a) {
    asm volatile("ldmatrix.sync.aligned.m8n8.x4.trans.shared.b16 {%0,%1,%2,%3}, [%4];" : "=r"(r[0]), "=r"(r[1]), "=r"(r[2]), "=r"(r[3]) : "r"(a) : "memory");
}
DEVI void mma16(float* d, uint32_t a0, uint32_t a1, uint32_t a2, uint32_t a3, uint32_t b0, uint32_t b1) {
    asm volatile("mma.sync.aligned.m16n8k16.row.col.f32.bf16.bf16.f32 {%0,%1,%2,%3}, {%4,%5,%6,%7}, {%8,%9}, {%0,%1,%2,%3};"
                 : "+f"(d[0]), "+f"(d[1]), "+f"(d[2]), "+f"(d[3]) : "r"(a0), "r"(a1), "r"(a2), "r"(a3), "r"(b0), "r"(b1));
}
DEVI void mma8(float* d, uint32_t a0, uint32_t a1, uint32_t b0) {
    asm volatile("mma.sync.aligned.m16n8k8.row.col.f32.bf16.bf16.f32 {%0,%1,%2,%3}, {%4,%5}, {%6}, {%0,%1,%2,%3};"
                 : "+f"(d[0]), "+f"(d[1]), "+f"(d[2]), "+f"(d[3]) : "r"(a0), "r"(a1), "r"(b0));
}
DEVI void mma_tf32(float* d, uint32_t a0, uint32_t a1, uint32_t a2, uint32_t a3, uint32_t b0, uint32_t b1) {
    asm volatile("mma.sync.aligned.m16n8k8.row.col.f32.tf32.tf32.f32 {%0,%1,%2,%3}, {%4,%5,%6,%7}, {%8,%9}, {%0,%1,%2,%3};"
                 : "+f"(d[0]), "+f"(d[1]), "+f"(d[2]), "+f"(d[3]) : "r"(a0), "r"(a1), "r"(a2), "r"(a3), "r"(b0), "r"(b1));
}
template <int ACC> DEVI void wgmma32(float* d, const uint32_t* a, uint64_t desc) {
    asm volatile("wgmma.mma_async.sync.aligned.m64n32k16.f32.bf16.bf16 "
                 "{%0,%1,%2,%3,%4,%5,%6,%7,%8,%9,%10,%11,%12,%13,%14,%15}, {%16,%17,%18,%19}, %20, %21, 1, 1, 0;"
                 : "+f"(d[0]), "+f"(d[1]), "+f"(d[2]), "+f"(d[3]), "+f"(d[4]), "+f"(d[5]), "+f"(d[6]), "+f"(d[7]),
                   "+f"(d[8]), "+f"(d[9]), "+f"(d[10]), "+f"(d[11]), "+f"(d[12]), "+f"(d[13]), "+f"(d[14]), "+f"(d[15])
                 : "r"(a[0]), "r"(a[1]), "r"(a[2]), "r"(a[3]), "l"(desc), "n"(ACC));
}
template <int ACC> DEVI void wgmma32_ss(float* d, uint64_t adesc, uint64_t desc) {
    asm volatile("wgmma.mma_async.sync.aligned.m64n32k16.f32.bf16.bf16 "
                 "{%0,%1,%2,%3,%4,%5,%6,%7,%8,%9,%10,%11,%12,%13,%14,%15}, %16, %17, %18, 1, 1, 1, 0;"
                 : "+f"(d[0]), "+f"(d[1]), "+f"(d[2]), "+f"(d[3]), "+f"(d[4]), "+f"(d[5]), "+f"(d[6]), "+f"(d[7]),
                   "+f"(d[8]), "+f"(d[9]), "+f"(d[10]), "+f"(d[11]), "+f"(d[12]), "+f"(d[13]), "+f"(d[14]), "+f"(d[15])
                 : "l"(adesc), "l"(desc), "n"(ACC));
}
DEVI void wg_fence() { asm volatile("wgmma.fence.sync.aligned;" ::: "memory"); }
DEVI void wg_commit() { asm volatile("wgmma.commit_group.sync.aligned;" ::: "memory"); }
DEVI void wg_wait0() { asm volatile("wgmma.wait_group.sync.aligned 0;" ::: "memory"); }
DEVI uint64_t desc_sw128(uint32_t saddr) { return ((uint64_t)1 << 62) | ((uint64_t)64 << 32) | ((uint64_t)1 << 16) | (uint64_t)((saddr & 0x3FFFF) >> 4); }
DEVI uint32_t desc_lo(uint32_t saddr) { return (1u << 16) | ((saddr & 0x3FFFF) >> 4); }
DEVI uint64_t desc_of(uint32_t lo) { uint64_t d; asm("mov.b64 %0, {%1, 0x40000040};" : "=l"(d) : "r"(lo)); return d; }
DEVI uint32_t pack2(float lo, float hi) { uint32_t r; asm("cvt.rn.bf16x2.f32 %0, %1, %2;" : "=r"(r) : "f"(hi), "f"(lo)); return r; }
DEVI void sts32(uint32_t a, uint32_t v) { asm volatile("st.shared.u32 [%0], %1;" :: "r"(a), "r"(v) : "memory"); }
DEVI void sts64f(uint32_t a, float x, float y) { asm volatile("st.shared.v2.f32 [%0], {%1,%2};" :: "r"(a), "f"(x), "f"(y) : "memory"); }
DEVI void sts128f(uint32_t a, float x, float y, float z, float w) { asm volatile("st.shared.v4.f32 [%0], {%1,%2,%3,%4};" :: "r"(a), "f"(x), "f"(y), "f"(z), "f"(w) : "memory"); }
DEVI float2 lds64f(uint32_t a) { float2 v; asm volatile("ld.shared.v2.f32 {%0,%1}, [%2];" : "=f"(v.x), "=f"(v.y) : "r"(a) : "memory"); return v; }
DEVI float4 lds128f(uint32_t a) { float4 v; asm volatile("ld.shared.v4.f32 {%0,%1,%2,%3}, [%4];" : "=f"(v.x), "=f"(v.y), "=f"(v.z), "=f"(v.w) : "r"(a) : "memory"); return v; }
DEVI uint4 lds128(uint32_t a) { uint4 v; asm volatile("ld.shared.v4.u32 {%0,%1,%2,%3}, [%4];" : "=r"(v.x), "=r"(v.y), "=r"(v.z), "=r"(v.w) : "r"(a) : "memory"); return v; }
DEVI uint4 ldm128(uint32_t a) {
    uint4 v;
    asm volatile("ld.shared.v4.u32 {%0,%1,%2,%3}, [%4];" : "=r"(v.x), "=r"(v.y), "=r"(v.z), "=r"(v.w) : "r"(a) : "memory");
    return v;
}
DEVI void sta32(uint32_t a, uint32_t v, uint32_t bar) { asm volatile("st.async.weak.shared::cluster.mbarrier::complete_tx::bytes.b32 [%0], %1, [%2];" :: "r"(a), "r"(v), "r"(bar) : "memory"); }
DEVI void sta64f(uint32_t a, float x, float y, uint32_t bar) { asm volatile("st.async.weak.shared::cluster.mbarrier::complete_tx::bytes.v2.f32 [%0], {%1,%2}, [%3];" :: "r"(a), "f"(x), "f"(y), "r"(bar) : "memory"); }
DEVI void sta128f(uint32_t a, float x, float y, float z, float w, uint32_t bar) {
    asm volatile("st.async.weak.shared::cluster.mbarrier::complete_tx::bytes.v4.f32 [%0], {%1,%2,%3,%4}, [%5];" :: "r"(a), "f"(x), "f"(y), "f"(z), "f"(w), "r"(bar) : "memory");
}
DEVI void stg_rlx(uint32_t* p, uint32_t v) { asm volatile("st.relaxed.gpu.global.u32 [%0], %1;" :: "l"(p), "r"(v) : "memory"); }
DEVI void stg_release(unsigned* p, unsigned v) { asm volatile("st.release.gpu.global.u32 [%0], %1;" :: "l"(p), "r"(v) : "memory"); }
DEVI uint32_t ldg_rlx(const uint32_t* p) { uint32_t v; asm volatile("ld.relaxed.gpu.global.u32 %0, [%1];" : "=r"(v) : "l"(p) : "memory"); return v; }
DEVI void bulk_g2s(uint32_t dst, const void* src, uint32_t bytes, uint32_t bar) {
    asm volatile("cp.async.bulk.shared::cluster.global.mbarrier::complete_tx::bytes [%0], [%1], %2, [%3];" :: "r"(dst), "l"(src), "r"(bytes), "r"(bar) : "memory");
}
DEVI void bulk_s2c(uint32_t dst, uint32_t src, uint32_t bytes, uint32_t bar) {
    asm volatile("cp.async.bulk.shared::cluster.shared::cta.mbarrier::complete_tx::bytes [%0], [%1], %2, [%3];" :: "r"(dst), "r"(src), "r"(bytes), "r"(bar) : "memory");
}
DEVI float ex2(float x) { float y; asm("ex2.approx.ftz.f32 %0, %1;" : "=f"(y) : "f"(x)); return y; }
DEVI float bf2f(__nv_bfloat16 v) { return __bfloat162float(v); }

DEVI uint32_t pin(uint32_t v) { return __shfl_sync(0xffffffffu, v, threadIdx.x & 31); }
template <typename T> DEVI T* pinp(T* p) { const uint64_t v = (uint64_t)p; return (T*)(((uint64_t)pin((uint32_t)(v >> 32)) << 32) | pin((uint32_t)v)); }
DEVI uint32_t fresh(uint32_t v) { uint32_t r; asm volatile("mov.u32 %0, %1;" : "=r"(r) : "r"(v)); return r; }
DEVI uint64_t fresh64(uint64_t v) { uint64_t r; asm volatile("mov.u64 %0, %1;" : "=l"(r) : "l"(v)); return r; }
DEVI uint32_t or3(uint32_t a, uint32_t b, uint32_t c) { uint32_t d; asm("lop3.b32 %0, %1, %2, %3, 0xfe;" : "=r"(d) : "r"(a), "r"(b), "r"(c)); return d; }
DEVI uint32_t and3(uint32_t a, uint32_t b, uint32_t c) { uint32_t d; asm("lop3.b32 %0, %1, %2, %3, 0x80;" : "=r"(d) : "r"(a), "r"(b), "r"(c)); return d; }
DEVI uint32_t diff2(uint32_t a, uint32_t b, uint32_t p) { uint32_t d; asm("lop3.b32 %0, %1, %2, %3, 0x7e;" : "=r"(d) : "r"(a), "r"(b), "r"(p)); return d; }
DEVI int lds32(uint32_t a) { int v; asm volatile("ld.volatile.shared.s32 %0, [%1];" : "=r"(v) : "r"(a) : "memory"); return v; }
DEVI uint2 lds64(uint32_t a) { uint2 v; asm volatile("ld.shared.v2.u32 {%0,%1}, [%2];" : "=r"(v.x), "=r"(v.y) : "r"(a) : "memory"); return v; }
DEVI void sts64(uint32_t a, uint32_t x, uint32_t y) { asm volatile("st.shared.v2.u32 [%0], {%1,%2};" :: "r"(a), "r"(x), "r"(y) : "memory"); }
DEVI void sta64(uint32_t a, uint32_t x, uint32_t y, uint32_t bar) { asm volatile("st.async.weak.shared::cluster.mbarrier::complete_tx::bytes.v2.b32 [%0], {%1,%2}, [%3];" :: "r"(a), "r"(x), "r"(y), "r"(bar) : "memory"); }
DEVI float rcp_fast(float x) { float y; asm("rcp.approx.ftz.f32 %0, %1;" : "=f"(y) : "f"(x)); return y; }
DEVI uint4 ldg_rlx4(const void* p) { uint4 v; asm volatile("ld.relaxed.gpu.global.v4.u32 {%0,%1,%2,%3}, [%4];" : "=r"(v.x), "=r"(v.y), "=r"(v.z), "=r"(v.w) : "l"(p) : "memory"); return v; }
DEVI void sts128(uint32_t a, uint32_t x, uint32_t y, uint32_t z, uint32_t w) { asm volatile("st.shared.v4.u32 [%0], {%1,%2,%3,%4};" :: "r"(a), "r"(x), "r"(y), "r"(z), "r"(w) : "memory"); }
DEVI void stsm4(uint32_t a, uint32_t x, uint32_t y, uint32_t z, uint32_t w) { asm volatile("stmatrix.sync.aligned.m8n8.x4.shared.b16 [%0], {%1,%2,%3,%4};" :: "r"(a), "r"(x), "r"(y), "r"(z), "r"(w) : "memory"); }
DEVI void stsm2(uint32_t a, uint32_t x, uint32_t y) { asm volatile("stmatrix.sync.aligned.m8n8.x2.shared.b16 [%0], {%1,%2};" :: "r"(a), "r"(x), "r"(y) : "memory"); }
DEVI void fence_smem_async() { asm volatile("fence.proxy.async.shared::cta;" ::: "memory"); }
DEVI uint32_t packh2(float lo, float hi) { uint32_t r; asm("cvt.rn.f16x2.f32 %0, %1, %2;" : "=r"(r) : "f"(hi), "f"(lo)); return r; }
DEVI uint32_t h2_to_bf2(uint32_t w) {
    uint32_t r;
    asm("{.reg .f16 l, h; .reg .f32 a, b; mov.b32 {l, h}, %1; cvt.f32.f16 a, l; cvt.f32.f16 b, h; cvt.rn.bf16x2.f32 %0, b, a;}" : "=r"(r) : "r"(w));
    return r;
}
DEVI uint32_t amax2(uint32_t m, uint32_t w) { return __vmaxu2(m, w & 0x7fff7fffu); }
DEVI uint32_t amax_fold(uint32_t m) { return __reduce_max_sync(0xffffffffu, max(m & 0xffffu, m >> 16)); }
DEVI float bflo(uint32_t w) { return __uint_as_float(w << 16); }
DEVI float bfhi(uint32_t w) { return __uint_as_float(w & 0xffff0000u); }
DEVI void red_b8(void* p, uint32_t a, uint32_t b, uint32_t c, uint32_t d) {
    asm volatile("red.relaxed.gpu.global.add.noftz.v4.bf16x2 [%0], {%1,%2,%3,%4};" :: "l"(p), "r"(a), "r"(b), "r"(c), "r"(d) : "memory");
}
DEVI void red_h8_if(bool on, void* p, uint32_t a, uint32_t b, uint32_t c, uint32_t d) {
    asm volatile("{.reg .pred p; setp.ne.u32 p, %5, 0; @p red.relaxed.gpu.global.add.noftz.v4.bf16x2 [%0], {%1,%2,%3,%4};}" :: "l"(p), "r"(a), "r"(b), "r"(c), "r"(d), "r"((uint32_t)on) : "memory");
}
DEVI void mbar_arrive_warp(uint32_t b) { asm volatile("{.reg .pred p; elect.sync _|p, 0xffffffff; @p mbarrier.arrive.shared::cta.b64 _, [%0];}" :: "r"(b) : "memory"); }
DEVI void bulk_s2c_warp(uint32_t dst, uint32_t src, uint32_t bytes, uint32_t bar) {
    asm volatile("{.reg .pred p; elect.sync _|p, 0xffffffff; @p cp.async.bulk.shared::cluster.shared::cta.mbarrier::complete_tx::bytes [%0], [%1], %2, [%3];}" :: "r"(dst), "r"(src), "r"(bytes), "r"(bar) : "memory");
}
DEVI char* mkptr(uint32_t lo, uint32_t hi) { uint64_t p; asm("mov.b64 %0, {%1, %2};" : "=l"(p) : "r"(lo), "r"(hi)); return (char*)p; }
DEVI void bulk_s2g(void* dst, uint32_t src, uint32_t bytes) { asm volatile("cp.async.bulk.global.shared::cta.bulk_group [%0], [%1], %2;" :: "l"(dst), "r"(src), "r"(bytes) : "memory"); }
DEVI void x_tma(uint32_t dst, const CUtensorMap* m, uint32_t xb, int row, int chunk) {
    asm volatile("cp.async.bulk.tensor.3d.shared::cluster.global.mbarrier::complete_tx::bytes.multicast::cluster [%0], [%1, {%3, %4, %5}], [%2], %6;"
                 :: "r"(dst), "l"(m), "r"(xb), "r"(0), "r"(row), "r"(chunk), "h"((uint16_t)7) : "memory");
}
#define RUNG_(A, B, PA, PB) "mov.u64 " A ", %%clock64;\n cvt.u32.u64 l, " B ";\n sub.s32 l, l, %0;\n setp.ge.s32 " PB ", l, 0;\n @" PA " bra.uni DONE;\n"
DEVI void fine_until(uint32_t t) {
    asm volatile("{.reg .pred p0, p1; .reg .b64 t0, t1; .reg .b32 l;\n setp.ne.u32 p0, 0, 0;\n mov.u64 t1, %%clock64;\n LOOP:\n"
                 RUNG_("t0", "t1", "p0", "p1") RUNG_("t1", "t0", "p1", "p0") RUNG_("t0", "t1", "p0", "p1") RUNG_("t1", "t0", "p1", "p0")
                 RUNG_("t0", "t1", "p0", "p1") RUNG_("t1", "t0", "p1", "p0") RUNG_("t0", "t1", "p0", "p1") RUNG_("t1", "t0", "p1", "p0")
                 "bra.uni LOOP;\n DONE:\n}" :: "r"(t) : "memory");
}
DEVI uint32_t clock_offset() {
    const uint32_t g0 = gtime();
    uint32_t e = clk();
#pragma unroll
    for (int i = 0; i < 7; i++) { const uint32_t g = gtime(), t = clk(); e = g == g0 ? t : e; }
    return ((((g0 >> 5) + 1) * 3686u) >> 6) - e;
}
DEVI uint32_t probe_rtt(uint32_t* a) {
    uint32_t best = 0xffffffffu;
#pragma unroll 1
    for (int r = 0; r < NPROBE; r++) {
        uint32_t v = 0, t0 = clk();
        if ((threadIdx.x & 31) == 0) asm volatile("atom.relaxed.gpu.global.exch.b32 %0, [%1], 0;" : "=r"(v) : "l"(a) : "memory");
        const uint32_t t1 = __shfl_sync(0xffffffffu, v, 0) == 0x9e3779b9u ? 0 : clk();
        best = min(best, t1 - t0);
    }
    return best;
}

constexpr int R_X0 = 0;
constexpr int R_WO = 36864;
constexpr int R_DBG = 110592;
constexpr int R_K = 114688 + 3072;
constexpr int R_V = R_K + 4608;
constexpr int R_VM = R_V + 8192;
constexpr int PAR = 17920;
constexpr int R_QM = R_VM + 2048 + PAR;
constexpr int R_SC = R_QM + 1536;
constexpr int R_O8 = R_SC + 2048;
constexpr int R_PX = R_O8 + 2048;
constexpr int R_PV = R_PX + 8192;
constexpr int R_Z = R_PV + 4096;
constexpr int R_T0 = R_Z + 512;
constexpr int R_T1 = R_T0 + 2048;
constexpr int R_T2 = R_T1 + 8192;
constexpr int R_T3 = R_T2 + 512;
constexpr int R_T4 = R_T3 + 2048;
constexpr int R_END = R_T4 + 4096;
constexpr int R_STAGE = 86016;
constexpr int R_MEM = 217088;
constexpr int R_BAR = R_MEM + 12288;
constexpr int R_MISC = R_BAR + 128;
constexpr int R_SMEM = R_MISC + 128;
static_assert(R_END <= R_STAGE + 7 * 16384, "smem");
enum { BX0 = 0  , BSC = 24, BME = 32, BVX = 40  , BML = 56 };
enum { NB_F1 = 1, NB_K = 5, NB_G1 = 6, NB_E0 = 7, NB_GO = 8, NB_W1 = 9, NB_H1 = 10, NB_TOK = 11, NB_W2 = 12, NB_F0 = 13, NB_L0 = 14   };
enum { M_EPOCH = 0, M_SINK = 4, M_PROBE = 8  , M_TGT = 16  , M_REF = 24  , M_ONE = 32 };
constexpr uint32_t EMPTY = 0xc200u;
constexpr float QS = 0.08838834764831845f * 1.4426950408889634f;

DEVI uint32_t acc_slot(uint32_t s) { return (s & 1) * 128 + (s & 2) * 16384; }
DEVI uint32_t acc_blk(uint32_t m, uint32_t l) { return (((l >> 1) << 2) | ((l & 1) << 1) | ((l & 1) ^ m)) * 4096; }
DEVI uint32_t acc_line(uint32_t i, uint32_t q, uint32_t l) { return acc_blk(q & 1, l) + (q >> 1) * 256 + (i < 4 ? i * 1024 : i * 1024 - 1536); }
DEVI uint32_t acc_stamp(uint32_t m, uint32_t n) { return acc_blk(m, n >> 5) + 512 + (n & 31) * 4; }

#define LOAD_TRANSIENT(LA) { _Pragma("unroll") for (int i_ = 0; i_ < NTR; i_++) ldsm4t(w[i_ & 1][i_ >> 1], (LA) + (i_ & 1) * 4096 + (i_ >> 1) * 2048); }
#define MMAW(D, T, K, B0, B1) mma16(D, w[T][K][0], w[T][K][1], w[T][K][2], w[T][K][3], B0, B1)

DEVI void proj_loop(uint32_t (&w)[2][18][4], unsigned char* smem, const uint32_t sb, const uint32_t c, const int wg, const int q, const uint32_t lane0) {
    const uint32_t bar = sb + R_BAR;
    const int p = q ^ (2 * wg);
    const bool c2 = c == 2, both = !c2 && p < 2, aq = c2 ? p < 2 : p != 2;
    const uint32_t lp = pin(sb + lane0 * 16 + p * 1024), ma = pin(sb + lane0 * 16 + wg * 1024);
    {
        const uint32_t l16 = sb + lane0 * 16;
        const int ia = c2 ? p & 1 : min(p, 2), vt = c2 ? 4 + p : 2 * c + p - 2;
        const uint32_t dtok = l16 + (wg ? (aq ? R_K - ((c2 ? 2 : 3) - ia) * 1024 : R_K + ia * 1536) : (both ? R_K + p * 1536 : R_V + vt * 1024));
        const uint32_t la = sb + R_STAGE + 7 * 16384 + wg * 8192 + (((lane0 >> 4) << 3) + (lane0 & 7)) * 128 + (((2 * q + ((lane0 >> 3) & 1)) ^ (lane0 & 7)) << 4);
        const bool lo = lane0 < 16, mq = aq && lo, mv = !both && !lo;
        const uint32_t dmem = sb + (mq ? R_QM + ia * 512 + (lane0 & 8) * 32 + wg * 128 : (mv ? R_PV + p * 1024 : R_K + ia * 1536 + 1024) + wg * 256 + (lane0 & 8) * 16) + (lane0 & 7) * 16;
        stsm4(lp + R_T4 + wg * 512, dtok, la, dmem, dmem + (mq || mv ? 0 : PAR));
        const uint32_t p0 = mapa(sb, c2 ? 0 : c + 1), p1 = mapa(sb, c == 0 ? 2 : c - 1), d = R_VM + vt * 256 + lane0 * 4;
        sts128(lp + R_PV + 512, p0 + d, p0 + R_BAR + BSC, p1 + d, p1 + R_BAR + BSC);
        __syncwarp();
        mbar_wait(bar + BX0, 0);
    }
#define PUBLISH(S) { asm volatile("cp.async.bulk.wait_group 0;" ::: "memory"); stg_rlx(&g_qflag[S][blockIdx.x / 3][c * 8], lds32(sb + R_MISC + M_EPOCH)); }
#pragma unroll 1
    for (int s = 0; s < NSEG; s++) {
        const int xi = s - 3 * ((s * 43) >> 7);
        {
            float d[16];
#define TOKEN(WG, T, I0, I1, ZERO)                                                                                          \
    {                                                                                                                       \
    const uint32_t xd = fresh(desc_lo(sb + xi * 36864)), ad = fresh(desc_lo(sb + R_STAGE + 7 * 16384));                     \
    wg_fence();                                                                                                             \
    _Pragma("unroll") for (int i = I0; i < I1; i++) {                                                                       \
        const int j = i < 10 ? i + 2 : (i < 12 ? i - 10 : i), g = 18 * WG + j;                                              \
        const uint64_t bd = desc_of(xd + (g >> 2) * 256 + (g & 3) * 2);                                                     \
        if (2 * j + (T) < NTR) wgmma32_ss<1>(d, desc_of(ad + ((WG * 8192 + (T) * 4096 + j * 2048) >> 4)), bd);                          \
        else if (i == 0 && ZERO) wgmma32<0>(d, w[T][j], bd);                                                                \
        else wgmma32<1>(d, w[T][j], bd);                                                                                    \
    }                                                                                                                       \
    wg_commit();                                                                                                            \
    }
#define HANDOVER(WG)                                                                                                        \
    {                                                                                                                       \
        const uint32_t xa = lp + R_PX + WG * 4096;                                                                          \
        sts128(xa, pack2(d[0], d[1]), pack2(d[2], d[3]), pack2(d[4], d[5]), pack2(d[6], d[7]));                             \
        sts128(xa + 512, pack2(d[8], d[9]), pack2(d[10], d[11]), pack2(d[12], d[13]), pack2(d[14], d[15]));                 \
    }
            if (wg == 0) {
                bar_sync(NB_G1, 256);
                TOKEN(0, 0, 0, 18, 1)
                const uint32_t la = tab1(lp + R_T4 + 128);
                wg_wait0();
                EV(3);
                if (q == 1 && s > 0) {
                    const uint2 tt = tab2(lp + R_T2 - 1024);
                    const uint32_t tag = s << 22;
                    const char* const sp = mkptr(tt.x + acc_slot(s - 1), tt.y);
                    uint4 v = ldg_rlx4(sp);
                    bar_sync(NB_E0, 256);
                    HANDOVER(0)
                    bar_arrive(NB_GO, 384);
                    LOAD_TRANSIENT(la)
                    const uint2 tr = lds64(sb + R_MISC + M_REF);
                    int n = 0;
                    while (__any_sync(0xffffffffu, (diff2(v.x, v.y, tag) | diff2(v.z, v.w, tag)) >> 22)) {
                        v = ldg_rlx4(sp);
                        if (++n > (1 << 22)) TRAP(1002);
                    }
                    const int m = __reduce_max_sync(0xffffffffu, max(max((int)((v.x - tr.y) << 10), (int)((v.y - tr.y) << 10)), max((int)((v.z - tr.y) << 10), (int)((v.w - tr.y) << 10)))) >> 10;
                    sts64(sb + R_MISC + M_TGT, tr.x + min(m, DMAX) + (CT - 65), s);
                    EV(0);
                    if (EVX(0)) EVV(11, m);
                } else {
                    bar_sync(NB_E0, 256);
                    HANDOVER(0)
                    bar_arrive(NB_GO, 384);
                    LOAD_TRANSIENT(la)
                }
                bar_sync(NB_F0, 256);
                TOKEN(0, 1, 0, F1T, 1)
                bar_arrive(NB_F1, 256);
                TOKEN(0, 1, F1T, 18, 0)
                const uint32_t dtok = tab1(lp + R_T4) + (s & 1) * PAR;
                bar_sync(NB_H1, 256);
                const uint4 oa = lds128(lp + R_PX + 4096);
                wg_wait0();
                const uint32_t u0 = pack2(d[0] + bflo(oa.x), d[1] + bfhi(oa.x)), u1 = pack2(d[2] + bflo(oa.y), d[3] + bfhi(oa.y));
                const uint4 ob = lds128(lp + R_PX + 4608);
                stsm4(dtok, u0, u1, pack2(d[4] + bflo(oa.z), d[5] + bfhi(oa.z)), pack2(d[6] + bflo(oa.w), d[7] + bfhi(oa.w)));
                stsm4(dtok + 512, pack2(d[8] + bflo(ob.x), d[9] + bfhi(ob.x)), pack2(d[10] + bflo(ob.y), d[11] + bfhi(ob.y)),
                      pack2(d[12] + bflo(ob.z), d[13] + bfhi(ob.z)), pack2(d[14] + bflo(ob.w), d[15] + bfhi(ob.w)));
                bar_arrive(NB_TOK, 384);
            } else {
                const uint2 tw = tab2(lp + R_T4 + 512);
                bar_sync(NB_GO, 384);
                TOKEN(1, 1, 0, F0T, 1)
                bar_arrive(NB_F0, 256);
                TOKEN(1, 1, F0T, 18, 0)
                const uint4 oa = lds128(lp + R_PX), ob = lds128(lp + R_PX + 512);
                wg_wait0();
                HANDOVER(1)
                bar_arrive(NB_H1, 256);
                {
                    const uint32_t ox[8] = {oa.x, oa.y, oa.z, oa.w, ob.x, ob.y, ob.z, ob.w};
#pragma unroll
                    for (int j = 0; j < 8; j++) { d[2 * j] = bflo(ox[j]); d[2 * j + 1] = bfhi(ox[j]); }
                }
                LOAD_TRANSIENT(tw.y)
                bar_sync(NB_F1, 256);
                TOKEN(1, 0, 0, 18, 0)
                if (q == 3 && s > 0) PUBLISH(s - 1)
                const float qs = aq ? QS : 1.f;
                const uint32_t dtok = tw.x + (s & 1) * PAR;
                wg_wait0();
                EV(13);
#pragma unroll
                for (int hf = 0; hf < 2; hf++) {
                    const float* e = d + 8 * hf;
                    stsm4(dtok + hf * 512, pack2(e[0] * qs, e[1] * qs), pack2(e[2] * qs, e[3] * qs), pack2(e[4] * qs, e[5] * qs), pack2(e[6] * qs, e[7] * qs));
                }
                EV(12);
                bar_arrive(NB_TOK, 384);
            }
#undef TOKEN
#undef HANDOVER
        }
        uint4 b[12];
        float a[4][4];
        int pass = 0;
      redo:
        mbar_wait(bar + BME, s & 1);
#pragma unroll
        for (int j = 0; j < 4; j++) a[0][j] = a[1][j] = a[2][j] = a[3][j] = 0.f;
#pragma unroll
        for (int i = 0; i < 4; i++) b[i] = ldm128(ma + R_MEM + (i >> 1) * 2048 + (i & 1) * 512);
#define BK0(k) ((k) % 3 == 2 ? b[(k) / 3 * 2].z : b[(k) / 3 * 2 + (k) % 3].x)
#define BK1(k) ((k) % 3 == 2 ? b[(k) / 3 * 2].w : b[(k) / 3 * 2 + (k) % 3].y)
#define KS(T, k) MMAW(a[2 * (T) + ((k) & 1)], T, k, BK0(k), BK1(k));
#define JOIN(g) { chk = or3(chk, b[2 * (g)].w, b[2 * (g) + 1].w); b[2 * (g)].w = b[2 * (g) + 1].z | chk; }
        uint32_t chk = 0;
#pragma unroll
        for (int k = 0; k < LW; k++) { if (k % 3 == 2) JOIN(k / 3) KS(0, k) KS(1, k) }
#pragma unroll
        for (int i = 4; i < 12; i++) b[i] = ldm128(ma + R_MEM + (i >> 1) * 2048 + (i & 1) * 512);
        const uint32_t dmem = tab1(lp + fresh(wg * 512 + (s & 1) * 128) + R_T4 + 256);
#pragma unroll
        for (int k = LW; k < 18; k++) { if (k % 3 == 2) JOIN(k / 3) KS(0, k) KS(1, k) }
        float r[4];
        {
            const float s0 = aq ? QS : 1.f;
#pragma unroll
            for (int j = 0; j < 4; j++) r[j] = a[3][j] + a[2][j];
            stsm4(dmem, pack2(fmaf(a[1][0], s0, a[0][0] * s0), fmaf(a[1][1], s0, a[0][1] * s0)), pack2(fmaf(a[1][2], s0, a[0][2] * s0), fmaf(a[1][3], s0, a[0][3] * s0)),
                  pack2(r[0], r[1]), pack2(r[2], r[3]));
            const uint32_t bad = __any_sync(0xffffffffu, chk);
            asm volatile("{.reg .pred p; setp.eq.u32 p, %0, 0; @p bar.arrive %1, 384;}" :: "r"(bad | wg), "n"((int)NB_K) : "memory");
            asm volatile("{.reg .pred p; setp.eq.u32 p, %0, 0; @p bar.sync %1, 384;}" :: "r"(bad | (wg ^ 1)), "n"((int)NB_K) : "memory");
            if (__builtin_expect(bad, 0)) goto repair;
        }
#undef JOIN
#undef KS
#undef BK0
#undef BK1
        if (wg == 0) { EV(1); continue; }
        if (!both) {
            const uint2 o = tab2(lp + R_PV);
            const uint4 tv = lds128(lp + R_PV + 512);
            const uint32_t lo = pack2(r[0] + bflo(o.x), r[1] + bfhi(o.x)), hi = pack2(r[2] + bflo(o.y), r[3] + bfhi(o.y));
            const uint32_t v0 = tv.x + (s & 1) * PAR, v1 = tv.z + (s & 1) * PAR, v2 = v0 - tv.y + bar + BSC;
            sta32(v0, lo, tv.y); sta32(v0 + 128, hi, tv.y);
            sta32(v1, lo, tv.w); sta32(v1 + 128, hi, tv.w);
            sts32(v2, lo); sts32(v2 + 128, hi);
            EV(2);
        }
        {
            if (q != 3) bar_arrive(NB_W1, 256);
            if (q == 3) {
                bar_sync(NB_W1, 256);
                unsigned char* const dst = g_qkv + (size_t)(s * 32 + blockIdx.x / 3) * 30720;
                const uint32_t so = sb + (s & 1) * PAR;
                fence_smem_async();
                asm volatile("{.reg .pred p; elect.sync _|p, 0xffffffff;\n"
                             "@p cp.async.bulk.global.shared::cta.bulk_group [%0], [%1], %2;\n"
                             "@p cp.async.bulk.global.shared::cta.bulk_group [%3], [%4], %5;\n"
                             "@p cp.async.bulk.global.shared::cta.bulk_group [%6], [%7], %8;\n"
                             "@p cp.async.bulk.commit_group;}"
                             :: "l"(dst + c * 7680), "r"(so + R_K - (c2 ? 2048 : 3072)), "r"(c2 ? 5120 : 7680),
                                "l"(dst + 20480 + c * 2048), "r"(so + R_V + c * 2048), "r"(c2 ? 4096 : 2048),
                                "l"(dst + 28672 + c * 512), "r"(so + R_VM + c * 512), "r"(c2 ? 1024 : 512) : "memory");
            } else if (q == 2) {
                const uint4 tz = lds128(lp + R_T0 + 1536);
                uint32_t z;
                asm volatile("atom.relaxed.gpu.global.exch.b32 %0, [%1], %2;" : "=r"(z) : "l"(mkptr(tz.x + acc_slot(s + 2), tz.y)), "r"(tz.w) : "memory");
                sts32(sb + R_MISC + M_SINK, z);
            }
        }
        continue;
      repair:
        {
            if (++pass > (1 << 20)) TRAP(1000);
#pragma unroll 1
            for (int i = 0; i < 2; i++) {
                const uint2 tb = tab2(ma + fresh(i * 512) + R_T1 + 256 + ((s - 1) & 3) * 2048);
                const uint32_t md = ma + (ma & 256) + R_MEM + i * 2048;
                const char* const ga = mkptr(tb.x, tb.y);
                cp16(md, ga); cp16(md + 256, ga + 1024); cp16(md + 4096, ga + 2048); cp16(md + 4352, ga + 3072);
                cp16(md + 8192, ga + 2560); cp16(md + 8448, ga + 3584);
            }
            asm volatile("cp.async.wait_all;" ::: "memory");
            __syncwarp();
            const uint32_t la = tab1(lp + fresh(wg * 512) + R_T4 + 128);
            LOAD_TRANSIENT(la)
            goto redo;
        }
    }
    if (wg == 1 && q == 3) PUBLISH(NSEG - 1)
#undef PUBLISH
}

DEVI void attn_loop(const uint32_t (&wo)[3][8][4], const CUtensorMap* xmap, const CUtensorMap* amap, unsigned char* smem, const uint32_t sb, const uint32_t c, const int q,
                    const uint32_t lane0, const uint32_t side, const uint32_t jw) {
    const uint32_t bar = sb + R_BAR;
    const bool c2 = c == 2;
    const uint32_t l16 = pin(sb + lane0 * 16);
    {
        const uint32_t lane = lane0, n = blockIdx.x, gl = (uint32_t)(uint64_t)(void*)g_acc, gh = (uint32_t)((uint64_t)(void*)g_acc >> 32);
        const uint32_t p0 = mapa(sb, c2 ? 0 : c + 1), p1 = mapa(sb, c == 0 ? 2 : c - 1), so = R_SC + lane * 4;
        if (q < 3) sts128(l16 + R_T0 + q * 512, p0 + so + (q == 2 ? 1536 : 512 + q * 256), p0 + R_BAR + BSC, p1 + so + (q == 2 ? 1664 : 1024 + q * 256), p1 + R_BAR + BSC);
        else {
            sts128(l16 + R_T0 + q * 512, gl + acc_line(n >> 4, (n >> 2) & 3, n & 3) + lane * 4, gh, gl + acc_stamp(lane & 1, n), (lane & 3) == 3 ? EMPTY : 0);
            stsm2(l16 + R_T2, gl + acc_stamp(side, (lane < 24 ? lane : 0) * 4), gh);
        }
        for (int i = 0; i < 4; i++)
            stsm4(l16 + R_T1 + i * 2048 + q * 512, gl + acc_slot(i) + acc_line(2 * jw, q, (lane >> 4) * 2 + ((lane >> 1) & 1)) + ((lane & 1) * 4 + ((lane >> 2) & 3)) * 16, gh,
                   gl + acc_slot(i) + acc_line(0, q, lane >> 3) + (lane & 7) * 16, gh);
        __syncwarp();
    }
    const uint32_t ls = pin(sb + (lane0 & 3) * 32);
#define UA(x) (l16 + fresh(x))
#pragma unroll 1
    for (int s = 0; s < NSEG - 1; s++) {
        const uint32_t par = (s & 1) * PAR;
        bar_sync(NB_TOK, 384);
#define SCORES()                                                                                                   \
    float x[2][3][4];                                                                                              \
    _Pragma("unroll") for (int t = 0; t < 3; t++) {                                                                \
        _Pragma("unroll") for (int j = 0; j < 4; j++) x[0][t][j] = x[1][t][j] = 0.f;                               \
        mma16(x[0][t], qf[t][0], qf[t][1], qf[t][2], qf[t][3], kf[t][0], kf[t][1]);                                \
        mma16(x[1][t], qf[t][0], qf[t][1], qf[t][2], qf[t][3], kf[t][2], kf[t][3]);                                \
    }                                                                                                              \
    bar_arrive(NB_G1 + (__float_as_uint(x[0][G1T][0]) & (l16 >> 31)), 256);                                         \
    const uint4 ta = lds128(UA(q * 512) + R_T0);                                                                            \
    float y[4];                                                                                                    \
    _Pragma("unroll") for (int j = 0; j < 4; j++)                                                                  \
        y[j] = ((x[j >> 1][0][j & 1] + x[j >> 1][0][2 + (j & 1)]) + (x[j >> 1][1][j & 1] + x[j >> 1][1][2 + (j & 1)])) + (x[j >> 1][2][j & 1] + x[j >> 1][2][2 + (j & 1)]);
        if (q < 2) {
            uint32_t qf[3][4], kf[3][4];
#pragma unroll
            for (int t = 0; t < 3; t++) ldsm4t(kf[t], UA(q * 512 + par) + R_K + t * 1536);
            bar_sync(NB_K, 384);
#pragma unroll
            for (int t = 0; t < 3; t++) ldsm4t(qf[t], l16 + R_QM + t * 512);
            SCORES()
            const uint32_t u0 = pack2(y[0], y[1]), u1 = pack2(y[2], y[3]);
            sta32(ta.x, u0, ta.y); sta32(ta.z, u0, ta.w);
            sta32(ta.x + 128, u1, ta.y); sta32(ta.z + 128, u1, ta.w);
            stsm2(UA(q * 256) + R_SC, u0, u1);
        } else if (q == 2) {
            if (s > 0 && s + 2 < NSEG) {
                const int xi = s - 1 - 3 * (((s - 1) * 43) >> 7);
                mbar_wait(bar + BME, s & 1);
                spin_until(clk() + XD);
                asm volatile("{.reg .pred p; elect.sync _|p, 0xffffffff;\n"
                             "@p mbarrier.arrive.expect_tx.shared::cta.b64 _, [%2], 36864;\n"
                             "@p cp.async.bulk.tensor.3d.shared::cluster.global.mbarrier::complete_tx::bytes.multicast::cluster [%0], [%1, {%3, %4, %5}], [%2], %6;}"
                             :: "r"(sb + xi * 36864 + c * 12288), "l"(xmap), "r"(bar + BX0 + xi * 8), "r"(0), "r"((s + 2) * 32), "r"(c * 3), "h"((uint16_t)7) : "memory");
            }
            uint32_t qf[3][4], kf[3][4];
            bar_sync(NB_K, 384);
#pragma unroll
            for (int t = 0; t < 3; t++) { ldsm4t(qf[t], l16 + R_QM + t * 512); ldsm4t(kf[t], UA(q * 512 + par) + R_K + t * 1536); }
            SCORES()
            const uint32_t u0 = pack2(y[0] + y[2], y[1] + y[3]);
            sta32(ta.x, u0, ta.y);
            sta32(ta.z, u0, ta.w);
            EV(4);
            stsm2(l16 + R_SC + 1792, u0, u0);
        } else {
            const uint4 ta = lds128(UA(q * 512) + R_T0);
            {
                const uint32_t vt = R_V + par + c * 2048, p0 = mapa(sb, c2 ? 0 : c + 1), p1 = mapa(sb, c == 0 ? 2 : c - 1);
                fence_smem_async();
                bulk_s2c_warp(p0 + vt, sb + vt, c2 ? 4096 : 2048, p0 + R_BAR + BVX + (s & 1) * 8);
                bulk_s2c_warp(p1 + vt, sb + vt, c2 ? 4096 : 2048, p1 + R_BAR + BVX + (s & 1) * 8);
            }
            {
                const int s3 = ((s + 1) * 43) >> 7;
                mbar_wait(bar + BX0 + (s + 1 - 3 * s3) * 8, s3 & 1);
                bar_arrive(NB_G1, 256);
            }
            sts32(sb + R_MISC + M_REF + 4, clock_offset());
            bar_sync(NB_K, 384);
            const uint32_t off = lds32(sb + R_MISC + M_REF + 4);
            const uint32_t t = off == 0x9e3779b9u ? 0u : clk();
            sts64(sb + R_MISC + M_REF, t, t + off);
            stg_rlx((uint32_t*)mkptr(ta.z + acc_slot(s), ta.y), ((t + off) & 0x3fffffu) | ((s + 1) << 22));
            mbar_wait(bar + BVX + (s & 1) * 8, (s >> 1) & 1);
        }
#undef SCORES
        bar_sync(NB_W1, 256);
        uint32_t vf[4][4];
        const uint32_t vo = par + q * 2048;
        float o0[4], o1[4], sum;
        uint2 tb;
        {
            uint32_t aw[5], bw[5], cw[5];
            ldsm4(aw, l16 + R_SC); aw[4] = tab1(l16 + R_SC + 1792);
            sts32(sb + R_MISC + M_SINK, aw[0] | aw[4]);
            mbar_wait(bar + BSC, s & 1);
            ldsm4(bw, l16 + R_SC + 512); ldsm4(cw, l16 + R_SC + 1024);
            { const uint2 t = tab2(l16 + R_SC + 1536); bw[4] = t.x; cw[4] = t.y; }
            EV(5);
            float x[10];
#pragma unroll
            for (int i = 0; i < 5; i++) { x[2 * i] = (bflo(aw[i]) + bflo(bw[i])) + bflo(cw[i]); x[2 * i + 1] = (bfhi(aw[i]) + bfhi(bw[i])) + bfhi(cw[i]); }
            float mx = fmaxf(fmaxf(fmaxf(fmaxf(x[0], x[1]), fmaxf(x[2], x[3])), fmaxf(fmaxf(x[4], x[5]), fmaxf(x[6], x[7]))), fmaxf(x[8], x[9]));
            const float m1 = __shfl_xor_sync(0xffffffffu, mx, 1), m2 = __shfl_xor_sync(0xffffffffu, mx, 2), m3 = __shfl_xor_sync(0xffffffffu, mx, 3);
            uint32_t vm[4];
            const uint32_t lv = l16 | (__float_as_uint(mx) & (l16 >> 31));
            ldsm4(vf[0], lv + fresh(vo) + R_V); ldsm4(vf[2], lv + fresh(vo) + R_V + 1024);
            ldsm4(vf[3], lv + fresh(vo) + R_V + 1536); ldsm4(vm, lv + fresh(q * 512 + par) + R_VM);
            tb = tab2(lv + fresh(q * 512 + (s & 3) * 2048) + R_T1);
            bar_arrive(NB_E0, 256);
            ldsm4(vf[1], lv + fresh(vo) + R_V + 512);
            mx = fmaxf(fmaxf(mx, m1), fmaxf(m2, m3));
            uint32_t pb[5];
            sum = 0.f;
#pragma unroll
            for (int i = 0; i < 5; i++) {
                const float e0 = ex2(x[2 * i] - mx), e1 = ex2(x[2 * i + 1] - mx);
                pb[i] = pack2(e0, e1);
                sum += e0 + e1;
            }
#pragma unroll
            for (int j = 0; j < 4; j++) o0[j] = o1[j] = 0.f;
            mma16(o0, vf[0][0], vf[0][1], vf[0][2], vf[0][3], pb[0], pb[1]);
            mma16(o1, vf[2][0], vf[2][1], vf[2][2], vf[2][3], pb[0], pb[1]);
            mma16(o0, vf[1][0], vf[1][1], vf[1][2], vf[1][3], pb[2], pb[3]);
            mma16(o1, vf[3][0], vf[3][1], vf[3][2], vf[3][3], pb[2], pb[3]);
            mma8(o0, vm[0], vm[1], pb[4]);
            mma8(o1, vm[2], vm[3], pb[4]);
        }
        asm volatile("stmatrix.sync.aligned.m8n8.x1.shared.b16 [%0], {%1};" :: "r"(l16 + R_Z), "r"(__float_as_uint(sum)) : "memory");
        const float4 s0 = lds128f(ls + R_Z), s1 = lds128f(ls + R_Z + 16);
        stsm4(UA(q * 512) + R_O8, pack2(o0[0], o0[1]), pack2(o0[2], o0[3]), pack2(o1[0], o1[1]), pack2(o1[2], o1[3]));
        EV(6);
        bar_sync(NB_W2, 128);
        uint32_t of[4][4];
#pragma unroll
        for (int i = 0; i < 4; i++) ldsm4t(of[i], l16 + R_O8 + i * 512);
        const float f0 = rcp_fast((s0.x + s0.y) + (s0.z + s0.w)), f1 = rcp_fast((s1.x + s1.y) + (s1.z + s1.w));
        float acc[3][2][4];
        uint32_t tie;
#pragma unroll
        for (int m = 0; m < 3; m++)
#pragma unroll
            for (int j = 0; j < 4; j++) acc[m][0][j] = acc[m][1][j] = 0.f;
#pragma unroll
        for (int i = 0; i < 4; i++)
#pragma unroll
            for (int m = 0; m < 3; m++)
#pragma unroll
                for (int e = 0; e < 2; e++) {
                    const int p = i ? 1 + (i + m + 2) % 3 : 0, kk = 2 * p + e;
                    if (i == 3 && m == 0 && e == 0)
                        tie = or3(or3(__float_as_uint(acc[0][0][0]), __float_as_uint(acc[0][1][0]), __float_as_uint(acc[1][0][0])),
                                  or3(__float_as_uint(acc[1][1][0]), __float_as_uint(acc[2][0][0]), __float_as_uint(acc[2][1][0])), __float_as_uint(f0) | __float_as_uint(f1));
                    mma16(acc[m][e], wo[m][kk][0], wo[m][kk][1], wo[m][kk][2], wo[m][kk][3], of[p][e * 2], of[p][e * 2 + 1]);
                }
        char* const gw = mkptr(tb.x, tb.y);
        bar_arrive(NB_GO + (tie & (l16 >> 31)), 384);
        const uint32_t one = lds32(sb + R_MISC + M_ONE);
        uint32_t wa[3], wb[3];
#pragma unroll
        for (int m = 0; m < 3; m++) {
            wa[m] = pack2(fmaf(acc[m][1][0], f0, acc[m][0][0] * f0), fmaf(acc[m][1][2], f0, acc[m][0][2] * f0));
            wb[m] = pack2(fmaf(acc[m][1][1], f1, acc[m][0][1] * f1), fmaf(acc[m][1][3], f1, acc[m][0][3] * f1));
        }
        red_b8(gw, wa[0], wa[1], wa[2], one); red_b8(gw + 1024, wb[0], wb[1], wb[2], one);
        const uint32_t t0 = clk();
        if (EVX(0)) EVV(7, t0);
        if (q < 2) {
            uint2 tg = lds64(sb + R_MISC + M_TGT);
            for (int n = 0; tg.y != s + 1; tg = lds64(sb + R_MISC + M_TGT)) if (++n > (1 << 26)) TRAP(1003);
            fine_until(t0 + max((int)(tg.x - t0), DMIN) - (q != side ? FE : 0) + (c ? DL : 0));
            asm volatile("{.reg .pred p; elect.sync _|p, 0xffffffff;\n"
                         "@p cp.async.bulk.tensor.5d.shared::cluster.global.mbarrier::complete_tx::bytes.multicast::cluster [%0], [%1, {%3, %4, %4, %4, %5}], [%2], %6;}"
                         :: "r"(sb + R_MEM + c * 4096 + q * 2048), "l"(amap + q), "r"(bar + (DL && c ? BML : BME)), "r"((s & 1) * 64), "r"(0), "r"((s & 2) * 64 + (c ? 6 + 2 * c : 0)), "h"((uint16_t)7) : "memory");
            EV(8);
        } else if (q == 2) {
            if (l16 == sb) {
                mbar_expect(bar + BME, DL ? 4096 : 12288);
                if (DL) mbar_expect(bar + BML, 8192);
                mbar_expect(bar + BSC, (c2 ? 1024 : 1536) + (s < NSEG - 2 ? 1280 : 0));
                mbar_expect(bar + BVX + 8 - (s & 1) * 8, c2 ? 4096 : 6144);
            }
        }
        EV(10);
    }
    bar_sync(NB_TOK, 384);
    bar_arrive(NB_K, 384);
    bar_arrive(NB_W1, 256);
    mbar_wait(bar + BSC, 1);
}

struct Maps { CUtensorMap x, acc[2]; };

__global__ void __launch_bounds__(384, 1)
rk_kernel(const __grid_constant__ Maps maps, const __nv_bfloat16* __restrict__ xraw, const __nv_bfloat16* __restrict__ mem0, const __nv_bfloat16* __restrict__ Wq,
          const __nv_bfloat16* __restrict__ Wk, const __nv_bfloat16* __restrict__ Wv, const __nv_bfloat16* __restrict__ Wo) {
    extern __shared__ __align__(1024) unsigned char smem[];
    const uint32_t sb = smem_u32(smem);
    const int tid = threadIdx.x;
    const int warp = __shfl_sync(0xffffffffu, tid >> 5, 0), q = warp & 3;
    const int h = blockIdx.x / 3;
    const uint32_t c = blockIdx.x - 3 * h;
    const uint32_t bar = sb + R_BAR;
    asm volatile("griddepcontrol.launch_dependents;");
    GT(0, 0);

    if (warp < 8) {
        asm volatile("setmaxnreg.inc.sync.aligned.u32 %0;" :: "n"(RP));
        const int wg = warp >> 2;
        const uint32_t lane = pin(tid & 31);
        uint32_t w[2][18][4];
        const uint32_t st = sb + R_STAGE + wg * 8192;
        const uint32_t la = st + (((lane >> 4) << 3) + (lane & 7)) * 128 + (((2 * q + ((lane >> 3) & 1)) ^ (lane & 7)) << 4);
        {
            const int t = tid & 127;
            const int r0 = t >> 3, ch = t & 7, p = (ch >> 1) ^ (2 * wg);
            const __nv_bfloat16* ta = c == 2 ? (p < 2 ? Wq : Wk) + 96 + (p & 1) * 16 : (p == 2 ? Wk : Wq) + c * 48 + min(p, 2) * 16;
            const __nv_bfloat16* tb = c == 2 ? Wv + 64 + p * 16 : (p >= 2 ? Wv + c * 32 + (p - 2) * 16 : Wk + c * 48 + p * 16);
            const size_t so = (size_t)(wg * 288 + r0) * HD + h * 128 + (ch & 1) * 8;
            const __nv_bfloat16* sp0 = ta + so;
            const __nv_bfloat16* sp1 = tb + so;
            const uint32_t dp = st + r0 * 128 + ((ch ^ (r0 & 7)) << 4);
#define ISSUE(KC, SLOT)                                                                                         \
    cp16(dp + (SLOT) * 16384, sp0 + (size_t)((KC) * 32) * HD); cp16(dp + (SLOT) * 16384 + 2048, sp0 + (size_t)((KC) * 32 + 16) * HD);               \
    cp16(dp + (SLOT) * 16384 + 4096, sp1 + (size_t)((KC) * 32) * HD); cp16(dp + (SLOT) * 16384 + 6144, sp1 + (size_t)((KC) * 32 + 16) * HD);        \
    cp_commit();
#pragma unroll
            for (int kc = 1; kc < 8; kc++) { ISSUE(kc, kc - 1) }
            ISSUE(0, 7)
            cluster_arrive_rlx(); cluster_wait();
#define LOADCHUNK(KC, SLOT, NWAIT)                                                   \
    cp_wait<NWAIT>(); bar_sync(NB_L0 + wg, 128);                                      \
    _Pragma("unroll") for (int i = 0; i < 4; i++) ldsm4t(w[i >> 1][(KC) * 2 + (i & 1)], la + (SLOT) * 16384 + i * 2048);
            LOADCHUNK(1, 0, 7)
            bar_sync(NB_L0 + wg, 128);
            ISSUE(8, 0)
            LOADCHUNK(2, 1, 7) LOADCHUNK(3, 2, 6) LOADCHUNK(4, 3, 5) LOADCHUNK(5, 4, 4) LOADCHUNK(6, 5, 3) LOADCHUNK(7, 6, 2) LOADCHUNK(0, 7, 1) LOADCHUNK(8, 0, 0)
#undef LOADCHUNK
#undef ISSUE
            fence_smem_async();
        }
        bar_sync(0, 384);
        cluster_arrive_rlx(); cluster_wait();

        GT(0, 1);
        if (c == 2) sts128(sb + (q == 3 ? R_QM + 1024 : R_K + 3072 + q * 512 + wg * PAR) + lane * 16, 0, 0, 0, 0);
        proj_loop(w, smem, sb, c, wg, q, lane);
    } else {
        asm volatile("setmaxnreg.dec.sync.aligned.u32 %0;" :: "n"(504 - 2 * RP));
        const uint32_t lane0 = pin(tid & 31);
        const uint32_t lane = lane0, n = blockIdx.x;
        volatile uint32_t* const misc = (volatile uint32_t*)(smem + R_MISC);
        const unsigned epoch = g_epoch[36 + n] + 1;
        uint32_t* const pa = (uint32_t*)((char*)g_acc + acc_blk(q & 1, n & 3) + 1536 + ((n >> 2) & 3) * 128 + ((n >> 4) & 1) * 32768 + (n >> 5) * 32);
        {
            const int t = tid - 256;
            if (t == 0) {
                mbar_init(bar + BX0, 1); mbar_init(bar + BX0 + 8, 1); mbar_init(bar + BX0 + 16, 1);
                mbar_init(bar + BSC, 1); mbar_init(bar + BME, 1); mbar_init(bar + BML, 1); mbar_arrive(bar + BME); mbar_arrive(bar + BML);
                mbar_init(bar + BVX, 1); mbar_init(bar + BVX + 8, 1);
                mbar_expect(bar + BSC, c == 2 ? 2304 : 2816); mbar_expect(bar + BVX, c == 2 ? 4096 : 6144);
                misc[M_TGT / 4 + 1] = 0; misc[M_ONE / 4] = 0x3f80u;
                misc[M_EPOCH / 4] = epoch; g_epoch[36 + n] = epoch;
                asm volatile("fence.mbarrier_init.release.cluster;" ::: "memory");
            }
            __syncwarp();
            cluster_arrive_rlx();
            uint32_t z;
            asm volatile("atom.relaxed.gpu.global.exch.b32 %0, [%1], %2;" : "=r"(z) : "l"((char*)g_acc + acc_slot(q) + acc_line(n >> 4, (n >> 2) & 3, n & 3) + lane * 4), "r"((lane & 3) == 3 ? EMPTY : 0) : "memory");
            if (lane < 2) stg_rlx((uint32_t*)((char*)g_acc + acc_slot(q) + acc_stamp(lane, n)), 0u);
            if (q < 2 && lane < 8) stg_rlx(pa + lane, 0u);
            uint32_t m0[3][6];
#pragma unroll
            for (int i = 0; i < 18; i++) m0[i / 6][i % 6] = __ldg((const uint32_t*)mem0 + (lane >> 2) * 288 + (q * 18 + i) * 4 + (lane & 3));
            const __nv_bfloat16* src = Wo + (size_t)h * 128 * DM;
#pragma unroll 4
            for (int i = 0; i < 24; i++) {
                const int idx = i * 128 + t, r = idx / 24, ch = idx - r * 24, qq = ch / 6, jq = (c + 3 - qq % 3) % 3;
                cp16(sb + R_WO + r * 384 + ((ch ^ ((r >> 1) & 3) * 2) << 4), src + r * DM + ((qq >> 1) * 36 + jq * 12 + (qq & 1) * 6 + ch - qq * 6) * 8);
            }
            cp_commit();
            cluster_wait();
            if (t == 0) {
                mbar_expect(bar + BX0, 36864);
                x_tma(sb + R_X0 + c * 12288, &maps.x, bar + BX0, 0, c * 3);
            }
            __syncwarp();
            {
                const uint32_t a = sb + R_MEM + (q & 1) * 6144 + (q >> 1) * 1024 + lane * 16;
#pragma unroll
                for (int i = 0; i < 6; i++) sts128(a + (i >> 1) * 2048 + (i & 1) * 512, m0[i >> 1][(i & 1) * 2], m0[i >> 1][(i & 1) * 2 + 1], m0[i >> 1][4 + (i & 1)], z & (lane >> 5));
            }
            asm volatile("fence.acq_rel.gpu;" ::: "memory");
            cp_wait<0>();
            bar_sync(NB_W2, 128);
            if (t == 0) stg_rlx(&g_pub[n], epoch);
            if (t == 32) asm volatile("cp.async.bulk.prefetch.L2.global [%0], 24576;" :: "l"((const char*)xraw + n * 24576) : "memory");
        }
        uint32_t wo[3][8][4];
        {
            const uint32_t g = lane >> 2, tq = lane & 3;
#pragma unroll
            for (int m = 0; m < 3; m++) {
                const uint32_t ch = 6 * q + (m < 2 ? (g >> 2) * 2 + m : 4 + (g >> 2));
                const uint32_t a = sb + R_WO + tq * 768 + ((ch ^ tq * 2) << 4) + (g & 3) * 4;
#pragma unroll
                for (int kk = 0; kk < 16; kk++) {
                    const uint32_t x = lds32(a + kk * 3072), y = lds32(a + kk * 3072 + 384);
                    wo[m][kk >> 1][(kk & 1) * 2] = __byte_perm(x, y, 0x5410);
                    wo[m][kk >> 1][(kk & 1) * 2 + 1] = __byte_perm(x, y, 0x7632);
                }
            }
        }
        bar_sync(0, 384);
        cluster_arrive_rlx(); cluster_wait();
        bar_arrive(NB_G1, 256);
        bar_arrive(NB_E0, 256);
        bar_arrive(NB_GO, 384);
        if (q >= 2 && lane == 0) {
            mbar_expect(bar + BX0 + (q - 1) * 8, 36864);
            x_tma(sb + (q - 1) * 36864 + c * 12288, &maps.x, bar + BX0 + (q - 1) * 8, (q - 1) * 32, c * 3);
        }
        __syncwarp();
        if (q < 2) { const uint32_t r = probe_rtt(pa); if (lane == 0) misc[M_PROBE / 4 + q] = r; }
        if (q == 3) {
            int it = 0;
            while (!__all_sync(0xffffffffu, ldg_rlx(&g_pub[lane]) == epoch && ldg_rlx(&g_pub[32 + lane]) == epoch && ldg_rlx(&g_pub[64 + lane]) == epoch))
                if (++it > (1 << 22)) TRAP(2000 + __LINE__);
        }
        bar_sync(NB_W2, 128);
        const uint32_t side = __shfl_sync(0xffffffffu, misc[M_PROBE / 4 + 1] < misc[M_PROBE / 4], 0);
        attn_loop(wo, &maps.x, maps.acc, smem, sb, c, q, lane0, side, (c + 3 - q % 3) % 3);
    }
    cluster_arrive_rlx(); cluster_wait();
    GT(0, 2);
}

constexpr int H_USTR = 32 * 144 + 16;
constexpr int H_U = 0;
constexpr int H_Z = H_U + 16 * H_USTR;
constexpr int H_W = 74752;
constexpr int H_WSTR = (2048 + 64) * 4;
constexpr int H_PAR = H_W + 8 * H_WSTR;
constexpr int H_KD = H_PAR + 4 * 2048;
constexpr int H_S4END = H_KD + 4 * 648 * 4;
constexpr int NST = 6;
constexpr int H_RING = H_W;
constexpr int H_XCH = H_RING + NST * 16384;
constexpr int H_QKV = H_XCH + 8192;
constexpr int H_AO = H_QKV + 30720;
constexpr int H_BAR = H_AO + 8192;
constexpr int H_SMEM = H_BAR + 512;
static_assert(H_Z + 256 <= H_W && H_S4END <= H_QKV && H_SMEM <= 232448 && H_RING % 1024 == 0, "smem");
enum { HB_FULL = 0  , HB_EMPTY = 64  , HB_WF = 128  , HB_WE = 192  , HB_QF = 256, HB_VF = 264, HB_QE = 272, HB_VE = 280, HB_OF = 288, HB_OE = 296 };
enum { HN_U = 1, HN_Y = 2, HN_P0 = 3, HN_P1 = 4, HN_X = 5   };

DEVI int slot_channel(int i) { return ((i >> 1) & 3) * 4 + (i >> 3) * 2 + (i & 1); }
#define LOAD_U(W)                                                                                                                      \
    _Pragma("unroll 1") for (int i0 = 0; i0 < 16; i0 += 4) {                                                                            \
        uint2 v[4][2];                                                                                                                  \
        _Pragma("unroll") for (int i = 0; i < 8; i++)                                                                                   \
            v[i >> 1][i & 1] = __ldg((const uint2*)(u + (size_t)(((W) * 16 + i0) * 16 + i * 8 + g) * DM + d0 + tq * 4));                \
        _Pragma("unroll") for (int i = 0; i < 4; i++) {                                                                                 \
            const int t0 = ((W) * 16 + i0 + i) * 16;                                                                                    \
            asm volatile("stmatrix.sync.aligned.m8n8.x4.trans.shared.b16 [%0], {%1,%2,%3,%4};"                                          \
                         :: "r"(sb + H_U + (lane & 15) * H_USTR + (t0 >> 6) * 144 + (t0 & 63) * 2 + (lane >> 4) * 16),                  \
                            "r"(v[i][0].x), "r"(v[i][0].y), "r"(v[i][1].x), "r"(v[i][1].y) : "memory");                                 \
        }                                                                                                                               \
    }
DEVI uint64_t desc_plain(uint32_t saddr, uint32_t lbo, uint32_t sbo) { return ((uint64_t)(sbo >> 4) << 32) | ((uint64_t)(lbo >> 4) << 16) | (uint64_t)((saddr & 0x3FFFF) >> 4); }
template <int ACC> DEVI void wgmma48_tt(float* d, uint64_t adesc, uint64_t bdesc) {
    asm volatile("wgmma.mma_async.sync.aligned.m64n48k16.f32.bf16.bf16 "
                 "{%0,%1,%2,%3,%4,%5,%6,%7,%8,%9,%10,%11,%12,%13,%14,%15,%16,%17,%18,%19,%20,%21,%22,%23}, %24, %25, %26, 1, 1, 1, 1;"
                 : "+f"(d[0]), "+f"(d[1]), "+f"(d[2]), "+f"(d[3]), "+f"(d[4]), "+f"(d[5]), "+f"(d[6]), "+f"(d[7]),
                   "+f"(d[8]), "+f"(d[9]), "+f"(d[10]), "+f"(d[11]), "+f"(d[12]), "+f"(d[13]), "+f"(d[14]), "+f"(d[15]),
                   "+f"(d[16]), "+f"(d[17]), "+f"(d[18]), "+f"(d[19]), "+f"(d[20]), "+f"(d[21]), "+f"(d[22]), "+f"(d[23])
                 : "l"(adesc), "l"(bdesc), "n"(ACC));
}
template <int ACC> DEVI void wgmma64(float* d, const uint32_t* a, uint64_t desc) {
    asm volatile("wgmma.mma_async.sync.aligned.m64n64k16.f32.bf16.bf16 "
                 "{%0,%1,%2,%3,%4,%5,%6,%7,%8,%9,%10,%11,%12,%13,%14,%15,%16,%17,%18,%19,%20,%21,%22,%23,%24,%25,%26,%27,%28,%29,%30,%31}, {%32,%33,%34,%35}, %36, %37, 1, 1, 0;"
                 : "+f"(d[0]), "+f"(d[1]), "+f"(d[2]), "+f"(d[3]), "+f"(d[4]), "+f"(d[5]), "+f"(d[6]), "+f"(d[7]),
                   "+f"(d[8]), "+f"(d[9]), "+f"(d[10]), "+f"(d[11]), "+f"(d[12]), "+f"(d[13]), "+f"(d[14]), "+f"(d[15]),
                   "+f"(d[16]), "+f"(d[17]), "+f"(d[18]), "+f"(d[19]), "+f"(d[20]), "+f"(d[21]), "+f"(d[22]), "+f"(d[23]),
                   "+f"(d[24]), "+f"(d[25]), "+f"(d[26]), "+f"(d[27]), "+f"(d[28]), "+f"(d[29]), "+f"(d[30]), "+f"(d[31])
                 : "r"(a[0]), "r"(a[1]), "r"(a[2]), "r"(a[3]), "l"(desc), "n"(ACC));
}
DEVI uint2 ldg_rlx2(const void* p) { uint2 v; asm volatile("ld.relaxed.gpu.global.v2.u32 {%0,%1}, [%2];" : "=r"(v.x), "=r"(v.y) : "l"(p) : "memory"); return v; }
DEVI unsigned ldg_acq(const unsigned* p) { unsigned v; asm volatile("ld.acquire.gpu.global.u32 %0, [%1];" : "=r"(v) : "l"(p) : "memory"); return v; }
DEVI void csq(float& x, float& y) { const float a = fmaf(x, x, -y * y), b = 2.f * x * y; x = a; y = b; }
DEVI uint32_t tf(float x) { return __float_as_uint(x) + 0x1000u; }
DEVI void cexp_turns(float l2mag, float turns, float& x, float& y) {
    const float m = ex2(l2mag), a = (turns - rintf(turns)) * 6.283185307179586f;
    x = m * __cosf(a); y = m * __sinf(a);
}

__global__ void __launch_bounds__(512, 1)
hk_kernel(const __nv_bfloat16* __restrict__ Wo, const __nv_bfloat16* __restrict__ u,
          const __nv_bfloat16* __restrict__ logA, const __nv_bfloat16* __restrict__ Aim, const __nv_bfloat16* __restrict__ Cre,
          const __nv_bfloat16* __restrict__ Cim, const __nv_bfloat16* __restrict__ logdt, const __nv_bfloat16* __restrict__ Dsk,
          __nv_bfloat16* __restrict__ out) {
    extern __shared__ __align__(1024) unsigned char smem[];
    const uint32_t sb = smem_u32(smem);
    const int tid = threadIdx.x, lane = tid & 31, warp = __shfl_sync(0xffffffffu, tid >> 5, 0), g = lane >> 2, tq = lane & 3;
    const int cta = blockIdx.x, nt = cta % 9, kg = cta / 9;
    const uint32_t bar = sb + H_BAR;
    const int d0 = cta * 16;
    const uint32_t tstart = clk();
    if (tid == 0) {
        for (int i = 0; i < NST; i++) { mbar_init(bar + HB_FULL + i * 8, 1); mbar_init(bar + HB_EMPTY + i * 8, 4); }
        for (int i = 0; i < 16; i++) mbar_init(bar + HB_WF + i * 8, 1);
        mbar_init(bar + HB_QF, 1); mbar_init(bar + HB_VF, 1); mbar_init(bar + HB_QE, 4); mbar_init(bar + HB_VE, 4); mbar_init(bar + HB_OF, 4); mbar_init(bar + HB_OE, 1);
        asm volatile("fence.proxy.async.shared::cta;" ::: "memory");
    }
    const unsigned epoch = g_epoch[cta] + 1;
    __syncthreads();
    if (tid == 0) g_epoch[cta] = epoch;
    if (warp < 8) {
        asm volatile("setmaxnreg.inc.sync.aligned.u32 176;");
        HEV(0); GT(96, 0);
        const int pr = warp & 3;
        float4* par = (float4*)(smem + H_PAR + pr * 2048);
        float* kd = (float*)(smem + H_KD + pr * 648 * 4);
        for (int i = lane; i < 64; i += 32) ((uint32_t*)(smem + H_W + (pr * 2 + (warp >> 2)) * H_WSTR))[i] = 0;
        HEV(1);
        if (!(HM & 1)) bar_sync(HN_U, 384);
#pragma unroll 1
        for (int it = 0; it < ((HM & 1) ? (warp < 4 ? 3 : 5) : 0); it++) {
            const int rnd = min(it, 3), ch = rnd * 4 + pr, d = d0 + slot_channel(ch);
            uint32_t* wz = (uint32_t*)(smem + H_W + (pr * 2 + (rnd & 1)) * H_WSTR);
            if (warp >= 4 && it < 4) {
            const float dt = bf2f(__float2bfloat16(expf(bf2f(logdt[d]))));
#pragma unroll
            for (int n = lane; n < 128; n += 32) {
                const float ar = -bf2f(__float2bfloat16(expf(bf2f(logA[d * 128 + n])))) * dt, ai = bf2f(Aim[d * 128 + n]) * dt;
                par[n] = make_float4(ar * 1.4426950408889634f, ai * 0.15915494309189535f, 2.f * bf2f(Cre[d * 128 + n]) * dt, 2.f * bf2f(Cim[d * 128 + n]) * dt);
            }
            __syncwarp();
            float kacc[5][4], klast = 0.f;
#pragma unroll
            for (int i = 0; i < 5; i++) kacc[i][0] = kacc[i][1] = kacc[i][2] = kacc[i][3] = 0.f;
            const float fa = (float)g, fb = (float)(g + 8);
            float4 pn[4];
#pragma unroll
            for (int i = 0; i < 4; i++) pn[i] = par[4 * i + tq];
#pragma unroll 4
            for (int ks = 0; ks < 32; ks++) {
                const float4 p = pn[ks & 3];
                pn[ks & 3] = par[(4 * ks + 16 + tq) & 127];
                float ax, ay, bx, by;
                cexp_turns(p.x * fa, p.y * fa, ax, ay);
                cexp_turns(p.x * fb, p.y * fb, bx, by);
                uint32_t F[4][4];
#pragma unroll
                for (int r = 0; r < 4; r++) {
                    F[r][0] = tf(ax); F[r][1] = tf(bx); F[r][2] = tf(ay); F[r][3] = tf(by);
                    csq(ax, ay); csq(bx, by);
                }
                mma_tf32(kacc[0], F[0][0], F[0][1], F[0][2], F[0][3], tf(fmaf(p.z, ax, -p.w * ay)), tf(-fmaf(p.z, ay, p.w * ax)));
#pragma unroll
                for (int r = 0; r < 4; r++) {
                    mma_tf32(kacc[r + 1], F[r][0], F[r][1], F[r][2], F[r][3], tf(fmaf(p.z, bx, -p.w * by)), tf(-fmaf(p.z, by, p.w * bx)));
                    csq(bx, by);
                }
                klast += fmaf(p.z, bx, -p.w * by);
            }
#pragma unroll
            for (int i = 0; i < 5; i++) {
                kd[i * 128 + 32 * tq + g] = kacc[i][0]; kd[i * 128 + 32 * tq + 16 + g] = kacc[i][1];
                kd[i * 128 + 32 * tq + g + 8] = kacc[i][2]; kd[i * 128 + 32 * tq + 24 + g] = kacc[i][3];
            }
            klast += __shfl_xor_sync(0xffffffffu, klast, 1);
            klast += __shfl_xor_sync(0xffffffffu, klast, 2);
            if (lane == 0) kd[640] = klast;
            __syncwarp();
            if (rnd >= 2) mbar_wait(bar + HB_WE + (pr * 2 + (rnd & 1)) * 8, 0);
#define RIDX(l, r) ((r) * 128 + (((l) + (1 << (r) >> 1) - 1 + (((l) >> (r)) & 1)) >> (r)))
#pragma unroll
            for (int x0 = 0; x0 < 256; x0 += 32) wz[64 + x0 + lane] = pack2(kd[x0 + lane], x0 + lane ? kd[x0 + lane - 1] : 0.f);
#pragma unroll
            for (int r = 1; r < 4; r++) {
                const int l0 = (128 << r) + lane;
                const float* k0 = kd + RIDX(l0, r);
                const float* k1 = kd + RIDX(l0 - 1, r);
#pragma unroll 8
                for (int i = 0; i < (4 << r); i++) wz[64 + l0 + 32 * i] = pack2(k0[i * (32 >> r)], k1[i * (32 >> r)]);
            }
#undef RIDX
            __syncwarp();
            if (lane == 0) wz[64 + 256] = pack2(kd[256], kd[255]);
            __syncwarp();
            if (lane == 0) mbar_arrive(bar + HB_WF + (pr * 2 + (rnd & 1)) * 8);
            if (rnd == 0) bar_sync(HN_U, 384);
            continue;
            }
            if (it == 0) { spin_until(tstart + UDLY); LOAD_U(warp) bar_sync(HN_U, 384); }
            mbar_wait(bar + HB_WF + (pr * 2 + (rnd & 1)) * 8, rnd >> 1);
            if (it == 0) HEV(2);
            float acc[4][4][4];
#pragma unroll
            for (int G = 0; G < 4; G++)
#pragma unroll
                for (int i = 0; i < 4; i++) acc[G][i][0] = acc[G][i][1] = acc[G][i][2] = acc[G][i][3] = 0.f;
            const uint32_t ub = sb + H_U + ch * H_USTR + (lane >> 3) * 16, zb = sb + H_Z + (lane >> 3) * 16;
            const uint32_t* wp = wz + 64 - 56 + g - 2 * tq;
            uint32_t Pn[15];
#pragma unroll
            for (int k = 0; k < 15; k++) Pn[k] = wp[8 * k];
            uint32_t bn[2][4];
            ldsm4(bn[0], ub + (24 + (lane & 7)) * 144); ldsm4(bn[1], ub + (24 + (lane & 7)) * 144 + 64);
#define CONV_RANGE(G0)                                                                                                  \
    _Pragma("unroll 1") for (int s = 8 * (G0); s < 8 * (G0) + 8; s++) {                                                  \
        uint32_t P[15], b[4][2][4];                                                                                      \
        _Pragma("unroll") for (int k = 0; k < 4; k++) { b[3][0][k] = bn[0][k]; b[3][1][k] = bn[1][k]; }                  \
        _Pragma("unroll") for (int G = 2; G >= (G0); G--) {                                                              \
            const int cidx = 8 * G + (lane & 7) - s;                                                                     \
            const uint32_t ba = (G > (G0) || cidx >= 0) ? ub + cidx * 144 : zb;                                          \
            ldsm4(b[G][0], ba); ldsm4(b[G][1], ba + 64);                                                                 \
        }                                                                                                                \
        {                                                                                                                \
            const int cidx = 23 + (lane & 7) - s;                                                                        \
            const uint32_t ba = cidx >= 0 ? ub + cidx * 144 : zb;                                                        \
            ldsm4(bn[0], ba); ldsm4(bn[1], ba + 64);                                                                     \
        }                                                                                                                \
        _Pragma("unroll") for (int k = 0; k < 15; k++) P[k] = Pn[k];                                                     \
        _Pragma("unroll") for (int k = 0; k < 7; k++) Pn[k] = P[k + 8];                                                  \
        _Pragma("unroll") for (int k = 7; k < 15; k++) Pn[k] = wp[64 * min(s + 1, 31) + 8 * k];                          \
        _Pragma("unroll") for (int G = 3; G >= (G0); G--)                                                                \
            _Pragma("unroll") for (int j = 0; j < 4; j++)                                                                \
                _Pragma("unroll") for (int i = 0; i < 4; i++) {                                                          \
                    const int k = 2 * (i - j) + 7;                                                                       \
                    mma16(acc[G][i], P[k], P[k + 1], P[k - 1], P[k], b[G][j >> 1][(j & 1) * 2], b[G][j >> 1][(j & 1) * 2 + 1]); \
                }                                                                                                        \
    }
            CONV_RANGE(0) CONV_RANGE(1) CONV_RANGE(2) CONV_RANGE(3)
#undef CONV_RANGE
            __syncwarp();
            if (lane == 0) mbar_arrive(bar + HB_WE + (pr * 2 + (rnd & 1)) * 8);
            if (it == 0) HEV(3);
            const float dsk = bf2f(Dsk[d]);
#pragma unroll
            for (int G = 0; G < 4; G++)
#pragma unroll
                for (int i = 0; i < 4; i++)
#pragma unroll
                    for (int j = 0; j < 4; j++) {
                        __nv_bfloat16* p = (__nv_bfloat16*)(smem + H_U + ch * H_USTR + (8 * G + 2 * tq + (j & 1)) * 144 + (16 * i + g + (j >> 1) * 8) * 2);
                        const float y = bf2f(__float2bfloat16(acc[G][i][j])), sk = bf2f(__float2bfloat16(bf2f(*p) * dsk));
                        *p = __float2bfloat16(y + sk);
                    }
        }
        HEV(4); GT(96, 1);
        const int wg = warp >> 2, q = warp & 3, t = tid & 127;
        fence_smem_async();
        bar_arrive(HN_Y, 320);
        uint32_t w[32][4];
        {
            const uint32_t* src = (const uint32_t*)(Wo + (size_t)(kg * 1024 + wg * 512 + tq * 8) * DM + nt * 64 + q * 16) + g;
#pragma unroll
            for (int i = 0; i < 64; i++) {
                const int row = (i >> 2) * 32 + (i & 3) * 2;
                const uint32_t x = __ldg(src + row * (DM / 2)), y = __ldg(src + (row + 1) * (DM / 2));
                w[i >> 1][(i & 1) * 2] = __byte_perm(x, y, 0x5410);
                w[i >> 1][(i & 1) * 2 + 1] = __byte_perm(x, y, 0x7632);
            }
        }
        HEV(5);
        const uint32_t xa = sb + H_XCH + t * 16;
        if (wg == 1) bar_arrive(HN_P0, 256);
#define PROJECT(OWN, OTHER)                                                                                              \
    float d[16];                                                                                                         \
    {                                                                                                                    \
        const int n = 4 * s + 2 * wg, r = n / NST, st = n - r * NST;   \
        const uint32_t dl = desc_lo(sb + H_RING + st * 16384);                                                           \
        mbar_wait(bar + HB_FULL + st * 8, r & 1);                                                                        \
        bar_sync(OWN, 256);                                                                                              \
        wg_fence();                                                                                                      \
        wgmma32<0>(d, w[0], desc_of(dl));                                                                                \
        _Pragma("unroll") for (int i = 1; i < 16; i++) wgmma32<1>(d, w[i], desc_of(dl + (i >> 2) * 256 + (i & 3) * 2));  \
        wg_commit();                                                                                                     \
        mbar_wait(bar + HB_FULL + st * 8 + 8, r & 1);                                                                    \
        wg_fence();                                                                                                      \
        _Pragma("unroll") for (int i = 16; i < PPT; i++) wgmma32<1>(d, w[i], desc_of(dl + (i >> 2) * 256 + (i & 3) * 2)); \
        bar_arrive(OTHER, 256);                                                                                          \
        _Pragma("unroll") for (int i = PPT; i < 32; i++) wgmma32<1>(d, w[i], desc_of(dl + (i >> 2) * 256 + (i & 3) * 2)); \
        wg_commit();                                                                                                     \
        asm volatile("wgmma.wait_group.sync.aligned 1;" ::: "memory");                                                   \
        mbar_arrive_warp(bar + HB_EMPTY + st * 8);                                                                       \
        wg_wait0();                                                                                                      \
        mbar_arrive_warp(bar + HB_EMPTY + st * 8 + 8);                                                                   \
    }
        if (wg == 0) {
            const uint2* const src = &g_part[0][nt][kg][0][t];
            uint32_t* const dst = (uint32_t*)(out + (size_t)(kg * 8 + 2 * tq) * OUTW + nt * 64 + q * 16) + g;
#pragma unroll 1
            for (int s = 0; s < ((HM & 4) ? NSEG + 2 : 0); s++) {
                if (s < NSEG) {
                    HS(0);
                    PROJECT(HN_P0, HN_P1)
                    HS(2);
                    sts128(xa + (s & 1) * 4096, pack2(d[0], d[2]), pack2(d[1], d[3]), pack2(d[4], d[6]), pack2(d[5], d[7]));
                    sts128(xa + (s & 1) * 4096 + 2048, pack2(d[8], d[10]), pack2(d[9], d[11]), pack2(d[12], d[14]), pack2(d[13], d[15]));
                }
                if (s >= 2) {
                    const int f = s - 2;
                    const uint32_t ph = ((f >> 2) + 1) & 1;
                    uint2 v[4];
                    for (int it = 0;;) {
#pragma unroll
                        for (int i = 0; i < 4; i++) v[i] = ldg_rlx2(src + (f & 3) * (9 * 4 * 4 * 128) + i * 128);
                        if (!__any_sync(0xffffffffu, (or3(diff2(v[0].x, v[0].y, ph), diff2(v[1].x, v[1].y, ph), diff2(v[2].x, v[2].y, ph)) | diff2(v[3].x, v[3].y, ph)) & 1)) break;
                        if (++it > (1 << 22)) TRAP(2000 + __LINE__);
                    }
                    dst[(size_t)f * 32 * (OUTW / 2)] = pack2((bflo(v[0].x) + bflo(v[1].x)) + (bflo(v[2].x) + bflo(v[3].x)), (bfhi(v[0].x) + bfhi(v[1].x)) + (bfhi(v[2].x) + bfhi(v[3].x)));
                    dst[((size_t)f * 32 + 1) * (OUTW / 2)] = pack2((bflo(v[0].y) + bflo(v[1].y)) + (bflo(v[2].y) + bflo(v[3].y)), (bfhi(v[0].y) + bfhi(v[1].y)) + (bfhi(v[2].y) + bfhi(v[3].y)));
                }
                if (s < NSEG) bar_arrive(HN_X + (s & 1), 256);
                HS(4);
            }
            if (HM & 4) bar_sync(HN_P0, 256);
        } else {
            uint2* const dst = &g_part[0][nt][0][kg][t];
#pragma unroll 1
            for (int s = 0; s < ((HM & 4) ? NSEG : 0); s++) {
                PROJECT(HN_P1, HN_P0)
                bar_sync(HN_X + (s & 1), 256);
                const uint4 oa = lds128(xa + (s & 1) * 4096), ob = lds128(xa + (s & 1) * 4096 + 2048);
                const uint32_t o[8] = {oa.x, oa.y, oa.z, oa.w, ob.x, ob.y, ob.z, ob.w};
                const uint32_t ph = ((s >> 2) + 1) & 1, rnd = ph ? 0u : 0x10000u;
#pragma unroll
                for (int j = 0; j < 4; j++) {
                    uint32_t wd[2];
#pragma unroll
                    for (int e = 0; e < 2; e++) {
                        const uint32_t lo = __float_as_uint(d[4 * j + e] + bflo(o[2 * j + e])) + rnd, hi = __float_as_uint(d[4 * j + 2 + e] + bfhi(o[2 * j + e])) + 0x8000u;
                        wd[e] = (__byte_perm(lo, hi, 0x7632) & 0xfffffffeu) | ph;
                    }
                    asm volatile("st.relaxed.gpu.global.v2.u32 [%0], {%1,%2};" :: "l"(dst + (s & 3) * (9 * 4 * 4 * 128) + j * 512), "r"(wd[0]), "r"(wd[1]) : "memory");
                }
                HS(3);
            }
        }
#undef PROJECT
    } else if (warp < 12) {
        asm volatile("setmaxnreg.dec.sync.aligned.u32 48;");
        if (tid - 256 < 64) ((uint32_t*)(smem + H_Z))[tid - 256] = 0;
        spin_until(tstart + UDLY);
        LOAD_U(warp - 4)
        bar_arrive(HN_U, 384);
        const int hd = kg * 8 + nt;
        if (warp == 8) {
            bar_sync(HN_Y, 320);
            int ready = 0;
#pragma unroll 1
            for (int s = 0; s < ((HM & 4) ? NSEG : 0); s++) {
                for (int it = 0; ready <= s;) {
                    unsigned v = epoch;
                    if (s + (lane >> 3) < NSEG) v = ldg_acq(&g_oflag[s + (lane >> 3)][kg * 8 + (lane & 7)][0]);
                    const uint32_t miss = ~__ballot_sync(0xffffffffu, v == epoch);
                    ready = s + (miss ? (__ffs(miss) - 1) >> 3 : 4);
                    if (++it > (1 << 24)) TRAP(2000 + __LINE__);
                }
                asm volatile("fence.proxy.async.global;" ::: "memory");
#pragma unroll 1
                for (int i = 0; i < 4; i++) {
                    const int n = 4 * s + i, r = n / NST, st = n - r * NST;
                    if (r > 0) mbar_wait(bar + HB_EMPTY + st * 8, (r - 1) & 1);
                    if (lane == 0) {
                        mbar_expect(bar + HB_FULL + st * 8, 16384);
                        bulk_g2s(sb + H_RING + st * 16384, (const char*)g_o + (size_t)(s * 64 + kg * 16 + i * 4) * 4096, 16384, bar + HB_FULL + st * 8);
                    }
                    __syncwarp();
                }
            }
        } else if (warp == 9) {
#pragma unroll 1
            for (int s = 0; s < ((HM & 2) && nt < 8 ? NSEG : 0); s++) {
                for (int it = 0; !__all_sync(0xffffffffu, ldg_acq(&g_qflag[s][hd][(lane % 3) * 8]) == epoch);)
                    if (++it > (1 << 24)) TRAP(2000 + __LINE__);
                HS(5);
                asm volatile("fence.proxy.async.global;" ::: "memory");
                const unsigned char* const src = g_qkv + (size_t)(s * 32 + hd) * 30720;
                if (s > 0) mbar_wait(bar + HB_QE, (s - 1) & 1);
                if (lane == 0) { mbar_expect(bar + HB_QF, 20480); bulk_g2s(sb + H_QKV, src, 20480, bar + HB_QF); }
                __syncwarp();
                if (s > 0) mbar_wait(bar + HB_VE, (s - 1) & 1);
                if (lane == 0) { mbar_expect(bar + HB_VF, 10240); bulk_g2s(sb + H_QKV + 20480, src + 20480, 10240, bar + HB_VF); }
                __syncwarp();
            }
        } else if (warp == 10) {
#pragma unroll 1
            for (int s = 0; s < ((HM & 2) && nt < 8 ? NSEG : 0); s++) {
                mbar_wait(bar + HB_OF, s & 1);
                if (lane == 0) {
                    bulk_s2g((char*)g_o + (size_t)(s * 64 + hd * 2) * 4096, sb + H_AO, 8192);
                    asm volatile("cp.async.bulk.commit_group;" ::: "memory");
                    asm volatile("cp.async.bulk.wait_group.read 0;" ::: "memory");
                    mbar_arrive(bar + HB_OE);
                    asm volatile("cp.async.bulk.wait_group 0;" ::: "memory");
                    stg_rlx(&g_oflag[s][hd][0], epoch);
                }
                __syncwarp();
                HS(6);
            }
        } else {
            bar_sync(HN_Y, 320);
#pragma unroll 1
            for (int i = 0; i < 128; i++) {
                const uint32_t t0 = clk();
                uint32_t v[4];
                ldsm4t(v, sb + H_U + (lane & 15) * H_USTR + (i >> 2) * 144 + (i & 3) * 32 + (lane >> 4) * 16);
                uint2* const p = (uint2*)(out + (size_t)(i * 16 + g) * OUTW + DM + d0 + tq * 4);
                p[0] = make_uint2(v[0], v[1]);
                p[8 * (OUTW / 4)] = make_uint2(v[2], v[3]);
                spin_until(t0 + YDLY);
            }
            asm volatile("griddepcontrol.wait;" ::: "memory");
        }
    } else {
        asm volatile("setmaxnreg.dec.sync.aligned.u32 112;");
        const uint32_t qk = sb + H_QKV;
        const int dg = 8 * (warp & 3) + g - 2 * tq;
        const uint32_t oa = pin(sb + H_AO + (8 * (warp & 3) + g) * 128);
#pragma unroll 1
        for (int s = 0; s < ((HM & 2) && nt < 8 ? NSEG : 0); s++) {
            float x[24];
            mbar_wait(bar + HB_QF, s & 1);
            wg_fence();
#pragma unroll
            for (int i = 0; i < 8; i++) {
                constexpr int QO[8] = {0, 1024, 2048, 7680, 8704, 9728, 15360, 16384}, KO[8] = {3072, 4608, 6144, 10752, 12288, 13824, 17408, 18944};
                if (i == 0) wgmma48_tt<0>(x, desc_plain(qk + QO[i], 128, 128), desc_plain(qk + KO[i], 128, 256));
                else wgmma48_tt<1>(x, desc_plain(qk + QO[i], 128, 128), desc_plain(qk + KO[i], 128, 256));
            }
            wg_commit();
            wg_wait0();
            mbar_arrive_warp(bar + HB_QE);
            x[16] += x[20]; x[17] += x[21];
            float m = fmaxf(x[16], x[17]);
#pragma unroll
            for (int b = 0; b < 4; b++) {
                if (8 * b > dg) x[4 * b] = NEG;
                if (8 * b + 1 > dg) x[4 * b + 1] = NEG;
                m = fmaxf(m, fmaxf(x[4 * b], x[4 * b + 1]));
            }
            m = fmaxf(m, __shfl_xor_sync(0xffffffffu, m, 1));
            m = fmaxf(m, __shfl_xor_sync(0xffffffffu, m, 2));
            float l = 0.f;
            uint32_t pa[3][4];
#pragma unroll
            for (int b = 0; b < 5; b++) {
                const float e0 = ex2(x[4 * b] - m), e1 = ex2(x[4 * b + 1] - m);
                l += e0 + e1;
                pa[b >> 1][(b & 1) * 2] = pack2(e0, e1);
                pa[b >> 1][(b & 1) * 2 + 1] = 0;
            }
            pa[2][2] = pa[2][3] = 0;
            l += __shfl_xor_sync(0xffffffffu, l, 1);
            l = rcp_fast(l + __shfl_xor_sync(0xffffffffu, l, 2));
            uint32_t ow[2][8];
            mbar_wait(bar + HB_VF, s & 1);
#pragma unroll
            for (int hf = 0; hf < 2; hf++) {
                float o[32];
                wg_fence();
                wgmma64<0>(o, pa[0], desc_plain(qk + 20480 + hf * 128, 256, 1024));
                wgmma64<1>(o, pa[1], desc_plain(qk + 20480 + 512 + hf * 128, 256, 1024));
                wgmma64<1>(o, pa[2], desc_plain(qk + 28672 + hf * 128, 0, 256));
                wg_commit();
                if (hf == 0 && s > 0) mbar_wait(bar + HB_OE, (s - 1) & 1);
                wg_wait0();
#pragma unroll
                for (int i = 0; i < 8; i++) ow[hf][i] = pack2(o[4 * i] * l, o[4 * i + 1] * l);
            }
            mbar_arrive_warp(bar + HB_VE);
#pragma unroll
            for (int grp = 0; grp < 4; grp++)
                sts128(oa + (grp >> 1) * 4096 + ((((grp & 1) * 4 + tq) ^ g) << 4), ow[0][2 * grp], ow[1][2 * grp], ow[0][2 * grp + 1], ow[1][2 * grp + 1]);
            fence_smem_async();
            mbar_arrive_warp(bar + HB_OF);
        }
    }
}

typedef CUresult (*EncodeFn)(CUtensorMap*, CUtensorMapDataType, cuuint32_t, void*, const cuuint64_t*, const cuuint64_t*, const cuuint32_t*,
                             const cuuint32_t*, CUtensorMapInterleave, CUtensorMapSwizzle, CUtensorMapL2promotion, CUtensorMapFloatOOBfill);

static void make_map(EncodeFn enc, CUtensorMap* m, void* base, int width, int boxchunks) {
    cuuint64_t dims[3] = {64, 2048, (cuuint64_t)(width / 64)};
    cuuint64_t strides[2] = {(cuuint64_t)width * 2, 128};
    cuuint32_t box[3] = {64, 32, (cuuint32_t)boxchunks};
    cuuint32_t es[3] = {1, 1, 1};
    enc(m, CU_TENSOR_MAP_DATA_TYPE_BFLOAT16, 3, base, dims, strides, box, es, CU_TENSOR_MAP_INTERLEAVE_NONE, CU_TENSOR_MAP_SWIZZLE_128B,
        CU_TENSOR_MAP_L2_PROMOTION_L2_256B, CU_TENSOR_MAP_FLOAT_OOB_FILL_NONE);
}

extern "C" void kernel_launch(void* const* d_in, const int* in_sizes, int n_in, void* d_out, int out_size) {
    typedef const __nv_bfloat16* P;
    static EncodeFn enc = nullptr;
    if (!enc) {
        void* fn = nullptr;
        cudaDriverEntryPointQueryResult st;
        cudaGetDriverEntryPoint("cuTensorMapEncodeTiled", &fn, cudaEnableDefault, &st);
        enc = (EncodeFn)fn;
        cudaFuncSetAttribute(rk_kernel, cudaFuncAttributeMaxDynamicSharedMemorySize, R_SMEM);
        cudaFuncSetAttribute(hk_kernel, cudaFuncAttributeMaxDynamicSharedMemorySize, H_SMEM);
    }
    Maps maps;
    make_map(enc, &maps.x, d_in[0], DM, 3);
    {
        void* acc = nullptr;
        cudaGetSymbolAddress(&acc, g_acc);
        for (int m = 0; m < 2; m++) {
            cuuint64_t dims[5] = {128, 2, 2, 2, 144};
            cuuint64_t strides[4] = {(cuuint64_t)(m ? 4096 : 12288), 1024, 16384, 256};
            cuuint32_t box[5] = {64, 2, 2, 2, 2}, es[5] = {1, 1, 1, 1, 1};
            enc(&maps.acc[m], CU_TENSOR_MAP_DATA_TYPE_BFLOAT16, 5, (char*)acc + m * 4096, dims, strides, box, es, CU_TENSOR_MAP_INTERLEAVE_NONE,
                CU_TENSOR_MAP_SWIZZLE_NONE, CU_TENSOR_MAP_L2_PROMOTION_NONE, CU_TENSOR_MAP_FLOAT_OOB_FILL_NONE);
        }
    }

    cudaLaunchConfig_t cfg = {};
    cudaLaunchAttribute at[1];
    cfg.gridDim = dim3(96); cfg.blockDim = dim3(384); cfg.dynamicSmemBytes = R_SMEM; cfg.stream = cudaStreamPerThread;
    at[0].id = cudaLaunchAttributeClusterDimension; at[0].val.clusterDim.x = 3; at[0].val.clusterDim.y = 1; at[0].val.clusterDim.z = 1;
    cfg.attrs = at; cfg.numAttrs = 1;
    cudaLaunchKernelEx(&cfg, rk_kernel, maps, (P)d_in[0], (P)d_in[1], (P)d_in[2], (P)d_in[3], (P)d_in[4], (P)d_in[5]);

    cfg.gridDim = dim3(36); cfg.blockDim = dim3(512); cfg.dynamicSmemBytes = H_SMEM;
    at[0].id = cudaLaunchAttributeProgrammaticStreamSerialization; at[0].val.programmaticStreamSerializationAllowed = 1;
    cudaLaunchKernelEx(&cfg, hk_kernel, (P)d_in[5], (P)d_in[7], (P)d_in[8], (P)d_in[9], (P)d_in[10], (P)d_in[11], (P)d_in[12], (P)d_in[13],
                       (__nv_bfloat16*)d_out);
}
```

```cpp
#include <cuda_runtime.h>
#include <cuda_bf16.h>
#include <cuda_fp16.h>
#include <cuda.h>
#include <stdint.h>

#define DEVI __device__ __forceinline__

#define NEG __int_as_float(0xff800000)
constexpr int DM = 576, NSEG = 64, HD = 4096, OUTW = 1152;

#define HM 7
#define QW 4000
#define NPROBE 4
#define CT 1700
#define FE 85
#define DL 0
#define DMIN 150
#define DMAX 4000
#define BACKOFF 200
#define LW 4
#define TIE 0
#define C2ADJ 80
#define DST 260
#define VFE 0
#define EW 0
#define LB 12
#define NTR 3
#define RP 176
#define NW2 3
#define KT 4
#define DDUMP 520
#define DPUSH 300
#define GOE 1
#define LDM 0
#define XD 150
#define G1T 0
#define F0T 14
#define F1T 16
#define SUMV 0
#define UDLY 6000
#define YDLY 300
#define PPT 32
#define LAG 3
#define QR 8
#define N1 8

__device__ __align__(1024) __nv_bfloat16 g_o[2048 * HD];
__device__ __align__(65536) uint32_t g_acc[16384];
__device__ __align__(128) unsigned g_pub[96];
__device__ __align__(128) uint32_t g_part[8][9][8][8][128];
__device__ __align__(1024) unsigned char g_qkv[(size_t)NSEG * 32 * 30720];
__device__ __align__(128) unsigned g_qflag[NSEG][32][32];
__device__ __align__(128) unsigned g_oflag[NSEG][32][8];
__device__ unsigned g_epoch[36 + 96];
#define EV(i)
#define EVV(i, v)
#define EVX(i) 0
#define EVADD(i, v)
#define HS(i)
#define HEV(i)
#define GT(b, i)

#define TRAP(code) __trap()
#define LOC(v)
DEVI uint32_t smem_u32(const void* p) { return (uint32_t)__cvta_generic_to_shared(p); }
DEVI uint32_t clk() { uint64_t t; asm volatile("mov.u64 %0, %%clock64;" : "=l"(t) :: "memory"); return (uint32_t)t; }
DEVI uint32_t gtime() { uint64_t t; asm volatile("mov.u64 %0, %%globaltimer;" : "=l"(t) :: "memory"); return (uint32_t)t; }
DEVI void spin_until(uint32_t t) { while ((int)(clk() - t) < 0) {} }
DEVI void jit() {}
DEVI uint32_t mapa(uint32_t a, uint32_t r) { uint32_t o; asm("mapa.shared::cluster.u32 %0, %1, %2;" : "=r"(o) : "r"(a), "r"(r)); return o; }
DEVI void mbar_init(uint32_t b, uint32_t n) { asm volatile("mbarrier.init.shared::cta.b64 [%0], %1;" :: "r"(b), "r"(n) : "memory"); }
DEVI void mbar_expect(uint32_t b, uint32_t bytes) { asm volatile("mbarrier.arrive.expect_tx.shared::cta.b64 _, [%0], %1;" :: "r"(b), "r"(bytes) : "memory"); }
DEVI void mbar_arrive(uint32_t b) { asm volatile("mbarrier.arrive.shared::cta.b64 _, [%0];" :: "r"(b) : "memory"); }
DEVI bool mbar_try(uint32_t b, uint32_t parity) {
    uint32_t ok;
    asm volatile("{.reg .pred p; mbarrier.try_wait.parity.shared::cta.b64 p, [%1], %2; selp.u32 %0, 1, 0, p;}" : "=r"(ok) : "r"(b), "r"(parity) : "memory");
    return ok;
}
DEVI void mbar_wait(uint32_t b, uint32_t parity) {
    LOC(0x100 | (b & 0xff) | (parity << 12));
    asm volatile("{.reg .pred p, q; .reg .u32 n; mov.u32 n, 0;\n W: mbarrier.try_wait.parity.shared::cta.b64 p, [%0], %1;\n"
                 "add.u32 n, n, 1; setp.lt.and.u32 q, n, 0x40000, !p; @q bra W;}" :: "r"(b), "r"(parity) : "memory");
    LOC(0x300 | (b & 0xff));
    jit();
}
DEVI void bar_sync(int id, int n) { jit(); LOC(0x200 | id); asm volatile("bar.sync %0, %1;" :: "r"(id), "r"(n) : "memory"); LOC(0x400 | id); jit(); }
DEVI void bar_arrive(int id, int n) { jit(); asm volatile("bar.arrive %0, %1;" :: "r"(id), "r"(n) : "memory"); jit(); }
DEVI void cluster_sync() { asm volatile("barrier.cluster.arrive.release.aligned; barrier.cluster.wait.acquire.aligned;" ::: "memory"); }
DEVI void cluster_arrive_rlx() { asm volatile("barrier.cluster.arrive.relaxed.aligned;" ::: "memory"); }
DEVI void cluster_wait() { asm volatile("barrier.cluster.wait.aligned;" ::: "memory"); }
DEVI void fence_async() { asm volatile("fence.proxy.async;" ::: "memory"); }
DEVI void cp16(uint32_t dst, const void* src) { asm volatile("cp.async.cg.shared.global [%0], [%1], 16;" :: "r"(dst), "l"(src) : "memory"); }
DEVI void cp_commit() { asm volatile("cp.async.commit_group;" ::: "memory"); }
template <int N> DEVI void cp_wait() { asm volatile("cp.async.wait_group %0;" :: "n"(N) : "memory"); }
DEVI void ldsm4(uint32_t* r, uint32_t a) {
    asm volatile("ldmatrix.sync.aligned.m8n8.x4.shared.b16 {%0,%1,%2,%3}, [%4];" : "=r"(r[0]), "=r"(r[1]), "=r"(r[2]), "=r"(r[3]) : "r"(a) : "memory");
}
DEVI uint32_t tab1(uint32_t a) { uint32_t r; asm volatile("ldmatrix.sync.aligned.m8n8.x1.shared.b16 {%0}, [%1];" : "=r"(r) : "r"(a) : "memory"); return r; }
DEVI uint2 tab2(uint32_t a) { uint2 r; asm volatile("ldmatrix.sync.aligned.m8n8.x2.shared.b16 {%0,%1}, [%2];" : "=r"(r.x), "=r"(r.y) : "r"(a) : "memory"); return r; }
DEVI void ldsm4t(uint32_t* r, uint32_t a) {
    asm volatile("ldmatrix.sync.aligned.m8n8.x4.trans.shared.b16 {%0,%1,%2,%3}, [%4];" : "=r"(r[0]), "=r"(r[1]), "=r"(r[2]), "=r"(r[3]) : "r"(a) : "memory");
}
DEVI void mma16(float* d, uint32_t a0, uint32_t a1, uint32_t a2, uint32_t a3, uint32_t b0, uint32_t b1) {
    asm volatile("mma.sync.aligned.m16n8k16.row.col.f32.bf16.bf16.f32 {%0,%1,%2,%3}, {%4,%5,%6,%7}, {%8,%9}, {%0,%1,%2,%3};"
                 : "+f"(d[0]), "+f"(d[1]), "+f"(d[2]), "+f"(d[3]) : "r"(a0), "r"(a1), "r"(a2), "r"(a3), "r"(b0), "r"(b1));
}
DEVI void mma8(float* d, uint32_t a0, uint32_t a1, uint32_t b0) {
    asm volatile("mma.sync.aligned.m16n8k8.row.col.f32.bf16.bf16.f32 {%0,%1,%2,%3}, {%4,%5}, {%6}, {%0,%1,%2,%3};"
                 : "+f"(d[0]), "+f"(d[1]), "+f"(d[2]), "+f"(d[3]) : "r"(a0), "r"(a1), "r"(b0));
}
DEVI void mma_tf32(float* d, uint32_t a0, uint32_t a1, uint32_t a2, uint32_t a3, uint32_t b0, uint32_t b1) {
    asm volatile("mma.sync.aligned.m16n8k8.row.col.f32.tf32.tf32.f32 {%0,%1,%2,%3}, {%4,%5,%6,%7}, {%8,%9}, {%0,%1,%2,%3};"
                 : "+f"(d[0]), "+f"(d[1]), "+f"(d[2]), "+f"(d[3]) : "r"(a0), "r"(a1), "r"(a2), "r"(a3), "r"(b0), "r"(b1));
}
template <int ACC> DEVI void wgmma32(float* d, const uint32_t* a, uint64_t desc) {
    asm volatile("wgmma.mma_async.sync.aligned.m64n32k16.f32.bf16.bf16 "
                 "{%0,%1,%2,%3,%4,%5,%6,%7,%8,%9,%10,%11,%12,%13,%14,%15}, {%16,%17,%18,%19}, %20, %21, 1, 1, 0;"
                 : "+f"(d[0]), "+f"(d[1]), "+f"(d[2]), "+f"(d[3]), "+f"(d[4]), "+f"(d[5]), "+f"(d[6]), "+f"(d[7]),
                   "+f"(d[8]), "+f"(d[9]), "+f"(d[10]), "+f"(d[11]), "+f"(d[12]), "+f"(d[13]), "+f"(d[14]), "+f"(d[15])
                 : "r"(a[0]), "r"(a[1]), "r"(a[2]), "r"(a[3]), "l"(desc), "n"(ACC));
}
template <int ACC> DEVI void wgmma32_ss(float* d, uint64_t adesc, uint64_t desc) {
    asm volatile("wgmma.mma_async.sync.aligned.m64n32k16.f32.bf16.bf16 "
                 "{%0,%1,%2,%3,%4,%5,%6,%7,%8,%9,%10,%11,%12,%13,%14,%15}, %16, %17, %18, 1, 1, 1, 0;"
                 : "+f"(d[0]), "+f"(d[1]), "+f"(d[2]), "+f"(d[3]), "+f"(d[4]), "+f"(d[5]), "+f"(d[6]), "+f"(d[7]),
                   "+f"(d[8]), "+f"(d[9]), "+f"(d[10]), "+f"(d[11]), "+f"(d[12]), "+f"(d[13]), "+f"(d[14]), "+f"(d[15])
                 : "l"(adesc), "l"(desc), "n"(ACC));
}
DEVI void wg_fence() { asm volatile("wgmma.fence.sync.aligned;" ::: "memory"); }
DEVI void wg_commit() { asm volatile("wgmma.commit_group.sync.aligned;" ::: "memory"); }
DEVI void wg_wait0() { asm volatile("wgmma.wait_group.sync.aligned 0;" ::: "memory"); }
DEVI uint64_t desc_sw128(uint32_t saddr) { return ((uint64_t)1 << 62) | ((uint64_t)64 << 32) | ((uint64_t)1 << 16) | (uint64_t)((saddr & 0x3FFFF) >> 4); }
DEVI uint32_t desc_lo(uint32_t saddr) { return (1u << 16) | ((saddr & 0x3FFFF) >> 4); }
DEVI uint64_t desc_of(uint32_t lo) { uint64_t d; asm("mov.b64 %0, {%1, 0x40000040};" : "=l"(d) : "r"(lo)); return d; }
DEVI uint32_t pack2(float lo, float hi) { uint32_t r; asm("cvt.rn.bf16x2.f32 %0, %1, %2;" : "=r"(r) : "f"(hi), "f"(lo)); return r; }
DEVI void sts32(uint32_t a, uint32_t v) { asm volatile("st.shared.u32 [%0], %1;" :: "r"(a), "r"(v) : "memory"); }
DEVI void sts64f(uint32_t a, float x, float y) { asm volatile("st.shared.v2.f32 [%0], {%1,%2};" :: "r"(a), "f"(x), "f"(y) : "memory"); }
DEVI void sts128f(uint32_t a, float x, float y, float z, float w) { asm volatile("st.shared.v4.f32 [%0], {%1,%2,%3,%4};" :: "r"(a), "f"(x), "f"(y), "f"(z), "f"(w) : "memory"); }
DEVI float2 lds64f(uint32_t a) { float2 v; asm volatile("ld.shared.v2.f32 {%0,%1}, [%2];" : "=f"(v.x), "=f"(v.y) : "r"(a) : "memory"); return v; }
DEVI float4 lds128f(uint32_t a) { float4 v; asm volatile("ld.shared.v4.f32 {%0,%1,%2,%3}, [%4];" : "=f"(v.x), "=f"(v.y), "=f"(v.z), "=f"(v.w) : "r"(a) : "memory"); return v; }
DEVI uint4 lds128(uint32_t a) { uint4 v; asm volatile("ld.shared.v4.u32 {%0,%1,%2,%3}, [%4];" : "=r"(v.x), "=r"(v.y), "=r"(v.z), "=r"(v.w) : "r"(a) : "memory"); return v; }
DEVI uint4 ldm128(uint32_t a) {
    uint4 v;
    asm volatile("ld.shared.v4.u32 {%0,%1,%2,%3}, [%4];" : "=r"(v.x), "=r"(v.y), "=r"(v.z), "=r"(v.w) : "r"(a) : "memory");
    return v;
}
DEVI void sta32(uint32_t a, uint32_t v, uint32_t bar) { asm volatile("st.async.weak.shared::cluster.mbarrier::complete_tx::bytes.b32 [%0], %1, [%2];" :: "r"(a), "r"(v), "r"(bar) : "memory"); }
DEVI void sta64f(uint32_t a, float x, float y, uint32_t bar) { asm volatile("st.async.weak.shared::cluster.mbarrier::complete_tx::bytes.v2.f32 [%0], {%1,%2}, [%3];" :: "r"(a), "f"(x), "f"(y), "r"(bar) : "memory"); }
DEVI void sta128f(uint32_t a, float x, float y, float z, float w, uint32_t bar) {
    asm volatile("st.async.weak.shared::cluster.mbarrier::complete_tx::bytes.v4.f32 [%0], {%1,%2,%3,%4}, [%5];" :: "r"(a), "f"(x), "f"(y), "f"(z), "f"(w), "r"(bar) : "memory");
}
DEVI void stg_rlx(uint32_t* p, uint32_t v) { asm volatile("st.relaxed.gpu.global.u32 [%0], %1;" :: "l"(p), "r"(v) : "memory"); }
DEVI void stg_release(unsigned* p, unsigned v) { asm volatile("st.release.gpu.global.u32 [%0], %1;" :: "l"(p), "r"(v) : "memory"); }
DEVI uint32_t ldg_rlx(const uint32_t* p) { uint32_t v; asm volatile("ld.relaxed.gpu.global.u32 %0, [%1];" : "=r"(v) : "l"(p) : "memory"); return v; }
DEVI void bulk_g2s(uint32_t dst, const void* src, uint32_t bytes, uint32_t bar) {
    asm volatile("cp.async.bulk.shared::cluster.global.mbarrier::complete_tx::bytes [%0], [%1], %2, [%3];" :: "r"(dst), "l"(src), "r"(bytes), "r"(bar) : "memory");
}
DEVI void bulk_s2c(uint32_t dst, uint32_t src, uint32_t bytes, uint32_t bar) {
    asm volatile("cp.async.bulk.shared::cluster.shared::cta.mbarrier::complete_tx::bytes [%0], [%1], %2, [%3];" :: "r"(dst), "r"(src), "r"(bytes), "r"(bar) : "memory");
}
DEVI float ex2(float x) { float y; asm("ex2.approx.ftz.f32 %0, %1;" : "=f"(y) : "f"(x)); return y; }
DEVI float bf2f(__nv_bfloat16 v) { return __bfloat162float(v); }

DEVI uint32_t pin(uint32_t v) { return __shfl_sync(0xffffffffu, v, threadIdx.x & 31); }
template <typename T> DEVI T* pinp(T* p) { const uint64_t v = (uint64_t)p; return (T*)(((uint64_t)pin((uint32_t)(v >> 32)) << 32) | pin((uint32_t)v)); }
DEVI uint32_t fresh(uint32_t v) { uint32_t r; asm volatile("mov.u32 %0, %1;" : "=r"(r) : "r"(v)); return r; }
DEVI uint64_t fresh64(uint64_t v) { uint64_t r; asm volatile("mov.u64 %0, %1;" : "=l"(r) : "l"(v)); return r; }
DEVI uint32_t or3(uint32_t a, uint32_t b, uint32_t c) { uint32_t d; asm("lop3.b32 %0, %1, %2, %3, 0xfe;" : "=r"(d) : "r"(a), "r"(b), "r"(c)); return d; }
DEVI uint32_t and3(uint32_t a, uint32_t b, uint32_t c) { uint32_t d; asm("lop3.b32 %0, %1, %2, %3, 0x80;" : "=r"(d) : "r"(a), "r"(b), "r"(c)); return d; }
DEVI uint32_t diff2(uint32_t a, uint32_t b, uint32_t p) { uint32_t d; asm("lop3.b32 %0, %1, %2, %3, 0x7e;" : "=r"(d) : "r"(a), "r"(b), "r"(p)); return d; }
DEVI int lds32(uint32_t a) { int v; asm volatile("ld.volatile.shared.s32 %0, [%1];" : "=r"(v) : "r"(a) : "memory"); return v; }
DEVI uint2 lds64(uint32_t a) { uint2 v; asm volatile("ld.shared.v2.u32 {%0,%1}, [%2];" : "=r"(v.x), "=r"(v.y) : "r"(a) : "memory"); return v; }
DEVI void sts64(uint32_t a, uint32_t x, uint32_t y) { asm volatile("st.shared.v2.u32 [%0], {%1,%2};" :: "r"(a), "r"(x), "r"(y) : "memory"); }
DEVI void sta64(uint32_t a, uint32_t x, uint32_t y, uint32_t bar) { asm volatile("st.async.weak.shared::cluster.mbarrier::complete_tx::bytes.v2.b32 [%0], {%1,%2}, [%3];" :: "r"(a), "r"(x), "r"(y), "r"(bar) : "memory"); }
DEVI float rcp_fast(float x) { float y; asm("rcp.approx.ftz.f32 %0, %1;" : "=f"(y) : "f"(x)); return y; }
DEVI uint4 ldg_rlx4(const void* p) { uint4 v; asm volatile("ld.relaxed.gpu.global.v4.u32 {%0,%1,%2,%3}, [%4];" : "=r"(v.x), "=r"(v.y), "=r"(v.z), "=r"(v.w) : "l"(p) : "memory"); return v; }
DEVI void sts128(uint32_t a, uint32_t x, uint32_t y, uint32_t z, uint32_t w) { asm volatile("st.shared.v4.u32 [%0], {%1,%2,%3,%4};" :: "r"(a), "r"(x), "r"(y), "r"(z), "r"(w) : "memory"); }
DEVI void stsm4(uint32_t a, uint32_t x, uint32_t y, uint32_t z, uint32_t w) { asm volatile("stmatrix.sync.aligned.m8n8.x4.shared.b16 [%0], {%1,%2,%3,%4};" :: "r"(a), "r"(x), "r"(y), "r"(z), "r"(w) : "memory"); }
DEVI void stsm2(uint32_t a, uint32_t x, uint32_t y) { asm volatile("stmatrix.sync.aligned.m8n8.x2.shared.b16 [%0], {%1,%2};" :: "r"(a), "r"(x), "r"(y) : "memory"); }
DEVI void fence_smem_async() { asm volatile("fence.proxy.async.shared::cta;" ::: "memory"); }
DEVI uint32_t packh2(float lo, float hi) { uint32_t r; asm("cvt.rn.f16x2.f32 %0, %1, %2;" : "=r"(r) : "f"(hi), "f"(lo)); return r; }
DEVI uint32_t h2_to_bf2(uint32_t w) {
    uint32_t r;
    asm("{.reg .f16 l, h; .reg .f32 a, b; mov.b32 {l, h}, %1; cvt.f32.f16 a, l; cvt.f32.f16 b, h; cvt.rn.bf16x2.f32 %0, b, a;}" : "=r"(r) : "r"(w));
    return r;
}
DEVI uint32_t amax2(uint32_t m, uint32_t w) { return __vmaxu2(m, w & 0x7fff7fffu); }
DEVI uint32_t amax_fold(uint32_t m) { return __reduce_max_sync(0xffffffffu, max(m & 0xffffu, m >> 16)); }
DEVI float bflo(uint32_t w) { return __uint_as_float(w << 16); }
DEVI float bfhi(uint32_t w) { return __uint_as_float(w & 0xffff0000u); }
DEVI void red_b8(void* p, uint32_t a, uint32_t b, uint32_t c, uint32_t d) {
    asm volatile("red.relaxed.gpu.global.add.noftz.v4.bf16x2 [%0], {%1,%2,%3,%4};" :: "l"(p), "r"(a), "r"(b), "r"(c), "r"(d) : "memory");
}
DEVI void red_h8_if(bool on, void* p, uint32_t a, uint32_t b, uint32_t c, uint32_t d) {
    asm volatile("{.reg .pred p; setp.ne.u32 p, %5, 0; @p red.relaxed.gpu.global.add.noftz.v4.bf16x2 [%0], {%1,%2,%3,%4};}" :: "l"(p), "r"(a), "r"(b), "r"(c), "r"(d), "r"((uint32_t)on) : "memory");
}
DEVI void mbar_arrive_warp(uint32_t b) { asm volatile("{.reg .pred p; elect.sync _|p, 0xffffffff; @p mbarrier.arrive.shared::cta.b64 _, [%0];}" :: "r"(b) : "memory"); }
DEVI void bulk_s2c_warp(uint32_t dst, uint32_t src, uint32_t bytes, uint32_t bar) {
    asm volatile("{.reg .pred p; elect.sync _|p, 0xffffffff; @p cp.async.bulk.shared::cluster.shared::cta.mbarrier::complete_tx::bytes [%0], [%1], %2, [%3];}" :: "r"(dst), "r"(src), "r"(bytes), "r"(bar) : "memory");
}
DEVI char* mkptr(uint32_t lo, uint32_t hi) { uint64_t p; asm("mov.b64 %0, {%1, %2};" : "=l"(p) : "r"(lo), "r"(hi)); return (char*)p; }
DEVI void bulk_s2g(void* dst, uint32_t src, uint32_t bytes) { asm volatile("cp.async.bulk.global.shared::cta.bulk_group [%0], [%1], %2;" :: "l"(dst), "r"(src), "r"(bytes) : "memory"); }
DEVI void x_tma(uint32_t dst, const CUtensorMap* m, uint32_t xb, int row, int chunk) {
    asm volatile("cp.async.bulk.tensor.3d.shared::cluster.global.mbarrier::complete_tx::bytes.multicast::cluster [%0], [%1, {%3, %4, %5}], [%2], %6;"
                 :: "r"(dst), "l"(m), "r"(xb), "r"(0), "r"(row), "r"(chunk), "h"((uint16_t)7) : "memory");
}
#define RUNG_(A, B, PA, PB) "mov.u64 " A ", %%clock64;\n cvt.u32.u64 l, " B ";\n sub.s32 l, l, %0;\n setp.ge.s32 " PB ", l, 0;\n @" PA " bra.uni DONE;\n"
DEVI void fine_until(uint32_t t) {
    asm volatile("{.reg .pred p0, p1; .reg .b64 t0, t1; .reg .b32 l;\n setp.ne.u32 p0, 0, 0;\n mov.u64 t1, %%clock64;\n LOOP:\n"
                 RUNG_("t0", "t1", "p0", "p1") RUNG_("t1", "t0", "p1", "p0") RUNG_("t0", "t1", "p0", "p1") RUNG_("t1", "t0", "p1", "p0")
                 RUNG_("t0", "t1", "p0", "p1") RUNG_("t1", "t0", "p1", "p0") RUNG_("t0", "t1", "p0", "p1") RUNG_("t1", "t0", "p1", "p0")
                 "bra.uni LOOP;\n DONE:\n}" :: "r"(t) : "memory");
}
DEVI uint32_t clock_offset() {
    const uint32_t g0 = gtime();
    uint32_t e = clk();
#pragma unroll
    for (int i = 0; i < 7; i++) { const uint32_t g = gtime(), t = clk(); e = g == g0 ? t : e; }
    return ((((g0 >> 5) + 1) * 3686u) >> 6) - e;
}
DEVI uint32_t probe_rtt(uint32_t* a) {
    uint32_t best = 0xffffffffu;
#pragma unroll 1
    for (int r = 0; r < NPROBE; r++) {
        uint32_t v = 0, t0 = clk();
        if ((threadIdx.x & 31) == 0) asm volatile("atom.relaxed.gpu.global.exch.b32 %0, [%1], 0;" : "=r"(v) : "l"(a) : "memory");
        const uint32_t t1 = __shfl_sync(0xffffffffu, v, 0) == 0x9e3779b9u ? 0 : clk();
        best = min(best, t1 - t0);
    }
    return best;
}

constexpr int R_X0 = 0;
constexpr int R_WO = 36864;
constexpr int R_DBG = 110592;
constexpr int R_K = 114688 + 3072;
constexpr int R_V = R_K + 4608;
constexpr int R_VM = R_V + 8192;
constexpr int PAR = 17920;
constexpr int R_QM = R_VM + 2048 + PAR;
constexpr int R_SC = R_QM + 1536;
constexpr int R_O8 = R_SC + 2048;
constexpr int R_PX = R_O8 + 2048;
constexpr int R_PV = R_PX + 8192;
constexpr int R_Z = R_PV + 4096;
constexpr int R_T0 = R_Z + 512;
constexpr int R_T1 = R_T0 + 2048;
constexpr int R_T2 = R_T1 + 8192;
constexpr int R_T3 = R_T2 + 512;
constexpr int R_T4 = R_T3 + 2048;
constexpr int R_END = R_T4 + 4096;
constexpr int R_STAGE = 86016;
constexpr int R_MEM = 217088;
constexpr int R_BAR = R_MEM + 12288;
constexpr int R_MISC = R_BAR + 128;
constexpr int R_SMEM = R_MISC + 128;
static_assert(R_END <= R_STAGE + 7 * 16384, "smem");
enum { BX0 = 0  , BSC = 24, BME = 32, BVX = 40  , BML = 56 };
enum { NB_F1 = 1, NB_K = 5, NB_G1 = 6, NB_E0 = 7, NB_GO = 8, NB_W1 = 9, NB_H1 = 10, NB_TOK = 11, NB_W2 = 12, NB_F0 = 13, NB_L0 = 14   };
enum { M_EPOCH = 0, M_SINK = 4, M_PROBE = 8  , M_TGT = 16  , M_REF = 24  , M_ONE = 32, M_RING = 40   };
constexpr uint32_t EMPTY = 0xc200u;
constexpr float QS = 0.08838834764831845f * 1.4426950408889634f;

DEVI uint32_t acc_slot(uint32_t s) { return (s & 1) * 128 + (s & 2) * 16384; }
DEVI uint32_t acc_blk(uint32_t m, uint32_t l) { return (((l >> 1) << 2) | ((l & 1) << 1) | ((l & 1) ^ m)) * 4096; }
DEVI uint32_t acc_line(uint32_t i, uint32_t q, uint32_t l) { return acc_blk(q & 1, l) + (q >> 1) * 256 + (i < 4 ? i * 1024 : i * 1024 - 1536); }
DEVI uint32_t acc_stamp(uint32_t m, uint32_t n) { return acc_blk(m, n >> 5) + 512 + (n & 31) * 4; }

#define LOAD_TRANSIENT(LA) { _Pragma("unroll") for (int i_ = 0; i_ < NTR; i_++) ldsm4t(w[i_ & 1][i_ >> 1], (LA) + (i_ & 1) * 4096 + (i_ >> 1) * 2048); }
#define MMAW(D, T, K, B0, B1) mma16(D, w[T][K][0], w[T][K][1], w[T][K][2], w[T][K][3], B0, B1)

DEVI void proj_loop(uint32_t (&w)[2][18][4], unsigned char* smem, const uint32_t sb, const uint32_t c, const int wg, const int q, const uint32_t lane0) {
    const uint32_t bar = sb + R_BAR;
    const int p = q ^ (2 * wg);
    const bool c2 = c == 2, both = !c2 && p < 2, aq = c2 ? p < 2 : p != 2;
    const uint32_t lp = pin(sb + lane0 * 16 + p * 1024), ma = pin(sb + lane0 * 16 + wg * 1024);
    {
        const uint32_t l16 = sb + lane0 * 16;
        const int ia = c2 ? p & 1 : min(p, 2), vt = c2 ? 4 + p : 2 * c + p - 2;
        const uint32_t dtok = l16 + (wg ? (aq ? R_K - ((c2 ? 2 : 3) - ia) * 1024 : R_K + ia * 1536) : (both ? R_K + p * 1536 : R_V + vt * 1024));
        const uint32_t la = sb + R_STAGE + 7 * 16384 + wg * 8192 + (((lane0 >> 4) << 3) + (lane0 & 7)) * 128 + (((2 * q + ((lane0 >> 3) & 1)) ^ (lane0 & 7)) << 4);
        const bool lo = lane0 < 16, mq = aq && lo, mv = !both && !lo;
        const uint32_t dmem = sb + (mq ? R_QM + ia * 512 + (lane0 & 8) * 32 + wg * 128 : (mv ? R_PV + p * 1024 : R_K + ia * 1536 + 1024) + wg * 256 + (lane0 & 8) * 16) + (lane0 & 7) * 16;
        stsm4(lp + R_T4 + wg * 512, dtok, la, dmem, dmem + (mq || mv ? 0 : PAR));
        const uint32_t p0 = mapa(sb, c2 ? 0 : c + 1), p1 = mapa(sb, c == 0 ? 2 : c - 1), d = R_VM + vt * 256 + lane0 * 4;
        sts128(lp + R_PV + 512, p0 + d, p0 + R_BAR + BSC, p1 + d, p1 + R_BAR + BSC);
        __syncwarp();
        mbar_wait(bar + BX0, 0);
    }
#define PUBLISH(S) { asm volatile("cp.async.bulk.wait_group 0;" ::: "memory"); stg_rlx(&g_qflag[S][blockIdx.x / 3][c * 8], lds32(sb + R_MISC + M_RING + ((S) & 1) * 4)); }
#pragma unroll 1
    for (int s = 0; s < NSEG; s++) {
        const int xi = s - 3 * ((s * 43) >> 7);
        {
            float d[16];
#define TOKEN(WG, T, I0, I1, ZERO)                                                                                          \
    {                                                                                                                       \
    const uint32_t xd = fresh(desc_lo(sb + xi * 36864)), ad = fresh(desc_lo(sb + R_STAGE + 7 * 16384));                     \
    wg_fence();                                                                                                             \
    _Pragma("unroll") for (int i = I0; i < I1; i++) {                                                                       \
        const int j = i < 10 ? i + 2 : (i < 12 ? i - 10 : i), g = 18 * WG + j;                                              \
        const uint64_t bd = desc_of(xd + (g >> 2) * 256 + (g & 3) * 2);                                                     \
        if (2 * j + (T) < NTR) wgmma32_ss<1>(d, desc_of(ad + ((WG * 8192 + (T) * 4096 + j * 2048) >> 4)), bd);                          \
        else if (i == 0 && ZERO) wgmma32<0>(d, w[T][j], bd);                                                                \
        else wgmma32<1>(d, w[T][j], bd);                                                                                    \
    }                                                                                                                       \
    wg_commit();                                                                                                            \
    }
#define HANDOVER(WG)                                                                                                        \
    {                                                                                                                       \
        const uint32_t xa = lp + R_PX + WG * 4096;                                                                          \
        sts128(xa, pack2(d[0], d[1]), pack2(d[2], d[3]), pack2(d[4], d[5]), pack2(d[6], d[7]));                             \
        sts128(xa + 512, pack2(d[8], d[9]), pack2(d[10], d[11]), pack2(d[12], d[13]), pack2(d[14], d[15]));                 \
    }
            if (wg == 0) {
                bar_sync(NB_G1, 256);
                TOKEN(0, 0, 0, 18, 1)
                const uint32_t la = tab1(lp + R_T4 + 128);
                wg_wait0();
                EV(3);
                if (q == 1 && s > 0) {
                    const uint2 tt = tab2(lp + R_T2 - 1024);
                    const uint32_t tag = s << 22;
                    const char* const sp = mkptr(tt.x + acc_slot(s - 1), tt.y);
                    uint4 v = ldg_rlx4(sp);
                    bar_sync(NB_E0, 256);
                    HANDOVER(0)
                    bar_arrive(NB_GO, 384);
                    LOAD_TRANSIENT(la)
                    const uint2 tr = lds64(sb + R_MISC + M_REF);
                    int n = 0;
                    while (__any_sync(0xffffffffu, (diff2(v.x, v.y, tag) | diff2(v.z, v.w, tag)) >> 22)) {
                        v = ldg_rlx4(sp);
                        if (++n > (1 << 22)) TRAP(1002);
                    }
                    const int m = __reduce_max_sync(0xffffffffu, max(max((int)((v.x - tr.y) << 10), (int)((v.y - tr.y) << 10)), max((int)((v.z - tr.y) << 10), (int)((v.w - tr.y) << 10)))) >> 10;
                    sts64(sb + R_MISC + M_TGT, tr.x + min(m, DMAX) + (CT - 65), s);
                    EV(0);
                    if (EVX(0)) EVV(11, m);
                } else {
                    bar_sync(NB_E0, 256);
                    HANDOVER(0)
                    bar_arrive(NB_GO, 384);
                    LOAD_TRANSIENT(la)
                }
                bar_sync(NB_F0, 256);
                TOKEN(0, 1, 0, F1T, 1)
                bar_arrive(NB_F1, 256);
                TOKEN(0, 1, F1T, 18, 0)
                const uint32_t dtok = tab1(lp + R_T4) + (s & 1) * PAR;
                bar_sync(NB_H1, 256);
                const uint4 oa = lds128(lp + R_PX + 4096);
                wg_wait0();
                const uint32_t u0 = pack2(d[0] + bflo(oa.x), d[1] + bfhi(oa.x)), u1 = pack2(d[2] + bflo(oa.y), d[3] + bfhi(oa.y));
                const uint4 ob = lds128(lp + R_PX + 4608);
                stsm4(dtok, u0, u1, pack2(d[4] + bflo(oa.z), d[5] + bfhi(oa.z)), pack2(d[6] + bflo(oa.w), d[7] + bfhi(oa.w)));
                stsm4(dtok + 512, pack2(d[8] + bflo(ob.x), d[9] + bfhi(ob.x)), pack2(d[10] + bflo(ob.y), d[11] + bfhi(ob.y)),
                      pack2(d[12] + bflo(ob.z), d[13] + bfhi(ob.z)), pack2(d[14] + bflo(ob.w), d[15] + bfhi(ob.w)));
                bar_arrive(NB_TOK, 384);
            } else {
                const uint2 tw = tab2(lp + R_T4 + 512);
                bar_sync(NB_GO, 384);
                TOKEN(1, 1, 0, F0T, 1)
                bar_arrive(NB_F0, 256);
                TOKEN(1, 1, F0T, 18, 0)
                const uint4 oa = lds128(lp + R_PX), ob = lds128(lp + R_PX + 512);
                wg_wait0();
                HANDOVER(1)
                bar_arrive(NB_H1, 256);
                {
                    const uint32_t ox[8] = {oa.x, oa.y, oa.z, oa.w, ob.x, ob.y, ob.z, ob.w};
#pragma unroll
                    for (int j = 0; j < 8; j++) { d[2 * j] = bflo(ox[j]); d[2 * j + 1] = bfhi(ox[j]); }
                }
                LOAD_TRANSIENT(tw.y)
                bar_sync(NB_F1, 256);
                TOKEN(1, 0, 0, 18, 0)
                if (q == 3 && s > 0) PUBLISH(s - 1)
                const float qs = aq ? QS : 1.f;
                const uint32_t dtok = tw.x + (s & 1) * PAR;
                wg_wait0();
                EV(13);
#pragma unroll
                for (int hf = 0; hf < 2; hf++) {
                    const float* e = d + 8 * hf;
                    stsm4(dtok + hf * 512, pack2(e[0] * qs, e[1] * qs), pack2(e[2] * qs, e[3] * qs), pack2(e[4] * qs, e[5] * qs), pack2(e[6] * qs, e[7] * qs));
                }
                EV(12);
                bar_arrive(NB_TOK, 384);
            }
#undef TOKEN
#undef HANDOVER
        }
        uint4 b[12];
        float a[4][4];
        int pass = 0;
      redo:
        mbar_wait(bar + BME, s & 1);
#pragma unroll
        for (int j = 0; j < 4; j++) a[0][j] = a[1][j] = a[2][j] = a[3][j] = 0.f;
#pragma unroll
        for (int i = 0; i < 4; i++) b[i] = ldm128(ma + R_MEM + (i >> 1) * 2048 + (i & 1) * 512);
#define BK0(k) ((k) % 3 == 2 ? b[(k) / 3 * 2].z : b[(k) / 3 * 2 + (k) % 3].x)
#define BK1(k) ((k) % 3 == 2 ? b[(k) / 3 * 2].w : b[(k) / 3 * 2 + (k) % 3].y)
#define KS(T, k) MMAW(a[2 * (T) + ((k) & 1)], T, k, BK0(k), BK1(k));
#define JOIN(g) { chk = or3(chk, b[2 * (g)].w, b[2 * (g) + 1].w); b[2 * (g)].w = b[2 * (g) + 1].z | chk; }
        uint32_t chk = 0;
#pragma unroll
        for (int k = 0; k < LW; k++) { if (k % 3 == 2) JOIN(k / 3) KS(0, k) KS(1, k) }
#pragma unroll
        for (int i = 4; i < 12; i++) b[i] = ldm128(ma + R_MEM + (i >> 1) * 2048 + (i & 1) * 512);
        const uint32_t dmem = tab1(lp + fresh(wg * 512 + (s & 1) * 128) + R_T4 + 256);
#pragma unroll
        for (int k = LW; k < 18; k++) { if (k % 3 == 2) JOIN(k / 3) KS(0, k) KS(1, k) }
        float r[4];
        {
            const float s0 = aq ? QS : 1.f;
#pragma unroll
            for (int j = 0; j < 4; j++) r[j] = a[3][j] + a[2][j];
            stsm4(dmem, pack2(fmaf(a[1][0], s0, a[0][0] * s0), fmaf(a[1][1], s0, a[0][1] * s0)), pack2(fmaf(a[1][2], s0, a[0][2] * s0), fmaf(a[1][3], s0, a[0][3] * s0)),
                  pack2(r[0], r[1]), pack2(r[2], r[3]));
            const uint32_t bad = __any_sync(0xffffffffu, chk);
            asm volatile("{.reg .pred p; setp.eq.u32 p, %0, 0; @p bar.arrive %1, 384;}" :: "r"(bad | wg), "n"((int)NB_K) : "memory");
            asm volatile("{.reg .pred p; setp.eq.u32 p, %0, 0; @p bar.sync %1, 384;}" :: "r"(bad | (wg ^ 1)), "n"((int)NB_K) : "memory");
            if (__builtin_expect(bad, 0)) goto repair;
        }
#undef JOIN
#undef KS
#undef BK0
#undef BK1
        if (wg == 0) { EV(1); continue; }
        if (!both) {
            const uint2 o = tab2(lp + R_PV);
            const uint4 tv = lds128(lp + R_PV + 512);
            const uint32_t lo = pack2(r[0] + bflo(o.x), r[1] + bfhi(o.x)), hi = pack2(r[2] + bflo(o.y), r[3] + bfhi(o.y));
            const uint32_t v0 = tv.x + (s & 1) * PAR, v1 = tv.z + (s & 1) * PAR, v2 = v0 - tv.y + bar + BSC;
            sta32(v0, lo, tv.y); sta32(v0 + 128, hi, tv.y);
            sta32(v1, lo, tv.w); sta32(v1 + 128, hi, tv.w);
            sts32(v2, lo); sts32(v2 + 128, hi);
            EV(2);
        }
        {
            if (q != 3) bar_arrive(NB_W1, 256);
            if (q == 3) {
                bar_sync(NB_W1, 256);
                unsigned char* const dst = g_qkv + (size_t)((__shfl_sync(0xffffffffu, lds32(sb + R_MISC + M_RING + (s & 1) * 4), 0) & 63) * 32 + blockIdx.x / 3) * 30720;
                const uint32_t so = sb + (s & 1) * PAR;
                fence_smem_async();
                asm volatile("{.reg .pred p; elect.sync _|p, 0xffffffff;\n"
                             "@p cp.async.bulk.global.shared::cta.bulk_group [%0], [%1], %2;\n"
                             "@p cp.async.bulk.global.shared::cta.bulk_group [%3], [%4], %5;\n"
                             "@p cp.async.bulk.global.shared::cta.bulk_group [%6], [%7], %8;\n"
                             "@p cp.async.bulk.commit_group;}"
                             :: "l"(dst + c * 7680), "r"(so + R_K - (c2 ? 2048 : 3072)), "r"(c2 ? 5120 : 7680),
                                "l"(dst + 20480 + c * 2048), "r"(so + R_V + c * 2048), "r"(c2 ? 4096 : 2048),
                                "l"(dst + 28672 + c * 512), "r"(so + R_VM + c * 512), "r"(c2 ? 1024 : 512) : "memory");
            } else if (q == 2) {
                const uint4 tz = lds128(lp + R_T0 + 1536);
                uint32_t z;
                asm volatile("atom.relaxed.gpu.global.exch.b32 %0, [%1], %2;" : "=r"(z) : "l"(mkptr(tz.x + acc_slot(s + 2), tz.y)), "r"(tz.w) : "memory");
                const uint32_t epoch = lds32(sb + R_MISC + M_EPOCH), done = ldg_rlx(&g_oflag[max(s + 1 - QR, 0)][blockIdx.x / 3][0]);
                sts32(sb + R_MISC + M_RING + 4 - (s & 1) * 4, epoch * 64 + ((s + 1) & (done == epoch ? QR - 1 : 63)));
                sts32(sb + R_MISC + M_SINK, z);
            }
        }
        continue;
      repair:
        {
            if (++pass > (1 << 20)) TRAP(1000);
#pragma unroll 1
            for (int i = 0; i < 2; i++) {
                const uint2 tb = tab2(ma + fresh(i * 512) + R_T1 + 256 + ((s - 1) & 3) * 2048);
                const uint32_t md = ma + (ma & 256) + R_MEM + i * 2048;
                const char* const ga = mkptr(tb.x, tb.y);
                cp16(md, ga); cp16(md + 256, ga + 1024); cp16(md + 4096, ga + 2048); cp16(md + 4352, ga + 3072);
                cp16(md + 8192, ga + 2560); cp16(md + 8448, ga + 3584);
            }
            asm volatile("cp.async.wait_all;" ::: "memory");
            __syncwarp();
            const uint32_t la = tab1(lp + fresh(wg * 512) + R_T4 + 128);
            LOAD_TRANSIENT(la)
            goto redo;
        }
    }
    if (wg == 1 && q == 3) PUBLISH(NSEG - 1)
#undef PUBLISH
}

DEVI void attn_loop(const uint32_t (&wo)[3][8][4], const CUtensorMap* xmap, const CUtensorMap* amap, unsigned char* smem, const uint32_t sb, const uint32_t c, const int q,
                    const uint32_t lane0, const uint32_t side, const uint32_t jw) {
    const uint32_t bar = sb + R_BAR;
    const bool c2 = c == 2;
    const uint32_t l16 = pin(sb + lane0 * 16);
    {
        const uint32_t lane = lane0, n = blockIdx.x, gl = (uint32_t)(uint64_t)(void*)g_acc, gh = (uint32_t)((uint64_t)(void*)g_acc >> 32);
        const uint32_t p0 = mapa(sb, c2 ? 0 : c + 1), p1 = mapa(sb, c == 0 ? 2 : c - 1), so = R_SC + lane * 4;
        if (q < 3) sts128(l16 + R_T0 + q * 512, p0 + so + (q == 2 ? 1536 : 512 + q * 256), p0 + R_BAR + BSC, p1 + so + (q == 2 ? 1664 : 1024 + q * 256), p1 + R_BAR + BSC);
        else {
            sts128(l16 + R_T0 + q * 512, gl + acc_line(n >> 4, (n >> 2) & 3, n & 3) + lane * 4, gh, gl + acc_stamp(lane & 1, n), (lane & 3) == 3 ? EMPTY : 0);
            stsm2(l16 + R_T2, gl + acc_stamp(side, (lane < 24 ? lane : 0) * 4), gh);
        }
        for (int i = 0; i < 4; i++)
            stsm4(l16 + R_T1 + i * 2048 + q * 512, gl + acc_slot(i) + acc_line(2 * jw, q, (lane >> 4) * 2 + ((lane >> 1) & 1)) + ((lane & 1) * 4 + ((lane >> 2) & 3)) * 16, gh,
                   gl + acc_slot(i) + acc_line(0, q, lane >> 3) + (lane & 7) * 16, gh);
        __syncwarp();
    }
    const uint32_t ls = pin(sb + (lane0 & 3) * 32);
#define UA(x) (l16 + fresh(x))
#pragma unroll 1
    for (int s = 0; s < NSEG - 1; s++) {
        const uint32_t par = (s & 1) * PAR;
        bar_sync(NB_TOK, 384);
#define SCORES()                                                                                                   \
    float x[2][3][4];                                                                                              \
    _Pragma("unroll") for (int t = 0; t < 3; t++) {                                                                \
        _Pragma("unroll") for (int j = 0; j < 4; j++) x[0][t][j] = x[1][t][j] = 0.f;                               \
        mma16(x[0][t], qf[t][0], qf[t][1], qf[t][2], qf[t][3], kf[t][0], kf[t][1]);                                \
        mma16(x[1][t], qf[t][0], qf[t][1], qf[t][2], qf[t][3], kf[t][2], kf[t][3]);                                \
    }                                                                                                              \
    bar_arrive(NB_G1 + (__float_as_uint(x[0][G1T][0]) & (l16 >> 31)), 256);                                         \
    const uint4 ta = lds128(UA(q * 512) + R_T0);                                                                            \
    float y[4];                                                                                                    \
    _Pragma("unroll") for (int j = 0; j < 4; j++)                                                                  \
        y[j] = ((x[j >> 1][0][j & 1] + x[j >> 1][0][2 + (j & 1)]) + (x[j >> 1][1][j & 1] + x[j >> 1][1][2 + (j & 1)])) + (x[j >> 1][2][j & 1] + x[j >> 1][2][2 + (j & 1)]);
        if (q < 2) {
            uint32_t qf[3][4], kf[3][4];
#pragma unroll
            for (int t = 0; t < 3; t++) ldsm4t(kf[t], UA(q * 512 + par) + R_K + t * 1536);
            bar_sync(NB_K, 384);
#pragma unroll
            for (int t = 0; t < 3; t++) ldsm4t(qf[t], l16 + R_QM + t * 512);
            SCORES()
            const uint32_t u0 = pack2(y[0], y[1]), u1 = pack2(y[2], y[3]);
            sta32(ta.x, u0, ta.y); sta32(ta.z, u0, ta.w);
            sta32(ta.x + 128, u1, ta.y); sta32(ta.z + 128, u1, ta.w);
            stsm2(UA(q * 256) + R_SC, u0, u1);
        } else if (q == 2) {
            if (s > 0 && s + 2 < NSEG) {
                const int xi = s - 1 - 3 * (((s - 1) * 43) >> 7);
                mbar_wait(bar + BME, s & 1);
                spin_until(clk() + XD);
                asm volatile("{.reg .pred p; elect.sync _|p, 0xffffffff;\n"
                             "@p mbarrier.arrive.expect_tx.shared::cta.b64 _, [%2], 36864;\n"
                             "@p cp.async.bulk.tensor.3d.shared::cluster.global.mbarrier::complete_tx::bytes.multicast::cluster [%0], [%1, {%3, %4, %5}], [%2], %6;}"
                             :: "r"(sb + xi * 36864 + c * 12288), "l"(xmap), "r"(bar + BX0 + xi * 8), "r"(0), "r"((s + 2) * 32), "r"(c * 3), "h"((uint16_t)7) : "memory");
            }
            uint32_t qf[3][4], kf[3][4];
            bar_sync(NB_K, 384);
#pragma unroll
            for (int t = 0; t < 3; t++) { ldsm4t(qf[t], l16 + R_QM + t * 512); ldsm4t(kf[t], UA(q * 512 + par) + R_K + t * 1536); }
            SCORES()
            const uint32_t u0 = pack2(y[0] + y[2], y[1] + y[3]);
            sta32(ta.x, u0, ta.y);
            sta32(ta.z, u0, ta.w);
            EV(4);
            stsm2(l16 + R_SC + 1792, u0, u0);
        } else {
            const uint4 ta = lds128(UA(q * 512) + R_T0);
            {
                const uint32_t vt = R_V + par + c * 2048, p0 = mapa(sb, c2 ? 0 : c + 1), p1 = mapa(sb, c == 0 ? 2 : c - 1);
                fence_smem_async();
                bulk_s2c_warp(p0 + vt, sb + vt, c2 ? 4096 : 2048, p0 + R_BAR + BVX + (s & 1) * 8);
                bulk_s2c_warp(p1 + vt, sb + vt, c2 ? 4096 : 2048, p1 + R_BAR + BVX + (s & 1) * 8);
            }
            {
                const int s3 = ((s + 1) * 43) >> 7;
                mbar_wait(bar + BX0 + (s + 1 - 3 * s3) * 8, s3 & 1);
                bar_arrive(NB_G1, 256);
            }
            sts32(sb + R_MISC + M_REF + 4, clock_offset());
            bar_sync(NB_K, 384);
            const uint32_t off = lds32(sb + R_MISC + M_REF + 4);
            const uint32_t t = off == 0x9e3779b9u ? 0u : clk();
            sts64(sb + R_MISC + M_REF, t, t + off);
            stg_rlx((uint32_t*)mkptr(ta.z + acc_slot(s), ta.y), ((t + off) & 0x3fffffu) | ((s + 1) << 22));
            mbar_wait(bar + BVX + (s & 1) * 8, (s >> 1) & 1);
        }
#undef SCORES
        bar_sync(NB_W1, 256);
        uint32_t vf[4][4];
        const uint32_t vo = par + q * 2048;
        float o0[4], o1[4], sum;
        uint2 tb;
        {
            uint32_t aw[5], bw[5], cw[5];
            ldsm4(aw, l16 + R_SC); aw[4] = tab1(l16 + R_SC + 1792);
            sts32(sb + R_MISC + M_SINK, aw[0] | aw[4]);
            mbar_wait(bar + BSC, s & 1);
            ldsm4(bw, l16 + R_SC + 512); ldsm4(cw, l16 + R_SC + 1024);
            { const uint2 t = tab2(l16 + R_SC + 1536); bw[4] = t.x; cw[4] = t.y; }
            EV(5);
            float x[10];
#pragma unroll
            for (int i = 0; i < 5; i++) { x[2 * i] = (bflo(aw[i]) + bflo(bw[i])) + bflo(cw[i]); x[2 * i + 1] = (bfhi(aw[i]) + bfhi(bw[i])) + bfhi(cw[i]); }
            float mx = fmaxf(fmaxf(fmaxf(fmaxf(x[0], x[1]), fmaxf(x[2], x[3])), fmaxf(fmaxf(x[4], x[5]), fmaxf(x[6], x[7]))), fmaxf(x[8], x[9]));
            const float m1 = __shfl_xor_sync(0xffffffffu, mx, 1), m2 = __shfl_xor_sync(0xffffffffu, mx, 2), m3 = __shfl_xor_sync(0xffffffffu, mx, 3);
            uint32_t vm[4];
            const uint32_t lv = l16 | (__float_as_uint(mx) & (l16 >> 31));
            ldsm4(vf[0], lv + fresh(vo) + R_V); ldsm4(vf[2], lv + fresh(vo) + R_V + 1024);
            ldsm4(vf[3], lv + fresh(vo) + R_V + 1536); ldsm4(vm, lv + fresh(q * 512 + par) + R_VM);
            tb = tab2(lv + fresh(q * 512 + (s & 3) * 2048) + R_T1);
            bar_arrive(NB_E0, 256);
            ldsm4(vf[1], lv + fresh(vo) + R_V + 512);
            mx = fmaxf(fmaxf(mx, m1), fmaxf(m2, m3));
            uint32_t pb[5];
            sum = 0.f;
#pragma unroll
            for (int i = 0; i < 5; i++) {
                const float e0 = ex2(x[2 * i] - mx), e1 = ex2(x[2 * i + 1] - mx);
                pb[i] = pack2(e0, e1);
                sum += e0 + e1;
            }
#pragma unroll
            for (int j = 0; j < 4; j++) o0[j] = o1[j] = 0.f;
            mma16(o0, vf[0][0], vf[0][1], vf[0][2], vf[0][3], pb[0], pb[1]);
            mma16(o1, vf[2][0], vf[2][1], vf[2][2], vf[2][3], pb[0], pb[1]);
            mma16(o0, vf[1][0], vf[1][1], vf[1][2], vf[1][3], pb[2], pb[3]);
            mma16(o1, vf[3][0], vf[3][1], vf[3][2], vf[3][3], pb[2], pb[3]);
            mma8(o0, vm[0], vm[1], pb[4]);
            mma8(o1, vm[2], vm[3], pb[4]);
        }
        asm volatile("stmatrix.sync.aligned.m8n8.x1.shared.b16 [%0], {%1};" :: "r"(l16 + R_Z), "r"(__float_as_uint(sum)) : "memory");
        const float4 s0 = lds128f(ls + R_Z), s1 = lds128f(ls + R_Z + 16);
        stsm4(UA(q * 512) + R_O8, pack2(o0[0], o0[1]), pack2(o0[2], o0[3]), pack2(o1[0], o1[1]), pack2(o1[2], o1[3]));
        EV(6);
        bar_sync(NB_W2, 128);
        uint32_t of[4][4];
#pragma unroll
        for (int i = 0; i < 4; i++) ldsm4t(of[i], l16 + R_O8 + i * 512);
        const float f0 = rcp_fast((s0.x + s0.y) + (s0.z + s0.w)), f1 = rcp_fast((s1.x + s1.y) + (s1.z + s1.w));
        float acc[3][2][4];
        uint32_t tie;
#pragma unroll
        for (int m = 0; m < 3; m++)
#pragma unroll
            for (int j = 0; j < 4; j++) acc[m][0][j] = acc[m][1][j] = 0.f;
#pragma unroll
        for (int i = 0; i < 4; i++)
#pragma unroll
            for (int m = 0; m < 3; m++)
#pragma unroll
                for (int e = 0; e < 2; e++) {
                    const int p = i ? 1 + (i + m + 2) % 3 : 0, kk = 2 * p + e;
                    if (i == 3 && m == 0 && e == 0)
                        tie = or3(or3(__float_as_uint(acc[0][0][0]), __float_as_uint(acc[0][1][0]), __float_as_uint(acc[1][0][0])),
                                  or3(__float_as_uint(acc[1][1][0]), __float_as_uint(acc[2][0][0]), __float_as_uint(acc[2][1][0])), __float_as_uint(f0) | __float_as_uint(f1));
                    mma16(acc[m][e], wo[m][kk][0], wo[m][kk][1], wo[m][kk][2], wo[m][kk][3], of[p][e * 2], of[p][e * 2 + 1]);
                }
        char* const gw = mkptr(tb.x, tb.y);
        bar_arrive(NB_GO + (tie & (l16 >> 31)), 384);
        const uint32_t one = lds32(sb + R_MISC + M_ONE);
        uint32_t wa[3], wb[3];
#pragma unroll
        for (int m = 0; m < 3; m++) {
            wa[m] = pack2(fmaf(acc[m][1][0], f0, acc[m][0][0] * f0), fmaf(acc[m][1][2], f0, acc[m][0][2] * f0));
            wb[m] = pack2(fmaf(acc[m][1][1], f1, acc[m][0][1] * f1), fmaf(acc[m][1][3], f1, acc[m][0][3] * f1));
        }
        red_b8(gw, wa[0], wa[1], wa[2], one); red_b8(gw + 1024, wb[0], wb[1], wb[2], one);
        const uint32_t t0 = clk();
        if (EVX(0)) EVV(7, t0);
        if (q < 2) {
            uint2 tg = lds64(sb + R_MISC + M_TGT);
            for (int n = 0; tg.y != s + 1; tg = lds64(sb + R_MISC + M_TGT)) if (++n > (1 << 26)) TRAP(1003);
            fine_until(t0 + max((int)(tg.x - t0), DMIN) - (q != side ? FE : 0) + (c ? DL : 0));
            asm volatile("{.reg .pred p; elect.sync _|p, 0xffffffff;\n"
                         "@p cp.async.bulk.tensor.5d.shared::cluster.global.mbarrier::complete_tx::bytes.multicast::cluster [%0], [%1, {%3, %4, %4, %4, %5}], [%2], %6;}"
                         :: "r"(sb + R_MEM + c * 4096 + q * 2048), "l"(amap + q), "r"(bar + (DL && c ? BML : BME)), "r"((s & 1) * 64), "r"(0), "r"((s & 2) * 64 + (c ? 6 + 2 * c : 0)), "h"((uint16_t)7) : "memory");
            EV(8);
        } else if (q == 2) {
            if (l16 == sb) {
                mbar_expect(bar + BME, DL ? 4096 : 12288);
                if (DL) mbar_expect(bar + BML, 8192);
                mbar_expect(bar + BSC, (c2 ? 1024 : 1536) + (s < NSEG - 2 ? 1280 : 0));
                mbar_expect(bar + BVX + 8 - (s & 1) * 8, c2 ? 4096 : 6144);
            }
        }
        EV(10);
    }
    bar_sync(NB_TOK, 384);
    bar_arrive(NB_K, 384);
    bar_arrive(NB_W1, 256);
    mbar_wait(bar + BSC, 1);
}

struct Maps { CUtensorMap x, acc[2]; };

__global__ void __launch_bounds__(384, 1)
rk_kernel(const __grid_constant__ Maps maps, const __nv_bfloat16* __restrict__ xraw, const __nv_bfloat16* __restrict__ mem0, const __nv_bfloat16* __restrict__ Wq,
          const __nv_bfloat16* __restrict__ Wk, const __nv_bfloat16* __restrict__ Wv, const __nv_bfloat16* __restrict__ Wo) {
    extern __shared__ __align__(1024) unsigned char smem[];
    const uint32_t sb = smem_u32(smem);
    const int tid = threadIdx.x;
    const int warp = __shfl_sync(0xffffffffu, tid >> 5, 0), q = warp & 3;
    const int h = blockIdx.x / 3;
    const uint32_t c = blockIdx.x - 3 * h;
    const uint32_t bar = sb + R_BAR;
    asm volatile("griddepcontrol.launch_dependents;");
    GT(0, 0);

    if (warp < 8) {
        asm volatile("setmaxnreg.inc.sync.aligned.u32 %0;" :: "n"(RP));
        const int wg = warp >> 2;
        const uint32_t lane = pin(tid & 31);
        uint32_t w[2][18][4];
        const uint32_t st = sb + R_STAGE + wg * 8192;
        const uint32_t la = st + (((lane >> 4) << 3) + (lane & 7)) * 128 + (((2 * q + ((lane >> 3) & 1)) ^ (lane & 7)) << 4);
        {
            const int t = tid & 127;
            const int r0 = t >> 3, ch = t & 7, p = (ch >> 1) ^ (2 * wg);
            const __nv_bfloat16* ta = c == 2 ? (p < 2 ? Wq : Wk) + 96 + (p & 1) * 16 : (p == 2 ? Wk : Wq) + c * 48 + min(p, 2) * 16;
            const __nv_bfloat16* tb = c == 2 ? Wv + 64 + p * 16 : (p >= 2 ? Wv + c * 32 + (p - 2) * 16 : Wk + c * 48 + p * 16);
            const size_t so = (size_t)(wg * 288 + r0) * HD + h * 128 + (ch & 1) * 8;
            const __nv_bfloat16* sp0 = ta + so;
            const __nv_bfloat16* sp1 = tb + so;
            const uint32_t dp = st + r0 * 128 + ((ch ^ (r0 & 7)) << 4);
#define ISSUE(KC, SLOT)                                                                                         \
    cp16(dp + (SLOT) * 16384, sp0 + (size_t)((KC) * 32) * HD); cp16(dp + (SLOT) * 16384 + 2048, sp0 + (size_t)((KC) * 32 + 16) * HD);               \
    cp16(dp + (SLOT) * 16384 + 4096, sp1 + (size_t)((KC) * 32) * HD); cp16(dp + (SLOT) * 16384 + 6144, sp1 + (size_t)((KC) * 32 + 16) * HD);        \
    cp_commit();
#pragma unroll
            for (int kc = 1; kc < 8; kc++) { ISSUE(kc, kc - 1) }
            ISSUE(0, 7)
            cluster_arrive_rlx(); cluster_wait();
#define LOADCHUNK(KC, SLOT, NWAIT)                                                   \
    cp_wait<NWAIT>(); bar_sync(NB_L0 + wg, 128);                                      \
    _Pragma("unroll") for (int i = 0; i < 4; i++) ldsm4t(w[i >> 1][(KC) * 2 + (i & 1)], la + (SLOT) * 16384 + i * 2048);
            LOADCHUNK(1, 0, 7)
            bar_sync(NB_L0 + wg, 128);
            ISSUE(8, 0)
            LOADCHUNK(2, 1, 7) LOADCHUNK(3, 2, 6) LOADCHUNK(4, 3, 5) LOADCHUNK(5, 4, 4) LOADCHUNK(6, 5, 3) LOADCHUNK(7, 6, 2) LOADCHUNK(0, 7, 1) LOADCHUNK(8, 0, 0)
#undef LOADCHUNK
#undef ISSUE
            fence_smem_async();
        }
        bar_sync(0, 384);
        cluster_arrive_rlx(); cluster_wait();

        GT(0, 1);
        if (c == 2) sts128(sb + (q == 3 ? R_QM + 1024 : R_K + 3072 + q * 512 + wg * PAR) + lane * 16, 0, 0, 0, 0);
        proj_loop(w, smem, sb, c, wg, q, lane);
    } else {
        asm volatile("setmaxnreg.dec.sync.aligned.u32 %0;" :: "n"(504 - 2 * RP));
        const uint32_t lane0 = pin(tid & 31);
        const uint32_t lane = lane0, n = blockIdx.x;
        volatile uint32_t* const misc = (volatile uint32_t*)(smem + R_MISC);
        const unsigned epoch = g_epoch[36 + n] + 1;
        uint32_t* const pa = (uint32_t*)((char*)g_acc + acc_blk(q & 1, n & 3) + 1536 + ((n >> 2) & 3) * 128 + ((n >> 4) & 1) * 32768 + (n >> 5) * 32);
        {
            const int t = tid - 256;
            if (t == 0) {
                mbar_init(bar + BX0, 1); mbar_init(bar + BX0 + 8, 1); mbar_init(bar + BX0 + 16, 1);
                mbar_init(bar + BSC, 1); mbar_init(bar + BME, 1); mbar_init(bar + BML, 1); mbar_arrive(bar + BME); mbar_arrive(bar + BML);
                mbar_init(bar + BVX, 1); mbar_init(bar + BVX + 8, 1);
                mbar_expect(bar + BSC, c == 2 ? 2304 : 2816); mbar_expect(bar + BVX, c == 2 ? 4096 : 6144);
                misc[M_TGT / 4 + 1] = 0; misc[M_ONE / 4] = 0x3f80u;
                misc[M_EPOCH / 4] = epoch; misc[M_RING / 4] = epoch * 64; g_epoch[36 + n] = epoch;
                asm volatile("fence.mbarrier_init.release.cluster;" ::: "memory");
            }
            __syncwarp();
            cluster_arrive_rlx();
            uint32_t z;
            asm volatile("atom.relaxed.gpu.global.exch.b32 %0, [%1], %2;" : "=r"(z) : "l"((char*)g_acc + acc_slot(q) + acc_line(n >> 4, (n >> 2) & 3, n & 3) + lane * 4), "r"((lane & 3) == 3 ? EMPTY : 0) : "memory");
            if (lane < 2) stg_rlx((uint32_t*)((char*)g_acc + acc_slot(q) + acc_stamp(lane, n)), 0u);
            if (q < 2 && lane < 8) stg_rlx(pa + lane, 0u);
            uint32_t m0[3][6];
#pragma unroll
            for (int i = 0; i < 18; i++) m0[i / 6][i % 6] = __ldg((const uint32_t*)mem0 + (lane >> 2) * 288 + (q * 18 + i) * 4 + (lane & 3));
            const __nv_bfloat16* src = Wo + (size_t)h * 128 * DM;
#pragma unroll 4
            for (int i = 0; i < 24; i++) {
                const int idx = i * 128 + t, r = idx / 24, ch = idx - r * 24, qq = ch / 6, jq = (c + 3 - qq % 3) % 3;
                cp16(sb + R_WO + r * 384 + ((ch ^ ((r >> 1) & 3) * 2) << 4), src + r * DM + ((qq >> 1) * 36 + jq * 12 + (qq & 1) * 6 + ch - qq * 6) * 8);
            }
            cp_commit();
            cluster_wait();
            if (t == 0) {
                mbar_expect(bar + BX0, 36864);
                x_tma(sb + R_X0 + c * 12288, &maps.x, bar + BX0, 0, c * 3);
            }
            __syncwarp();
            {
                const uint32_t a = sb + R_MEM + (q & 1) * 6144 + (q >> 1) * 1024 + lane * 16;
#pragma unroll
                for (int i = 0; i < 6; i++) sts128(a + (i >> 1) * 2048 + (i & 1) * 512, m0[i >> 1][(i & 1) * 2], m0[i >> 1][(i & 1) * 2 + 1], m0[i >> 1][4 + (i & 1)], z & (lane >> 5));
            }
            asm volatile("fence.acq_rel.gpu;" ::: "memory");
            cp_wait<0>();
            bar_sync(NB_W2, 128);
            if (t == 0) stg_rlx(&g_pub[n], epoch);
            if (t == 32) asm volatile("cp.async.bulk.prefetch.L2.global [%0], 24576;" :: "l"((const char*)xraw + n * 24576) : "memory");
        }
        uint32_t wo[3][8][4];
        {
            const uint32_t g = lane >> 2, tq = lane & 3;
#pragma unroll
            for (int m = 0; m < 3; m++) {
                const uint32_t ch = 6 * q + (m < 2 ? (g >> 2) * 2 + m : 4 + (g >> 2));
                const uint32_t a = sb + R_WO + tq * 768 + ((ch ^ tq * 2) << 4) + (g & 3) * 4;
#pragma unroll
                for (int kk = 0; kk < 16; kk++) {
                    const uint32_t x = lds32(a + kk * 3072), y = lds32(a + kk * 3072 + 384);
                    wo[m][kk >> 1][(kk & 1) * 2] = __byte_perm(x, y, 0x5410);
                    wo[m][kk >> 1][(kk & 1) * 2 + 1] = __byte_perm(x, y, 0x7632);
                }
            }
        }
        bar_sync(0, 384);
        cluster_arrive_rlx(); cluster_wait();
        bar_arrive(NB_G1, 256);
        bar_arrive(NB_E0, 256);
        bar_arrive(NB_GO, 384);
        if (q >= 2 && lane == 0) {
            mbar_expect(bar + BX0 + (q - 1) * 8, 36864);
            x_tma(sb + (q - 1) * 36864 + c * 12288, &maps.x, bar + BX0 + (q - 1) * 8, (q - 1) * 32, c * 3);
        }
        __syncwarp();
        if (q < 2) { const uint32_t r = probe_rtt(pa); if (lane == 0) misc[M_PROBE / 4 + q] = r; }
        if (q == 3) {
            int it = 0;
            while (!__all_sync(0xffffffffu, ldg_rlx(&g_pub[lane]) == epoch && ldg_rlx(&g_pub[32 + lane]) == epoch && ldg_rlx(&g_pub[64 + lane]) == epoch))
                if (++it > (1 << 22)) TRAP(2000 + __LINE__);
        }
        bar_sync(NB_W2, 128);
        const uint32_t side = __shfl_sync(0xffffffffu, misc[M_PROBE / 4 + 1] < misc[M_PROBE / 4], 0);
        attn_loop(wo, &maps.x, maps.acc, smem, sb, c, q, lane0, side, (c + 3 - q % 3) % 3);
    }
    cluster_arrive_rlx(); cluster_wait();
    GT(0, 2);
}

constexpr int H_USTR = 32 * 144 + 16;
constexpr int H_U = 0;
constexpr int H_Z = H_U + 16 * H_USTR;
constexpr int H_W = 74752;
constexpr int H_WSTR = (2048 + 64) * 4;
constexpr int H_PAR = H_W + 8 * H_WSTR;
constexpr int H_KD = H_PAR + 4 * 2048;
constexpr int H_S4END = H_KD + 4 * 648 * 4;
constexpr int NST = 6;
constexpr int H_RING = H_W;
constexpr int H_QKV = H_RING + NST * 16384;
constexpr int H_AO = H_QKV + 30720;
constexpr int H_BAR = H_AO + 8192;
constexpr int H_SMEM = H_BAR + 512;
static_assert(H_Z + 256 <= H_W && H_S4END <= H_QKV && H_SMEM <= 232448 && H_RING % 1024 == 0, "smem");
enum { HB_FULL = 0  , HB_EMPTY = 64  , HB_WF = 128  , HB_WE = 192  , HB_QF = 256, HB_VF = 264, HB_QE = 272, HB_VE = 280, HB_OF = 288, HB_OE = 296 };
enum { HN_U = 1, HN_Y = 2, HN_P = 3   };

DEVI int slot_channel(int i) { return ((i >> 1) & 3) * 4 + (i >> 3) * 2 + (i & 1); }
#define LOAD_U(W)                                                                                                                      \
    _Pragma("unroll 1") for (int i0 = 0; i0 < 16; i0 += 4) {                                                                            \
        uint2 v[4][2];                                                                                                                  \
        _Pragma("unroll") for (int i = 0; i < 8; i++)                                                                                   \
            v[i >> 1][i & 1] = __ldg((const uint2*)(u + (size_t)(((W) * 16 + i0) * 16 + i * 8 + g) * DM + d0 + tq * 4));                \
        _Pragma("unroll") for (int i = 0; i < 4; i++) {                                                                                 \
            const int t0 = ((W) * 16 + i0 + i) * 16;                                                                                    \
            asm volatile("stmatrix.sync.aligned.m8n8.x4.trans.shared.b16 [%0], {%1,%2,%3,%4};"                                          \
                         :: "r"(sb + H_U + (lane & 15) * H_USTR + (t0 >> 6) * 144 + (t0 & 63) * 2 + (lane >> 4) * 16),                  \
                            "r"(v[i][0].x), "r"(v[i][0].y), "r"(v[i][1].x), "r"(v[i][1].y) : "memory");                                 \
        }                                                                                                                               \
    }
DEVI uint64_t desc_plain(uint32_t saddr, uint32_t lbo, uint32_t sbo) { return ((uint64_t)(sbo >> 4) << 32) | ((uint64_t)(lbo >> 4) << 16) | (uint64_t)((saddr & 0x3FFFF) >> 4); }
template <int ACC> DEVI void wgmma48_tt(float* d, uint64_t adesc, uint64_t bdesc) {
    asm volatile("wgmma.mma_async.sync.aligned.m64n48k16.f32.bf16.bf16 "
                 "{%0,%1,%2,%3,%4,%5,%6,%7,%8,%9,%10,%11,%12,%13,%14,%15,%16,%17,%18,%19,%20,%21,%22,%23}, %24, %25, %26, 1, 1, 1, 1;"
                 : "+f"(d[0]), "+f"(d[1]), "+f"(d[2]), "+f"(d[3]), "+f"(d[4]), "+f"(d[5]), "+f"(d[6]), "+f"(d[7]),
                   "+f"(d[8]), "+f"(d[9]), "+f"(d[10]), "+f"(d[11]), "+f"(d[12]), "+f"(d[13]), "+f"(d[14]), "+f"(d[15]),
                   "+f"(d[16]), "+f"(d[17]), "+f"(d[18]), "+f"(d[19]), "+f"(d[20]), "+f"(d[21]), "+f"(d[22]), "+f"(d[23])
                 : "l"(adesc), "l"(bdesc), "n"(ACC));
}
template <int ACC> DEVI void wgmma64(float* d, const uint32_t* a, uint64_t desc) {
    asm volatile("wgmma.mma_async.sync.aligned.m64n64k16.f32.bf16.bf16 "
                 "{%0,%1,%2,%3,%4,%5,%6,%7,%8,%9,%10,%11,%12,%13,%14,%15,%16,%17,%18,%19,%20,%21,%22,%23,%24,%25,%26,%27,%28,%29,%30,%31}, {%32,%33,%34,%35}, %36, %37, 1, 1, 0;"
                 : "+f"(d[0]), "+f"(d[1]), "+f"(d[2]), "+f"(d[3]), "+f"(d[4]), "+f"(d[5]), "+f"(d[6]), "+f"(d[7]),
                   "+f"(d[8]), "+f"(d[9]), "+f"(d[10]), "+f"(d[11]), "+f"(d[12]), "+f"(d[13]), "+f"(d[14]), "+f"(d[15]),
                   "+f"(d[16]), "+f"(d[17]), "+f"(d[18]), "+f"(d[19]), "+f"(d[20]), "+f"(d[21]), "+f"(d[22]), "+f"(d[23]),
                   "+f"(d[24]), "+f"(d[25]), "+f"(d[26]), "+f"(d[27]), "+f"(d[28]), "+f"(d[29]), "+f"(d[30]), "+f"(d[31])
                 : "r"(a[0]), "r"(a[1]), "r"(a[2]), "r"(a[3]), "l"(desc), "n"(ACC));
}
DEVI uint2 ldg_rlx2(const void* p) { uint2 v; asm volatile("ld.relaxed.gpu.global.v2.u32 {%0,%1}, [%2];" : "=r"(v.x), "=r"(v.y) : "l"(p) : "memory"); return v; }
DEVI unsigned ldg_acq(const unsigned* p) { unsigned v; asm volatile("ld.acquire.gpu.global.u32 %0, [%1];" : "=r"(v) : "l"(p) : "memory"); return v; }
DEVI void csq(float& x, float& y) { const float a = fmaf(x, x, -y * y), b = 2.f * x * y; x = a; y = b; }
DEVI uint32_t tf(float x) { return __float_as_uint(x) + 0x1000u; }
DEVI void cexp_turns(float l2mag, float turns, float& x, float& y) {
    const float m = ex2(l2mag), a = (turns - rintf(turns)) * 6.283185307179586f;
    x = m * __cosf(a); y = m * __sinf(a);
}

__global__ void __launch_bounds__(512, 1)
hk_kernel(const __nv_bfloat16* __restrict__ Wo, const __nv_bfloat16* __restrict__ u,
          const __nv_bfloat16* __restrict__ logA, const __nv_bfloat16* __restrict__ Aim, const __nv_bfloat16* __restrict__ Cre,
          const __nv_bfloat16* __restrict__ Cim, const __nv_bfloat16* __restrict__ logdt, const __nv_bfloat16* __restrict__ Dsk,
          __nv_bfloat16* __restrict__ out) {
    extern __shared__ __align__(1024) unsigned char smem[];
    const uint32_t sb = smem_u32(smem);
    const int tid = threadIdx.x, lane = tid & 31, warp = __shfl_sync(0xffffffffu, tid >> 5, 0), g = lane >> 2, tq = lane & 3;
    const int cta = blockIdx.x;
    const bool shared = cta < 32;
    const uint32_t bar = sb + H_BAR;
    const int d0 = cta * 16;
    const uint32_t tstart = clk();
    if (tid == 0) {
        for (int i = 0; i < NST; i++) { mbar_init(bar + HB_FULL + i * 8, 1); mbar_init(bar + HB_EMPTY + i * 8, shared ? 8 : 4); }
        for (int i = 0; i < 16; i++) mbar_init(bar + HB_WF + i * 8, 1);
        mbar_init(bar + HB_QF, 1); mbar_init(bar + HB_VF, 1); mbar_init(bar + HB_QE, 4); mbar_init(bar + HB_VE, 4); mbar_init(bar + HB_OF, 4); mbar_init(bar + HB_OE, 1);
        asm volatile("fence.proxy.async.shared::cta;" ::: "memory");
    }
    const unsigned epoch = g_epoch[cta] + 1;
    __syncthreads();
    if (tid == 0) g_epoch[cta] = epoch;
    if (warp < 8) {
        asm volatile("setmaxnreg.inc.sync.aligned.u32 176;");
        HEV(0); GT(96, 0);
        const int pr = warp & 3;
        float4* par = (float4*)(smem + H_PAR + pr * 2048);
        float* kd = (float*)(smem + H_KD + pr * 648 * 4);
        for (int i = lane; i < 64; i += 32) ((uint32_t*)(smem + H_W + (pr * 2 + (warp >> 2)) * H_WSTR))[i] = 0;
        HEV(1);
        if (!(HM & 1)) bar_sync(HN_U, 384);
#pragma unroll 1
        for (int it = 0; it < ((HM & 1) ? (warp < 4 ? 3 : 5) : 0); it++) {
            const int rnd = min(it, 3), ch = rnd * 4 + pr, d = d0 + slot_channel(ch);
            uint32_t* wz = (uint32_t*)(smem + H_W + (pr * 2 + (rnd & 1)) * H_WSTR);
            if (warp >= 4 && it < 4) {
            const float dt = bf2f(__float2bfloat16(expf(bf2f(logdt[d]))));
#pragma unroll
            for (int n = lane; n < 128; n += 32) {
                const float ar = -bf2f(__float2bfloat16(expf(bf2f(logA[d * 128 + n])))) * dt, ai = bf2f(Aim[d * 128 + n]) * dt;
                par[n] = make_float4(ar * 1.4426950408889634f, ai * 0.15915494309189535f, 2.f * bf2f(Cre[d * 128 + n]) * dt, 2.f * bf2f(Cim[d * 128 + n]) * dt);
            }
            __syncwarp();
            float kacc[5][4], klast = 0.f;
#pragma unroll
            for (int i = 0; i < 5; i++) kacc[i][0] = kacc[i][1] = kacc[i][2] = kacc[i][3] = 0.f;
            const float fa = (float)g, fb = (float)(g + 8);
            float4 pn[4];
#pragma unroll
            for (int i = 0; i < 4; i++) pn[i] = par[4 * i + tq];
#pragma unroll 4
            for (int ks = 0; ks < 32; ks++) {
                const float4 p = pn[ks & 3];
                pn[ks & 3] = par[(4 * ks + 16 + tq) & 127];
                float ax, ay, bx, by;
                cexp_turns(p.x * fa, p.y * fa, ax, ay);
                cexp_turns(p.x * fb, p.y * fb, bx, by);
                uint32_t F[4][4];
#pragma unroll
                for (int r = 0; r < 4; r++) {
                    F[r][0] = tf(ax); F[r][1] = tf(bx); F[r][2] = tf(ay); F[r][3] = tf(by);
                    csq(ax, ay); csq(bx, by);
                }
                mma_tf32(kacc[0], F[0][0], F[0][1], F[0][2], F[0][3], tf(fmaf(p.z, ax, -p.w * ay)), tf(-fmaf(p.z, ay, p.w * ax)));
#pragma unroll
                for (int r = 0; r < 4; r++) {
                    mma_tf32(kacc[r + 1], F[r][0], F[r][1], F[r][2], F[r][3], tf(fmaf(p.z, bx, -p.w * by)), tf(-fmaf(p.z, by, p.w * bx)));
                    csq(bx, by);
                }
                klast += fmaf(p.z, bx, -p.w * by);
            }
#pragma unroll
            for (int i = 0; i < 5; i++) {
                kd[i * 128 + 32 * tq + g] = kacc[i][0]; kd[i * 128 + 32 * tq + 16 + g] = kacc[i][1];
                kd[i * 128 + 32 * tq + g + 8] = kacc[i][2]; kd[i * 128 + 32 * tq + 24 + g] = kacc[i][3];
            }
            klast += __shfl_xor_sync(0xffffffffu, klast, 1);
            klast += __shfl_xor_sync(0xffffffffu, klast, 2);
            if (lane == 0) kd[640] = klast;
            __syncwarp();
            if (rnd >= 2) mbar_wait(bar + HB_WE + (pr * 2 + (rnd & 1)) * 8, 0);
#define RIDX(l, r) ((r) * 128 + (((l) + (1 << (r) >> 1) - 1 + (((l) >> (r)) & 1)) >> (r)))
#pragma unroll
            for (int x0 = 0; x0 < 256; x0 += 32) wz[64 + x0 + lane] = pack2(kd[x0 + lane], x0 + lane ? kd[x0 + lane - 1] : 0.f);
#pragma unroll
            for (int r = 1; r < 4; r++) {
                const int l0 = (128 << r) + lane;
                const float* k0 = kd + RIDX(l0, r);
                const float* k1 = kd + RIDX(l0 - 1, r);
#pragma unroll 8
                for (int i = 0; i < (4 << r); i++) wz[64 + l0 + 32 * i] = pack2(k0[i * (32 >> r)], k1[i * (32 >> r)]);
            }
#undef RIDX
            __syncwarp();
            if (lane == 0) wz[64 + 256] = pack2(kd[256], kd[255]);
            __syncwarp();
            if (lane == 0) mbar_arrive(bar + HB_WF + (pr * 2 + (rnd & 1)) * 8);
            if (rnd == 0) bar_sync(HN_U, 384);
            continue;
            }
            if (it == 0) { spin_until(tstart + UDLY); LOAD_U(warp) bar_sync(HN_U, 384); }
            mbar_wait(bar + HB_WF + (pr * 2 + (rnd & 1)) * 8, rnd >> 1);
            if (it == 0) HEV(2);
            float acc[4][4][4];
#pragma unroll
            for (int G = 0; G < 4; G++)
#pragma unroll
                for (int i = 0; i < 4; i++) acc[G][i][0] = acc[G][i][1] = acc[G][i][2] = acc[G][i][3] = 0.f;
            const uint32_t ub = sb + H_U + ch * H_USTR + (lane >> 3) * 16, zb = sb + H_Z + (lane >> 3) * 16;
            const uint32_t* wp = wz + 64 - 56 + g - 2 * tq;
            uint32_t Pn[15];
#pragma unroll
            for (int k = 0; k < 15; k++) Pn[k] = wp[8 * k];
            uint32_t bn[2][4];
            ldsm4(bn[0], ub + (24 + (lane & 7)) * 144); ldsm4(bn[1], ub + (24 + (lane & 7)) * 144 + 64);
#define CONV_RANGE(G0)                                                                                                  \
    _Pragma("unroll 1") for (int s = 8 * (G0); s < 8 * (G0) + 8; s++) {                                                  \
        uint32_t P[15], b[4][2][4];                                                                                      \
        _Pragma("unroll") for (int k = 0; k < 4; k++) { b[3][0][k] = bn[0][k]; b[3][1][k] = bn[1][k]; }                  \
        _Pragma("unroll") for (int G = 2; G >= (G0); G--) {                                                              \
            const int cidx = 8 * G + (lane & 7) - s;                                                                     \
            const uint32_t ba = (G > (G0) || cidx >= 0) ? ub + cidx * 144 : zb;                                          \
            ldsm4(b[G][0], ba); ldsm4(b[G][1], ba + 64);                                                                 \
        }                                                                                                                \
        {                                                                                                                \
            const int cidx = 23 + (lane & 7) - s;                                                                        \
            const uint32_t ba = cidx >= 0 ? ub + cidx * 144 : zb;                                                        \
            ldsm4(bn[0], ba); ldsm4(bn[1], ba + 64);                                                                     \
        }                                                                                                                \
        _Pragma("unroll") for (int k = 0; k < 15; k++) P[k] = Pn[k];                                                     \
        _Pragma("unroll") for (int k = 0; k < 7; k++) Pn[k] = P[k + 8];                                                  \
        _Pragma("unroll") for (int k = 7; k < 15; k++) Pn[k] = wp[64 * min(s + 1, 31) + 8 * k];                          \
        _Pragma("unroll") for (int G = 3; G >= (G0); G--)                                                                \
            _Pragma("unroll") for (int j = 0; j < 4; j++)                                                                \
                _Pragma("unroll") for (int i = 0; i < 4; i++) {                                                          \
                    const int k = 2 * (i - j) + 7;                                                                       \
                    mma16(acc[G][i], P[k], P[k + 1], P[k - 1], P[k], b[G][j >> 1][(j & 1) * 2], b[G][j >> 1][(j & 1) * 2 + 1]); \
                }                                                                                                        \
    }
            CONV_RANGE(0) CONV_RANGE(1) CONV_RANGE(2) CONV_RANGE(3)
#undef CONV_RANGE
            __syncwarp();
            if (lane == 0) mbar_arrive(bar + HB_WE + (pr * 2 + (rnd & 1)) * 8);
            if (it == 0) HEV(3);
            const float dsk = bf2f(Dsk[d]);
#pragma unroll
            for (int G = 0; G < 4; G++)
#pragma unroll
                for (int i = 0; i < 4; i++)
#pragma unroll
                    for (int j = 0; j < 4; j++) {
                        __nv_bfloat16* p = (__nv_bfloat16*)(smem + H_U + ch * H_USTR + (8 * G + 2 * tq + (j & 1)) * 144 + (16 * i + g + (j >> 1) * 8) * 2);
                        const float y = bf2f(__float2bfloat16(acc[G][i][j])), sk = bf2f(__float2bfloat16(bf2f(*p) * dsk));
                        *p = __float2bfloat16(y + sk);
                    }
        }
        HEV(4); GT(96, 1);
        const int wg = warp >> 2, q = warp & 3, t = tid & 127;
        const int nt = shared ? (cta & 3) * 2 + wg : 8, kg = shared ? cta >> 2 : (cta - 32) * 2 + wg;
        fence_smem_async();
        bar_arrive(HN_Y, 320);
        uint32_t w[32][4];
        {
            const uint32_t* src = (const uint32_t*)(Wo + (size_t)(kg * 512 + tq * 8) * DM + nt * 64 + q * 16) + g;
#pragma unroll
            for (int i = 0; i < 64; i++) {
                const int row = (i >> 2) * 32 + (i & 3) * 2;
                const uint32_t x = __ldg(src + row * (DM / 2)), y = __ldg(src + (row + 1) * (DM / 2));
                w[i >> 1][(i & 1) * 2] = __byte_perm(x, y, 0x5410);
                w[i >> 1][(i & 1) * 2 + 1] = __byte_perm(x, y, 0x7632);
            }
        }
        HEV(5);
        if (wg == 1) bar_arrive(HN_P, 256);
        uint32_t* const px = &g_part[0][nt][0][0][t];
        uint32_t* const dst = (uint32_t*)(out + (size_t)((kg >> 1) * 8 + 2 * tq + (kg & 1)) * OUTW + nt * 64 + q * 16) + g;
#pragma unroll 1
        for (int s = 0; s < ((HM & 4) ? NSEG + LAG : 0); s++) {
            const int f = s - LAG;
            const uint32_t* const src = px + (f & 7) * (9 * 8192) + kg * 1024;
            uint32_t v[8];
#pragma unroll
            for (int i = 0; i < 8; i++) v[i] = ldg_rlx(src + i * 128);
            float d[16];
            if (s < NSEG) {
                const int n = shared ? 2 * s : 4 * s + 2 * wg, r = n / NST, st = n - r * NST;
                const uint32_t dl = desc_lo(sb + H_RING + st * 16384);
                if (wg == 0) HS(0);
                mbar_wait(bar + HB_FULL + st * 8, r & 1);
                bar_sync(HN_P + wg, 256);
                if (wg == 0) HS(1);
                wg_fence();
                wgmma32<0>(d, w[0], desc_of(dl));
#pragma unroll
                for (int i = 1; i < 16; i++) wgmma32<1>(d, w[i], desc_of(dl + (i >> 2) * 256 + (i & 3) * 2));
                wg_commit();
                mbar_wait(bar + HB_FULL + st * 8 + 8, r & 1);
                wg_fence();
#pragma unroll
                for (int i = 16; i < PPT; i++) wgmma32<1>(d, w[i], desc_of(dl + (i >> 2) * 256 + (i & 3) * 2));
                bar_arrive(HN_P + (wg ^ 1), 256);
#pragma unroll
                for (int i = PPT; i < 32; i++) wgmma32<1>(d, w[i], desc_of(dl + (i >> 2) * 256 + (i & 3) * 2));
                wg_commit();
                asm volatile("wgmma.wait_group.sync.aligned 1;" ::: "memory");
                mbar_arrive_warp(bar + HB_EMPTY + st * 8);
                wg_wait0();
                mbar_arrive_warp(bar + HB_EMPTY + st * 8 + 8);
                if (wg == 0) HS(2);
                const uint32_t ph = ((s >> 3) + 1) & 1, rnd = ph ? 0u : 0x10000u;
                uint32_t* const p = px + (s & 7) * (9 * 8192) + kg * 128;
#pragma unroll
                for (int r = 0; r < 8; r++) {
                    const uint32_t lo = __float_as_uint(d[4 * (r >> 1) + (r & 1)]) + rnd, hi = __float_as_uint(d[4 * (r >> 1) + 2 + (r & 1)]) + 0x8000u;
                    stg_rlx(p + r * 1024, (__byte_perm(lo, hi, 0x7632) & 0xfffffffeu) | ph);
                }
                if (wg == 0) HS(3);
            }
            if (s >= LAG) {
                const uint32_t ph = ((f >> 3) + 1) & 1;
                for (int it = 0; __any_sync(0xffffffffu, (or3(diff2(v[0], v[1], ph), diff2(v[2], v[3], ph), diff2(v[4], v[5], ph)) | diff2(v[6], v[7], ph)) & 1);) {
#pragma unroll
                    for (int i = 0; i < 8; i++) v[i] = ldg_rlx(src + i * 128);
                    if (++it > (1 << 22)) TRAP(2000 + __LINE__);
                }
            }
            if (s >= LAG)
                dst[(size_t)f * 32 * (OUTW / 2)] = pack2(((bflo(v[0]) + bflo(v[1])) + (bflo(v[2]) + bflo(v[3]))) + ((bflo(v[4]) + bflo(v[5])) + (bflo(v[6]) + bflo(v[7]))),
                                                         ((bfhi(v[0]) + bfhi(v[1])) + (bfhi(v[2]) + bfhi(v[3]))) + ((bfhi(v[4]) + bfhi(v[5])) + (bfhi(v[6]) + bfhi(v[7]))));
            if (wg == 0) HS(4);
        }
        if ((HM & 4) && wg == 0) bar_sync(HN_P, 256);
    } else if (warp < 12) {
        asm volatile("setmaxnreg.dec.sync.aligned.u32 48;");
        if (tid - 256 < 64) ((uint32_t*)(smem + H_Z))[tid - 256] = 0;
        spin_until(tstart + UDLY);
        LOAD_U(warp - 4)
        bar_arrive(HN_U, 384);
        const int hd = cta, h0 = shared ? cta & 28 : (cta - 32) * 8, nst = shared ? 2 : 4;
        if (warp == 8) {
            bar_sync(HN_Y, 320);
            int ready = 0;
#pragma unroll 1
            for (int s = 0; s < ((HM & 4) ? NSEG : 0); s++) {
                for (int it = 0; ready <= s;) {
                    unsigned v = epoch;
                    if (s + (lane >> 3) < NSEG) v = ldg_acq(&g_oflag[s + (lane >> 3)][h0 + (lane & (2 * nst - 1))][0]);
                    const uint32_t miss = ~__ballot_sync(0xffffffffu, v == epoch);
                    ready = s + (miss ? (__ffs(miss) - 1) >> 3 : 4);
                    if (++it > (1 << 24)) TRAP(2000 + __LINE__);
                }
                asm volatile("fence.proxy.async.global;" ::: "memory");
#pragma unroll 1
                for (int i = 0; i < nst; i++) {
                    const int n = nst * s + i, r = n / NST, st = n - r * NST;
                    if (r > 0) mbar_wait(bar + HB_EMPTY + st * 8, (r - 1) & 1);
                    if (lane == 0) {
                        mbar_expect(bar + HB_FULL + st * 8, 16384);
                        bulk_g2s(sb + H_RING + st * 16384, (const char*)g_o + (size_t)(s * 64 + h0 * 2 + i * 4) * 4096, 16384, bar + HB_FULL + st * 8);
                    }
                    __syncwarp();
                }
                HS(7);
            }
        } else if (warp == 9) {
#pragma unroll 1
            for (int s = 0; s < ((HM & 2) && shared ? NSEG : 0); s++) {
                const int c = lane % 3;
                unsigned v;
                for (int it = 0; v = ldg_acq(&g_qflag[s][hd][c * 8]), !__all_sync(0xffffffffu, (v ^ (epoch * 64)) < 64);)
                    if (++it > (1 << 24)) TRAP(2000 + __LINE__);
                HS(5);
                asm volatile("fence.proxy.async.global;" ::: "memory");
                const uint32_t off = lane < 3 ? c * 7680 : lane < 6 ? 20480 + c * 2048 : 28672 + c * 512;
                const unsigned char* const src = g_qkv + (size_t)((v & 63) * 32 + hd) * 30720 + off;
                if (s > 0) mbar_wait(bar + HB_QE, (s - 1) & 1);
                if (lane == 0) mbar_expect(bar + HB_QF, 20480);
                if (lane < 3) bulk_g2s(sb + H_QKV + off, src, c == 2 ? 5120 : 7680, bar + HB_QF);
                __syncwarp();
                if (s > 0) mbar_wait(bar + HB_VE, (s - 1) & 1);
                if (lane == 0) mbar_expect(bar + HB_VF, 10240);
                if (lane >= 3 && lane < 9) bulk_g2s(sb + H_QKV + off, src, (lane < 6 ? 2048 : 512) << (c >> 1), bar + HB_VF);
                __syncwarp();
            }
        } else if (warp == 10) {
#pragma unroll 1
            for (int s = 0; s < ((HM & 2) && shared ? NSEG : 0); s++) {
                mbar_wait(bar + HB_OF, s & 1);
                if (lane == 0) {
                    bulk_s2g((char*)g_o + (size_t)(s * 64 + hd * 2) * 4096, sb + H_AO, 8192);
                    asm volatile("cp.async.bulk.commit_group;" ::: "memory");
                    asm volatile("cp.async.bulk.wait_group.read 0;" ::: "memory");
                    mbar_arrive(bar + HB_OE);
                    asm volatile("cp.async.bulk.wait_group 0;" ::: "memory");
                    stg_rlx(&g_oflag[s][hd][0], epoch);
                }
                __syncwarp();
                HS(6);
            }
        } else {
            bar_sync(HN_Y, 320);
#pragma unroll 1
            for (int i = 0; i < 128; i++) {
                const uint32_t t0 = clk();
                uint32_t v[4];
                ldsm4t(v, sb + H_U + (lane & 15) * H_USTR + (i >> 2) * 144 + (i & 3) * 32 + (lane >> 4) * 16);
                uint2* const p = (uint2*)(out + (size_t)(i * 16 + g) * OUTW + DM + d0 + tq * 4);
                p[0] = make_uint2(v[0], v[1]);
                p[8 * (OUTW / 4)] = make_uint2(v[2], v[3]);
                spin_until(t0 + YDLY);
            }
            asm volatile("griddepcontrol.wait;" ::: "memory");
        }
    } else {
        asm volatile("setmaxnreg.dec.sync.aligned.u32 112;");
        const uint32_t qk = sb + H_QKV;
        const int dg = 8 * (warp & 3) + g - 2 * tq;
        const uint32_t oa = pin(sb + H_AO + (8 * (warp & 3) + g) * 128);
#pragma unroll 1
        for (int s = 0; s < ((HM & 2) && shared ? NSEG : 0); s++) {
            float x[24];
            mbar_wait(bar + HB_QF, s & 1);
            wg_fence();
#pragma unroll
            for (int i = 0; i < 8; i++) {
                constexpr int QO[8] = {0, 1024, 2048, 7680, 8704, 9728, 15360, 16384}, KO[8] = {3072, 4608, 6144, 10752, 12288, 13824, 17408, 18944};
                if (i == 0) wgmma48_tt<0>(x, desc_plain(qk + QO[i], 128, 128), desc_plain(qk + KO[i], 128, 256));
                else wgmma48_tt<1>(x, desc_plain(qk + QO[i], 128, 128), desc_plain(qk + KO[i], 128, 256));
            }
            wg_commit();
            wg_wait0();
            mbar_arrive_warp(bar + HB_QE);
            x[16] += x[20]; x[17] += x[21];
            float m = fmaxf(x[16], x[17]);
#pragma unroll
            for (int b = 0; b < 4; b++) {
                if (8 * b > dg) x[4 * b] = NEG;
                if (8 * b + 1 > dg) x[4 * b + 1] = NEG;
                m = fmaxf(m, fmaxf(x[4 * b], x[4 * b + 1]));
            }
            m = fmaxf(m, __shfl_xor_sync(0xffffffffu, m, 1));
            m = fmaxf(m, __shfl_xor_sync(0xffffffffu, m, 2));
            float l = 0.f;
            uint32_t pa[3][4];
#pragma unroll
            for (int b = 0; b < 5; b++) {
                const float e0 = ex2(x[4 * b] - m), e1 = ex2(x[4 * b + 1] - m);
                l += e0 + e1;
                pa[b >> 1][(b & 1) * 2] = pack2(e0, e1);
                pa[b >> 1][(b & 1) * 2 + 1] = 0;
            }
            pa[2][2] = pa[2][3] = 0;
            l += __shfl_xor_sync(0xffffffffu, l, 1);
            l = rcp_fast(l + __shfl_xor_sync(0xffffffffu, l, 2));
            uint32_t ow[2][8];
            mbar_wait(bar + HB_VF, s & 1);
#pragma unroll
            for (int hf = 0; hf < 2; hf++) {
                float o[32];
                wg_fence();
                wgmma64<0>(o, pa[0], desc_plain(qk + 20480 + hf * 128, 256, 1024));
                wgmma64<1>(o, pa[1], desc_plain(qk + 20480 + 512 + hf * 128, 256, 1024));
                wgmma64<1>(o, pa[2], desc_plain(qk + 28672 + hf * 128, 0, 256));
                wg_commit();
                if (hf == 0 && s > 0) mbar_wait(bar + HB_OE, (s - 1) & 1);
                wg_wait0();
#pragma unroll
                for (int i = 0; i < 8; i++) ow[hf][i] = pack2(o[4 * i] * l, o[4 * i + 1] * l);
            }
            mbar_arrive_warp(bar + HB_VE);
#pragma unroll
            for (int grp = 0; grp < 4; grp++)
                sts128(oa + (grp >> 1) * 4096 + ((((grp & 1) * 4 + tq) ^ g) << 4), ow[0][2 * grp], ow[1][2 * grp], ow[0][2 * grp + 1], ow[1][2 * grp + 1]);
            fence_smem_async();
            mbar_arrive_warp(bar + HB_OF);
        }
    }
}

typedef CUresult (*EncodeFn)(CUtensorMap*, CUtensorMapDataType, cuuint32_t, void*, const cuuint64_t*, const cuuint64_t*, const cuuint32_t*,
                             const cuuint32_t*, CUtensorMapInterleave, CUtensorMapSwizzle, CUtensorMapL2promotion, CUtensorMapFloatOOBfill);

static void make_map(EncodeFn enc, CUtensorMap* m, void* base, int width, int boxchunks) {
    cuuint64_t dims[3] = {64, 2048, (cuuint64_t)(width / 64)};
    cuuint64_t strides[2] = {(cuuint64_t)width * 2, 128};
    cuuint32_t box[3] = {64, 32, (cuuint32_t)boxchunks};
    cuuint32_t es[3] = {1, 1, 1};
    enc(m, CU_TENSOR_MAP_DATA_TYPE_BFLOAT16, 3, base, dims, strides, box, es, CU_TENSOR_MAP_INTERLEAVE_NONE, CU_TENSOR_MAP_SWIZZLE_128B,
        CU_TENSOR_MAP_L2_PROMOTION_L2_256B, CU_TENSOR_MAP_FLOAT_OOB_FILL_NONE);
}

extern "C" void kernel_launch(void* const* d_in, const int* in_sizes, int n_in, void* d_out, int out_size) {
    typedef const __nv_bfloat16* P;
    static EncodeFn enc = nullptr;
    if (!enc) {
        void* fn = nullptr;
        cudaDriverEntryPointQueryResult st;
        cudaGetDriverEntryPoint("cuTensorMapEncodeTiled", &fn, cudaEnableDefault, &st);
        enc = (EncodeFn)fn;
        cudaFuncSetAttribute(rk_kernel, cudaFuncAttributeMaxDynamicSharedMemorySize, R_SMEM);
        cudaFuncSetAttribute(hk_kernel, cudaFuncAttributeMaxDynamicSharedMemorySize, H_SMEM);
    }
    Maps maps;
    make_map(enc, &maps.x, d_in[0], DM, 3);
    {
        void* acc = nullptr;
        cudaGetSymbolAddress(&acc, g_acc);
        for (int m = 0; m < 2; m++) {
            cuuint64_t dims[5] = {128, 2, 2, 2, 144};
            cuuint64_t strides[4] = {(cuuint64_t)(m ? 4096 : 12288), 1024, 16384, 256};
            cuuint32_t box[5] = {64, 2, 2, 2, 2}, es[5] = {1, 1, 1, 1, 1};
            enc(&maps.acc[m], CU_TENSOR_MAP_DATA_TYPE_BFLOAT16, 5, (char*)acc + m * 4096, dims, strides, box, es, CU_TENSOR_MAP_INTERLEAVE_NONE,
                CU_TENSOR_MAP_SWIZZLE_NONE, CU_TENSOR_MAP_L2_PROMOTION_NONE, CU_TENSOR_MAP_FLOAT_OOB_FILL_NONE);
        }
    }

    cudaLaunchConfig_t cfg = {};
    cudaLaunchAttribute at[1];
    cfg.gridDim = dim3(96); cfg.blockDim = dim3(384); cfg.dynamicSmemBytes = R_SMEM; cfg.stream = cudaStreamPerThread;
    at[0].id = cudaLaunchAttributeClusterDimension; at[0].val.clusterDim.x = 3; at[0].val.clusterDim.y = 1; at[0].val.clusterDim.z = 1;
    cfg.attrs = at; cfg.numAttrs = 1;
    cudaLaunchKernelEx(&cfg, rk_kernel, maps, (P)d_in[0], (P)d_in[1], (P)d_in[2], (P)d_in[3], (P)d_in[4], (P)d_in[5]);

    cfg.gridDim = dim3(36); cfg.blockDim = dim3(512); cfg.dynamicSmemBytes = H_SMEM;
    at[0].id = cudaLaunchAttributeProgrammaticStreamSerialization; at[0].val.programmaticStreamSerializationAllowed = 1;
    cudaLaunchKernelEx(&cfg, hk_kernel, (P)d_in[5], (P)d_in[7], (P)d_in[8], (P)d_in[9], (P)d_in[10], (P)d_in[11], (P)d_in[12], (P)d_in[13],
                       (__nv_bfloat16*)d_out);
}
```

```cpp
#include <cuda_runtime.h>
#include <cuda_bf16.h>
#include <cuda_fp16.h>
#include <cuda.h>
#include <stdint.h>

#define DEVI __device__ __forceinline__

#define NEG __int_as_float(0xff800000)
constexpr int DM = 576, NSEG = 64, HD = 4096, OUTW = 1152;

#define HM 7
#define QW 4000
#define NPROBE 4
#define CT 1700
#define FE 85
#define DL 0
#define DMIN 150
#define DMAX 4000
#define BACKOFF 200
#define LW 4
#define TIE 0
#define C2ADJ 80
#define DST 260
#define VFE 0
#define EW 0
#define LB 12
#define NTR 3
#define RP 176
#define NW2 3
#define KT 4
#define DDUMP 520
#define DPUSH 300
#define GOE 1
#define LDM 0
#define XD 150
#define G1T 0
#define F0T 14
#define F1T 16
#define SUMV 0
#define UDLY 0
#define YDLY 300
#define PPT 32
#define LAG 3
#define QR 4
#define DUPL 1
#define N1 8

__device__ __align__(1024) __nv_bfloat16 g_o[2048 * HD];
__device__ __align__(65536) uint32_t g_acc[16384];
__device__ __align__(128) unsigned g_pub[96];
__device__ __align__(128) uint32_t g_part[8][9][8][8][128];
__device__ __align__(1024) unsigned char g_qkv[(size_t)NSEG * 32 * 30720];
__device__ __align__(128) unsigned g_qflag[NSEG][32][32];
__device__ __align__(128) unsigned g_oflag[NSEG][32][8];
__device__ unsigned g_epoch[36 + 96];
#define EV(i)
#define EVV(i, v)
#define EVX(i) 0
#define EVADD(i, v)
#define HS(i)
#define HEV(i)
#define GT(b, i)

#define TRAP(code) __trap()
#define LOC(v)
DEVI uint32_t smem_u32(const void* p) { return (uint32_t)__cvta_generic_to_shared(p); }
DEVI uint32_t clk() { uint64_t t; asm volatile("mov.u64 %0, %%clock64;" : "=l"(t) :: "memory"); return (uint32_t)t; }
DEVI uint32_t gtime() { uint64_t t; asm volatile("mov.u64 %0, %%globaltimer;" : "=l"(t) :: "memory"); return (uint32_t)t; }
DEVI void spin_until(uint32_t t) { while ((int)(clk() - t) < 0) {} }
DEVI void jit() {}
DEVI uint32_t mapa(uint32_t a, uint32_t r) { uint32_t o; asm("mapa.shared::cluster.u32 %0, %1, %2;" : "=r"(o) : "r"(a), "r"(r)); return o; }
DEVI void mbar_init(uint32_t b, uint32_t n) { asm volatile("mbarrier.init.shared::cta.b64 [%0], %1;" :: "r"(b), "r"(n) : "memory"); }
DEVI void mbar_expect(uint32_t b, uint32_t bytes) { asm volatile("mbarrier.arrive.expect_tx.shared::cta.b64 _, [%0], %1;" :: "r"(b), "r"(bytes) : "memory"); }
DEVI void mbar_arrive(uint32_t b) { asm volatile("mbarrier.arrive.shared::cta.b64 _, [%0];" :: "r"(b) : "memory"); }
DEVI bool mbar_try(uint32_t b, uint32_t parity) {
    uint32_t ok;
    asm volatile("{.reg .pred p; mbarrier.try_wait.parity.shared::cta.b64 p, [%1], %2; selp.u32 %0, 1, 0, p;}" : "=r"(ok) : "r"(b), "r"(parity) : "memory");
    return ok;
}
DEVI void mbar_wait(uint32_t b, uint32_t parity) {
    LOC(0x100 | (b & 0xff) | (parity << 12));
    asm volatile("{.reg .pred p, q; .reg .u32 n; mov.u32 n, 0;\n W: mbarrier.try_wait.parity.shared::cta.b64 p, [%0], %1;\n"
                 "add.u32 n, n, 1; setp.lt.and.u32 q, n, 0x40000, !p; @q bra W;}" :: "r"(b), "r"(parity) : "memory");
    LOC(0x300 | (b & 0xff));
    jit();
}
DEVI void bar_sync(int id, int n) { jit(); LOC(0x200 | id); asm volatile("bar.sync %0, %1;" :: "r"(id), "r"(n) : "memory"); LOC(0x400 | id); jit(); }
DEVI void bar_arrive(int id, int n) { jit(); asm volatile("bar.arrive %0, %1;" :: "r"(id), "r"(n) : "memory"); jit(); }
DEVI void cluster_sync() { asm volatile("barrier.cluster.arrive.release.aligned; barrier.cluster.wait.acquire.aligned;" ::: "memory"); }
DEVI void cluster_arrive_rlx() { asm volatile("barrier.cluster.arrive.relaxed.aligned;" ::: "memory"); }
DEVI void cluster_wait() { asm volatile("barrier.cluster.wait.aligned;" ::: "memory"); }
DEVI void fence_async() { asm volatile("fence.proxy.async;" ::: "memory"); }
DEVI void cp16(uint32_t dst, const void* src) { asm volatile("cp.async.cg.shared.global [%0], [%1], 16;" :: "r"(dst), "l"(src) : "memory"); }
DEVI void cp_commit() { asm volatile("cp.async.commit_group;" ::: "memory"); }
template <int N> DEVI void cp_wait() { asm volatile("cp.async.wait_group %0;" :: "n"(N) : "memory"); }
DEVI void ldsm4(uint32_t* r, uint32_t a) {
    asm volatile("ldmatrix.sync.aligned.m8n8.x4.shared.b16 {%0,%1,%2,%3}, [%4];" : "=r"(r[0]), "=r"(r[1]), "=r"(r[2]), "=r"(r[3]) : "r"(a) : "memory");
}
DEVI uint32_t tab1(uint32_t a) { uint32_t r; asm volatile("ldmatrix.sync.aligned.m8n8.x1.shared.b16 {%0}, [%1];" : "=r"(r) : "r"(a) : "memory"); return r; }
DEVI uint2 tab2(uint32_t a) { uint2 r; asm volatile("ldmatrix.sync.aligned.m8n8.x2.shared.b16 {%0,%1}, [%2];" : "=r"(r.x), "=r"(r.y) : "r"(a) : "memory"); return r; }
DEVI void ldsm4t(uint32_t* r, uint32_t a) {
    asm volatile("ldmatrix.sync.aligned.m8n8.x4.trans.shared.b16 {%0,%1,%2,%3}, [%4];" : "=r"(r[0]), "=r"(r[1]), "=r"(r[2]), "=r"(r[3]) : "r"(a) : "memory");
}
DEVI void mma16(float* d, uint32_t a0, uint32_t a1, uint32_t a2, uint32_t a3, uint32_t b0, uint32_t b1) {
    asm volatile("mma.sync.aligned.m16n8k16.row.col.f32.bf16.bf16.f32 {%0,%1,%2,%3}, {%4,%5,%6,%7}, {%8,%9}, {%0,%1,%2,%3};"
                 : "+f"(d[0]), "+f"(d[1]), "+f"(d[2]), "+f"(d[3]) : "r"(a0), "r"(a1), "r"(a2), "r"(a3), "r"(b0), "r"(b1));
}
DEVI void mma8(float* d, uint32_t a0, uint32_t a1, uint32_t b0) {
    asm volatile("mma.sync.aligned.m16n8k8.row.col.f32.bf16.bf16.f32 {%0,%1,%2,%3}, {%4,%5}, {%6}, {%0,%1,%2,%3};"
                 : "+f"(d[0]), "+f"(d[1]), "+f"(d[2]), "+f"(d[3]) : "r"(a0), "r"(a1), "r"(b0));
}
DEVI void mma_tf32(float* d, uint32_t a0, uint32_t a1, uint32_t a2, uint32_t a3, uint32_t b0, uint32_t b1) {
    asm volatile("mma.sync.aligned.m16n8k8.row.col.f32.tf32.tf32.f32 {%0,%1,%2,%3}, {%4,%5,%6,%7}, {%8,%9}, {%0,%1,%2,%3};"
                 : "+f"(d[0]), "+f"(d[1]), "+f"(d[2]), "+f"(d[3]) : "r"(a0), "r"(a1), "r"(a2), "r"(a3), "r"(b0), "r"(b1));
}
template <int ACC> DEVI void wgmma32(float* d, const uint32_t* a, uint64_t desc) {
    asm volatile("wgmma.mma_async.sync.aligned.m64n32k16.f32.bf16.bf16 "
                 "{%0,%1,%2,%3,%4,%5,%6,%7,%8,%9,%10,%11,%12,%13,%14,%15}, {%16,%17,%18,%19}, %20, %21, 1, 1, 0;"
                 : "+f"(d[0]), "+f"(d[1]), "+f"(d[2]), "+f"(d[3]), "+f"(d[4]), "+f"(d[5]), "+f"(d[6]), "+f"(d[7]),
                   "+f"(d[8]), "+f"(d[9]), "+f"(d[10]), "+f"(d[11]), "+f"(d[12]), "+f"(d[13]), "+f"(d[14]), "+f"(d[15])
                 : "r"(a[0]), "r"(a[1]), "r"(a[2]), "r"(a[3]), "l"(desc), "n"(ACC));
}
template <int ACC> DEVI void wgmma32_ss(float* d, uint64_t adesc, uint64_t desc) {
    asm volatile("wgmma.mma_async.sync.aligned.m64n32k16.f32.bf16.bf16 "
                 "{%0,%1,%2,%3,%4,%5,%6,%7,%8,%9,%10,%11,%12,%13,%14,%15}, %16, %17, %18, 1, 1, 1, 0;"
                 : "+f"(d[0]), "+f"(d[1]), "+f"(d[2]), "+f"(d[3]), "+f"(d[4]), "+f"(d[5]), "+f"(d[6]), "+f"(d[7]),
                   "+f"(d[8]), "+f"(d[9]), "+f"(d[10]), "+f"(d[11]), "+f"(d[12]), "+f"(d[13]), "+f"(d[14]), "+f"(d[15])
                 : "l"(adesc), "l"(desc), "n"(ACC));
}
DEVI void wg_fence() { asm volatile("wgmma.fence.sync.aligned;" ::: "memory"); }
DEVI void wg_commit() { asm volatile("wgmma.commit_group.sync.aligned;" ::: "memory"); }
DEVI void wg_wait0() { asm volatile("wgmma.wait_group.sync.aligned 0;" ::: "memory"); }
DEVI uint64_t desc_sw128(uint32_t saddr) { return ((uint64_t)1 << 62) | ((uint64_t)64 << 32) | ((uint64_t)1 << 16) | (uint64_t)((saddr & 0x3FFFF) >> 4); }
DEVI uint32_t desc_lo(uint32_t saddr) { return (1u << 16) | ((saddr & 0x3FFFF) >> 4); }
DEVI uint64_t desc_of(uint32_t lo) { uint64_t d; asm("mov.b64 %0, {%1, 0x40000040};" : "=l"(d) : "r"(lo)); return d; }
DEVI uint32_t pack2(float lo, float hi) { uint32_t r; asm("cvt.rn.bf16x2.f32 %0, %1, %2;" : "=r"(r) : "f"(hi), "f"(lo)); return r; }
DEVI void sts32(uint32_t a, uint32_t v) { asm volatile("st.shared.u32 [%0], %1;" :: "r"(a), "r"(v) : "memory"); }
DEVI void sts64f(uint32_t a, float x, float y) { asm volatile("st.shared.v2.f32 [%0], {%1,%2};" :: "r"(a), "f"(x), "f"(y) : "memory"); }
DEVI void sts128f(uint32_t a, float x, float y, float z, float w) { asm volatile("st.shared.v4.f32 [%0], {%1,%2,%3,%4};" :: "r"(a), "f"(x), "f"(y), "f"(z), "f"(w) : "memory"); }
DEVI float2 lds64f(uint32_t a) { float2 v; asm volatile("ld.shared.v2.f32 {%0,%1}, [%2];" : "=f"(v.x), "=f"(v.y) : "r"(a) : "memory"); return v; }
DEVI float4 lds128f(uint32_t a) { float4 v; asm volatile("ld.shared.v4.f32 {%0,%1,%2,%3}, [%4];" : "=f"(v.x), "=f"(v.y), "=f"(v.z), "=f"(v.w) : "r"(a) : "memory"); return v; }
DEVI uint4 lds128(uint32_t a) { uint4 v; asm volatile("ld.shared.v4.u32 {%0,%1,%2,%3}, [%4];" : "=r"(v.x), "=r"(v.y), "=r"(v.z), "=r"(v.w) : "r"(a) : "memory"); return v; }
DEVI uint4 ldm128(uint32_t a) {
    uint4 v;
    asm volatile("ld.shared.v4.u32 {%0,%1,%2,%3}, [%4];" : "=r"(v.x), "=r"(v.y), "=r"(v.z), "=r"(v.w) : "r"(a) : "memory");
    return v;
}
DEVI void sta32(uint32_t a, uint32_t v, uint32_t bar) { asm volatile("st.async.weak.shared::cluster.mbarrier::complete_tx::bytes.b32 [%0], %1, [%2];" :: "r"(a), "r"(v), "r"(bar) : "memory"); }
DEVI void sta64f(uint32_t a, float x, float y, uint32_t bar) { asm volatile("st.async.weak.shared::cluster.mbarrier::complete_tx::bytes.v2.f32 [%0], {%1,%2}, [%3];" :: "r"(a), "f"(x), "f"(y), "r"(bar) : "memory"); }
DEVI void sta128f(uint32_t a, float x, float y, float z, float w, uint32_t bar) {
    asm volatile("st.async.weak.shared::cluster.mbarrier::complete_tx::bytes.v4.f32 [%0], {%1,%2,%3,%4}, [%5];" :: "r"(a), "f"(x), "f"(y), "f"(z), "f"(w), "r"(bar) : "memory");
}
DEVI void stg_rlx(uint32_t* p, uint32_t v) { asm volatile("st.relaxed.gpu.global.u32 [%0], %1;" :: "l"(p), "r"(v) : "memory"); }
DEVI void stg_release(unsigned* p, unsigned v) { asm volatile("st.release.gpu.global.u32 [%0], %1;" :: "l"(p), "r"(v) : "memory"); }
DEVI uint32_t ldg_rlx(const uint32_t* p) { uint32_t v; asm volatile("ld.relaxed.gpu.global.u32 %0, [%1];" : "=r"(v) : "l"(p) : "memory"); return v; }
DEVI void bulk_g2s(uint32_t dst, const void* src, uint32_t bytes, uint32_t bar) {
    asm volatile("cp.async.bulk.shared::cluster.global.mbarrier::complete_tx::bytes [%0], [%1], %2, [%3];" :: "r"(dst), "l"(src), "r"(bytes), "r"(bar) : "memory");
}
DEVI void bulk_s2c(uint32_t dst, uint32_t src, uint32_t bytes, uint32_t bar) {
    asm volatile("cp.async.bulk.shared::cluster.shared::cta.mbarrier::complete_tx::bytes [%0], [%1], %2, [%3];" :: "r"(dst), "r"(src), "r"(bytes), "r"(bar) : "memory");
}
DEVI float ex2(float x) { float y; asm("ex2.approx.ftz.f32 %0, %1;" : "=f"(y) : "f"(x)); return y; }
DEVI float bf2f(__nv_bfloat16 v) { return __bfloat162float(v); }

DEVI uint32_t pin(uint32_t v) { return __shfl_sync(0xffffffffu, v, threadIdx.x & 31); }
template <typename T> DEVI T* pinp(T* p) { const uint64_t v = (uint64_t)p; return (T*)(((uint64_t)pin((uint32_t)(v >> 32)) << 32) | pin((uint32_t)v)); }
DEVI uint32_t fresh(uint32_t v) { uint32_t r; asm volatile("mov.u32 %0, %1;" : "=r"(r) : "r"(v)); return r; }
DEVI uint64_t fresh64(uint64_t v) { uint64_t r; asm volatile("mov.u64 %0, %1;" : "=l"(r) : "l"(v)); return r; }
DEVI uint32_t or3(uint32_t a, uint32_t b, uint32_t c) { uint32_t d; asm("lop3.b32 %0, %1, %2, %3, 0xfe;" : "=r"(d) : "r"(a), "r"(b), "r"(c)); return d; }
DEVI uint32_t and3(uint32_t a, uint32_t b, uint32_t c) { uint32_t d; asm("lop3.b32 %0, %1, %2, %3, 0x80;" : "=r"(d) : "r"(a), "r"(b), "r"(c)); return d; }
DEVI uint32_t diff2(uint32_t a, uint32_t b, uint32_t p) { uint32_t d; asm("lop3.b32 %0, %1, %2, %3, 0x7e;" : "=r"(d) : "r"(a), "r"(b), "r"(p)); return d; }
DEVI int lds32(uint32_t a) { int v; asm volatile("ld.volatile.shared.s32 %0, [%1];" : "=r"(v) : "r"(a) : "memory"); return v; }
DEVI uint2 lds64(uint32_t a) { uint2 v; asm volatile("ld.shared.v2.u32 {%0,%1}, [%2];" : "=r"(v.x), "=r"(v.y) : "r"(a) : "memory"); return v; }
DEVI void sts64(uint32_t a, uint32_t x, uint32_t y) { asm volatile("st.shared.v2.u32 [%0], {%1,%2};" :: "r"(a), "r"(x), "r"(y) : "memory"); }
DEVI void sta64(uint32_t a, uint32_t x, uint32_t y, uint32_t bar) { asm volatile("st.async.weak.shared::cluster.mbarrier::complete_tx::bytes.v2.b32 [%0], {%1,%2}, [%3];" :: "r"(a), "r"(x), "r"(y), "r"(bar) : "memory"); }
DEVI float rcp_fast(float x) { float y; asm("rcp.approx.ftz.f32 %0, %1;" : "=f"(y) : "f"(x)); return y; }
DEVI uint4 ldg_rlx4(const void* p) { uint4 v; asm volatile("ld.relaxed.gpu.global.v4.u32 {%0,%1,%2,%3}, [%4];" : "=r"(v.x), "=r"(v.y), "=r"(v.z), "=r"(v.w) : "l"(p) : "memory"); return v; }
DEVI void sts128(uint32_t a, uint32_t x, uint32_t y, uint32_t z, uint32_t w) { asm volatile("st.shared.v4.u32 [%0], {%1,%2,%3,%4};" :: "r"(a), "r"(x), "r"(y), "r"(z), "r"(w) : "memory"); }
DEVI void stsm4(uint32_t a, uint32_t x, uint32_t y, uint32_t z, uint32_t w) { asm volatile("stmatrix.sync.aligned.m8n8.x4.shared.b16 [%0], {%1,%2,%3,%4};" :: "r"(a), "r"(x), "r"(y), "r"(z), "r"(w) : "memory"); }
DEVI void stsm2(uint32_t a, uint32_t x, uint32_t y) { asm volatile("stmatrix.sync.aligned.m8n8.x2.shared.b16 [%0], {%1,%2};" :: "r"(a), "r"(x), "r"(y) : "memory"); }
DEVI void fence_smem_async() { asm volatile("fence.proxy.async.shared::cta;" ::: "memory"); }
DEVI uint32_t packh2(float lo, float hi) { uint32_t r; asm("cvt.rn.f16x2.f32 %0, %1, %2;" : "=r"(r) : "f"(hi), "f"(lo)); return r; }
DEVI uint32_t h2_to_bf2(uint32_t w) {
    uint32_t r;
    asm("{.reg .f16 l, h; .reg .f32 a, b; mov.b32 {l, h}, %1; cvt.f32.f16 a, l; cvt.f32.f16 b, h; cvt.rn.bf16x2.f32 %0, b, a;}" : "=r"(r) : "r"(w));
    return r;
}
DEVI uint32_t amax2(uint32_t m, uint32_t w) { return __vmaxu2(m, w & 0x7fff7fffu); }
DEVI uint32_t amax_fold(uint32_t m) { return __reduce_max_sync(0xffffffffu, max(m & 0xffffu, m >> 16)); }
DEVI float bflo(uint32_t w) { return __uint_as_float(w << 16); }
DEVI float bfhi(uint32_t w) { return __uint_as_float(w & 0xffff0000u); }
DEVI void red_b8(void* p, uint32_t a, uint32_t b, uint32_t c, uint32_t d) {
    asm volatile("red.relaxed.gpu.global.add.noftz.v4.bf16x2 [%0], {%1,%2,%3,%4};" :: "l"(p), "r"(a), "r"(b), "r"(c), "r"(d) : "memory");
}
DEVI void red_h8_if(bool on, void* p, uint32_t a, uint32_t b, uint32_t c, uint32_t d) {
    asm volatile("{.reg .pred p; setp.ne.u32 p, %5, 0; @p red.relaxed.gpu.global.add.noftz.v4.bf16x2 [%0], {%1,%2,%3,%4};}" :: "l"(p), "r"(a), "r"(b), "r"(c), "r"(d), "r"((uint32_t)on) : "memory");
}
DEVI void mbar_arrive_warp(uint32_t b) { asm volatile("{.reg .pred p; elect.sync _|p, 0xffffffff; @p mbarrier.arrive.shared::cta.b64 _, [%0];}" :: "r"(b) : "memory"); }
DEVI void bulk_s2c_warp(uint32_t dst, uint32_t src, uint32_t bytes, uint32_t bar) {
    asm volatile("{.reg .pred p; elect.sync _|p, 0xffffffff; @p cp.async.bulk.shared::cluster.shared::cta.mbarrier::complete_tx::bytes [%0], [%1], %2, [%3];}" :: "r"(dst), "r"(src), "r"(bytes), "r"(bar) : "memory");
}
DEVI char* mkptr(uint32_t lo, uint32_t hi) { uint64_t p; asm("mov.b64 %0, {%1, %2};" : "=l"(p) : "r"(lo), "r"(hi)); return (char*)p; }
DEVI void bulk_s2g(void* dst, uint32_t src, uint32_t bytes) { asm volatile("cp.async.bulk.global.shared::cta.bulk_group [%0], [%1], %2;" :: "l"(dst), "r"(src), "r"(bytes) : "memory"); }
DEVI void x_tma(uint32_t dst, const CUtensorMap* m, uint32_t xb, int row, int chunk) {
    asm volatile("cp.async.bulk.tensor.3d.shared::cluster.global.mbarrier::complete_tx::bytes.multicast::cluster [%0], [%1, {%3, %4, %5}], [%2], %6;"
                 :: "r"(dst), "l"(m), "r"(xb), "r"(0), "r"(row), "r"(chunk), "h"((uint16_t)7) : "memory");
}
#define RUNG_(A, B, PA, PB) "mov.u64 " A ", %%clock64;\n cvt.u32.u64 l, " B ";\n sub.s32 l, l, %0;\n setp.ge.s32 " PB ", l, 0;\n @" PA " bra.uni DONE;\n"
DEVI void fine_until(uint32_t t) {
    asm volatile("{.reg .pred p0, p1; .reg .b64 t0, t1; .reg .b32 l;\n setp.ne.u32 p0, 0, 0;\n mov.u64 t1, %%clock64;\n LOOP:\n"
                 RUNG_("t0", "t1", "p0", "p1") RUNG_("t1", "t0", "p1", "p0") RUNG_("t0", "t1", "p0", "p1") RUNG_("t1", "t0", "p1", "p0")
                 RUNG_("t0", "t1", "p0", "p1") RUNG_("t1", "t0", "p1", "p0") RUNG_("t0", "t1", "p0", "p1") RUNG_("t1", "t0", "p1", "p0")
                 "bra.uni LOOP;\n DONE:\n}" :: "r"(t) : "memory");
}
DEVI uint32_t clock_offset() {
    const uint32_t g0 = gtime();
    uint32_t e = clk();
#pragma unroll
    for (int i = 0; i < 7; i++) { const uint32_t g = gtime(), t = clk(); e = g == g0 ? t : e; }
    return ((((g0 >> 5) + 1) * 3686u) >> 6) - e;
}
DEVI uint32_t probe_rtt(uint32_t* a) {
    uint32_t best = 0xffffffffu;
#pragma unroll 1
    for (int r = 0; r < NPROBE; r++) {
        uint32_t v = 0, t0 = clk();
        if ((threadIdx.x & 31) == 0) asm volatile("atom.relaxed.gpu.global.exch.b32 %0, [%1], 0;" : "=r"(v) : "l"(a) : "memory");
        const uint32_t t1 = __shfl_sync(0xffffffffu, v, 0) == 0x9e3779b9u ? 0 : clk();
        best = min(best, t1 - t0);
    }
    return best;
}

constexpr int R_X0 = 0;
constexpr int R_WO = 36864;
constexpr int R_DBG = 110592;
constexpr int R_K = 114688 + 3072;
constexpr int R_V = R_K + 4608;
constexpr int R_VM = R_V + 8192;
constexpr int PAR = 17920;
constexpr int R_QM = R_VM + 2048 + PAR;
constexpr int R_SC = R_QM + 1536;
constexpr int R_O8 = R_SC + 2048;
constexpr int R_PX = R_O8 + 2048;
constexpr int R_PV = R_PX + 8192;
constexpr int R_Z = R_PV + 4096;
constexpr int R_T0 = R_Z + 512;
constexpr int R_T1 = R_T0 + 2048;
constexpr int R_T2 = R_T1 + 8192;
constexpr int R_T3 = R_T2 + 512;
constexpr int R_T4 = R_T3 + 2048;
constexpr int R_END = R_T4 + 4096;
constexpr int R_STAGE = 86016;
constexpr int R_MEM = 217088;
constexpr int R_BAR = R_MEM + 12288;
constexpr int R_MISC = R_BAR + 128;
constexpr int R_SMEM = R_MISC + 128;
static_assert(R_END <= R_STAGE + 7 * 16384, "smem");
enum { BX0 = 0  , BSC = 24, BME = 32, BVX = 40  , BML = 56 };
enum { NB_F1 = 1, NB_K = 5, NB_G1 = 6, NB_E0 = 7, NB_GO = 8, NB_W1 = 9, NB_H1 = 10, NB_TOK = 11, NB_W2 = 12, NB_F0 = 13, NB_L0 = 14   };
enum { M_EPOCH = 0, M_SINK = 4, M_PROBE = 8  , M_TGT = 16  , M_REF = 24  , M_ONE = 32, M_RING = 40   };
constexpr uint32_t EMPTY = 0xc200u;
constexpr float QS = 0.08838834764831845f * 1.4426950408889634f;

DEVI uint32_t acc_slot(uint32_t s) { return (s & 1) * 128 + (s & 2) * 16384; }
DEVI uint32_t acc_blk(uint32_t m, uint32_t l) { return (((l >> 1) << 2) | ((l & 1) << 1) | ((l & 1) ^ m)) * 4096; }
DEVI uint32_t acc_line(uint32_t i, uint32_t q, uint32_t l) { return acc_blk(q & 1, l) + (q >> 1) * 256 + (i < 4 ? i * 1024 : i * 1024 - 1536); }
DEVI uint32_t acc_stamp(uint32_t m, uint32_t n) { return acc_blk(m, n >> 5) + 512 + (n & 31) * 4; }

#define LOAD_TRANSIENT(LA) { _Pragma("unroll") for (int i_ = 0; i_ < NTR; i_++) ldsm4t(w[i_ & 1][i_ >> 1], (LA) + (i_ & 1) * 4096 + (i_ >> 1) * 2048); }
#define MMAW(D, T, K, B0, B1) mma16(D, w[T][K][0], w[T][K][1], w[T][K][2], w[T][K][3], B0, B1)

DEVI void proj_loop(uint32_t (&w)[2][18][4], unsigned char* smem, const uint32_t sb, const uint32_t c, const int wg, const int q, const uint32_t lane0) {
    const uint32_t bar = sb + R_BAR;
    const int p = q ^ (2 * wg);
    const bool c2 = c == 2, both = !c2 && p < 2, aq = c2 ? p < 2 : p != 2;
    const uint32_t lp = pin(sb + lane0 * 16 + p * 1024), ma = pin(sb + lane0 * 16 + wg * 1024);
    {
        const uint32_t l16 = sb + lane0 * 16;
        const int ia = c2 ? p & 1 : min(p, 2), vt = c2 ? 4 + p : 2 * c + p - 2;
        const uint32_t dtok = l16 + (wg ? (aq ? R_K - ((c2 ? 2 : 3) - ia) * 1024 : R_K + ia * 1536) : (both ? R_K + p * 1536 : R_V + vt * 1024));
        const uint32_t la = sb + R_STAGE + 7 * 16384 + wg * 8192 + (((lane0 >> 4) << 3) + (lane0 & 7)) * 128 + (((2 * q + ((lane0 >> 3) & 1)) ^ (lane0 & 7)) << 4);
        const bool lo = lane0 < 16, mq = aq && lo, mv = !both && !lo;
        const uint32_t dmem = sb + (mq ? R_QM + ia * 512 + (lane0 & 8) * 32 + wg * 128 : (mv ? R_PV + p * 1024 : R_K + ia * 1536 + 1024) + wg * 256 + (lane0 & 8) * 16) + (lane0 & 7) * 16;
        stsm4(lp + R_T4 + wg * 512, dtok, la, dmem, dmem + (mq || mv ? 0 : PAR));
        const uint32_t p0 = mapa(sb, c2 ? 0 : c + 1), p1 = mapa(sb, c == 0 ? 2 : c - 1), d = R_VM + vt * 256 + lane0 * 4;
        sts128(lp + R_PV + 512, p0 + d, p0 + R_BAR + BSC, p1 + d, p1 + R_BAR + BSC);
        __syncwarp();
        mbar_wait(bar + BX0, 0);
    }
#define PUBLISH(S) { asm volatile("cp.async.bulk.wait_group 0;" ::: "memory"); stg_rlx(&g_qflag[S][blockIdx.x / 3][c * 8], lds32(sb + R_MISC + M_RING + ((S) & 1) * 4)); }
#pragma unroll 1
    for (int s = 0; s < NSEG; s++) {
        const int xi = s - 3 * ((s * 43) >> 7);
        {
            float d[16];
#define TOKEN(WG, T, I0, I1, ZERO)                                                                                          \
    {                                                                                                                       \
    const uint32_t xd = fresh(desc_lo(sb + xi * 36864)), ad = fresh(desc_lo(sb + R_STAGE + 7 * 16384));                     \
    wg_fence();                                                                                                             \
    _Pragma("unroll") for (int i = I0; i < I1; i++) {                                                                       \
        const int j = i < 10 ? i + 2 : (i < 12 ? i - 10 : i), g = 18 * WG + j;                                              \
        const uint64_t bd = desc_of(xd + (g >> 2) * 256 + (g & 3) * 2);                                                     \
        if (2 * j + (T) < NTR) wgmma32_ss<1>(d, desc_of(ad + ((WG * 8192 + (T) * 4096 + j * 2048) >> 4)), bd);                          \
        else if (i == 0 && ZERO) wgmma32<0>(d, w[T][j], bd);                                                                \
        else wgmma32<1>(d, w[T][j], bd);                                                                                    \
    }                                                                                                                       \
    wg_commit();                                                                                                            \
    }
#define HANDOVER(WG)                                                                                                        \
    {                                                                                                                       \
        const uint32_t xa = lp + R_PX + WG * 4096;                                                                          \
        sts128(xa, pack2(d[0], d[1]), pack2(d[2], d[3]), pack2(d[4], d[5]), pack2(d[6], d[7]));                             \
        sts128(xa + 512, pack2(d[8], d[9]), pack2(d[10], d[11]), pack2(d[12], d[13]), pack2(d[14], d[15]));                 \
    }
            if (wg == 0) {
                bar_sync(NB_G1, 256);
                TOKEN(0, 0, 0, 18, 1)
                const uint32_t la = tab1(lp + R_T4 + 128);
                wg_wait0();
                EV(3);
                if (q == 1 && s > 0) {
                    const uint2 tt = tab2(lp + R_T2 - 1024);
                    const uint32_t tag = s << 22;
                    const char* const sp = mkptr(tt.x + acc_slot(s - 1), tt.y);
                    uint4 v = ldg_rlx4(sp);
                    bar_sync(NB_E0, 256);
                    HANDOVER(0)
                    bar_arrive(NB_GO, 384);
                    LOAD_TRANSIENT(la)
                    const uint2 tr = lds64(sb + R_MISC + M_REF);
                    int n = 0;
                    while (__any_sync(0xffffffffu, (diff2(v.x, v.y, tag) | diff2(v.z, v.w, tag)) >> 22)) {
                        v = ldg_rlx4(sp);
                        if (++n > (1 << 22)) TRAP(1002);
                    }
                    const int m = __reduce_max_sync(0xffffffffu, max(max((int)((v.x - tr.y) << 10), (int)((v.y - tr.y) << 10)), max((int)((v.z - tr.y) << 10), (int)((v.w - tr.y) << 10)))) >> 10;
                    sts64(sb + R_MISC + M_TGT, tr.x + min(m, DMAX) + (CT - 65), s);
                    EV(0);
                    if (EVX(0)) EVV(11, m);
                } else {
                    bar_sync(NB_E0, 256);
                    HANDOVER(0)
                    bar_arrive(NB_GO, 384);
                    LOAD_TRANSIENT(la)
                }
                bar_sync(NB_F0, 256);
                TOKEN(0, 1, 0, F1T, 1)
                bar_arrive(NB_F1, 256);
                TOKEN(0, 1, F1T, 18, 0)
                const uint32_t dtok = tab1(lp + R_T4) + (s & 1) * PAR;
                bar_sync(NB_H1, 256);
                const uint4 oa = lds128(lp + R_PX + 4096);
                wg_wait0();
                const uint32_t u0 = pack2(d[0] + bflo(oa.x), d[1] + bfhi(oa.x)), u1 = pack2(d[2] + bflo(oa.y), d[3] + bfhi(oa.y));
                const uint4 ob = lds128(lp + R_PX + 4608);
                stsm4(dtok, u0, u1, pack2(d[4] + bflo(oa.z), d[5] + bfhi(oa.z)), pack2(d[6] + bflo(oa.w), d[7] + bfhi(oa.w)));
                stsm4(dtok + 512, pack2(d[8] + bflo(ob.x), d[9] + bfhi(ob.x)), pack2(d[10] + bflo(ob.y), d[11] + bfhi(ob.y)),
                      pack2(d[12] + bflo(ob.z), d[13] + bfhi(ob.z)), pack2(d[14] + bflo(ob.w), d[15] + bfhi(ob.w)));
                bar_arrive(NB_TOK, 384);
            } else {
                const uint2 tw = tab2(lp + R_T4 + 512);
                bar_sync(NB_GO, 384);
                TOKEN(1, 1, 0, F0T, 1)
                bar_arrive(NB_F0, 256);
                TOKEN(1, 1, F0T, 18, 0)
                const uint4 oa = lds128(lp + R_PX), ob = lds128(lp + R_PX + 512);
                wg_wait0();
                HANDOVER(1)
                bar_arrive(NB_H1, 256);
                {
                    const uint32_t ox[8] = {oa.x, oa.y, oa.z, oa.w, ob.x, ob.y, ob.z, ob.w};
#pragma unroll
                    for (int j = 0; j < 8; j++) { d[2 * j] = bflo(ox[j]); d[2 * j + 1] = bfhi(ox[j]); }
                }
                LOAD_TRANSIENT(tw.y)
                bar_sync(NB_F1, 256);
                TOKEN(1, 0, 0, 18, 0)
                if (q == 3 && s > 0) PUBLISH(s - 1)
                const float qs = aq ? QS : 1.f;
                const uint32_t dtok = tw.x + (s & 1) * PAR;
                wg_wait0();
                EV(13);
#pragma unroll
                for (int hf = 0; hf < 2; hf++) {
                    const float* e = d + 8 * hf;
                    stsm4(dtok + hf * 512, pack2(e[0] * qs, e[1] * qs), pack2(e[2] * qs, e[3] * qs), pack2(e[4] * qs, e[5] * qs), pack2(e[6] * qs, e[7] * qs));
                }
                EV(12);
                bar_arrive(NB_TOK, 384);
            }
#undef TOKEN
#undef HANDOVER
        }
        uint4 b[12];
        float a[4][4];
        int pass = 0;
      redo:
        mbar_wait(bar + BME, s & 1);
#pragma unroll
        for (int j = 0; j < 4; j++) a[0][j] = a[1][j] = a[2][j] = a[3][j] = 0.f;
#pragma unroll
        for (int i = 0; i < 4; i++) b[i] = ldm128(ma + R_MEM + (i >> 1) * 2048 + (i & 1) * 512);
#define BK0(k) ((k) % 3 == 2 ? b[(k) / 3 * 2].z : b[(k) / 3 * 2 + (k) % 3].x)
#define BK1(k) ((k) % 3 == 2 ? b[(k) / 3 * 2].w : b[(k) / 3 * 2 + (k) % 3].y)
#define KS(T, k) MMAW(a[2 * (T) + ((k) & 1)], T, k, BK0(k), BK1(k));
#define JOIN(g) { chk = or3(chk, b[2 * (g)].w, b[2 * (g) + 1].w); b[2 * (g)].w = b[2 * (g) + 1].z | chk; }
        uint32_t chk = 0;
#pragma unroll
        for (int k = 0; k < LW; k++) { if (k % 3 == 2) JOIN(k / 3) KS(0, k) KS(1, k) }
#pragma unroll
        for (int i = 4; i < 12; i++) b[i] = ldm128(ma + R_MEM + (i >> 1) * 2048 + (i & 1) * 512);
        const uint32_t dmem = tab1(lp + fresh(wg * 512 + (s & 1) * 128) + R_T4 + 256);
#pragma unroll
        for (int k = LW; k < 18; k++) { if (k % 3 == 2) JOIN(k / 3) KS(0, k) KS(1, k) }
        float r[4];
        {
            const float s0 = aq ? QS : 1.f;
#pragma unroll
            for (int j = 0; j < 4; j++) r[j] = a[3][j] + a[2][j];
            stsm4(dmem, pack2(fmaf(a[1][0], s0, a[0][0] * s0), fmaf(a[1][1], s0, a[0][1] * s0)), pack2(fmaf(a[1][2], s0, a[0][2] * s0), fmaf(a[1][3], s0, a[0][3] * s0)),
                  pack2(r[0], r[1]), pack2(r[2], r[3]));
            const uint32_t bad = __any_sync(0xffffffffu, chk);
            asm volatile("{.reg .pred p; setp.eq.u32 p, %0, 0; @p bar.arrive %1, 384;}" :: "r"(bad | wg), "n"((int)NB_K) : "memory");
            asm volatile("{.reg .pred p; setp.eq.u32 p, %0, 0; @p bar.sync %1, 384;}" :: "r"(bad | (wg ^ 1)), "n"((int)NB_K) : "memory");
            if (__builtin_expect(bad, 0)) goto repair;
        }
#undef JOIN
#undef KS
#undef BK0
#undef BK1
        if (wg == 0) { EV(1); continue; }
        if (!both) {
            const uint2 o = tab2(lp + R_PV);
            const uint4 tv = lds128(lp + R_PV + 512);
            const uint32_t lo = pack2(r[0] + bflo(o.x), r[1] + bfhi(o.x)), hi = pack2(r[2] + bflo(o.y), r[3] + bfhi(o.y));
            const uint32_t v0 = tv.x + (s & 1) * PAR, v1 = tv.z + (s & 1) * PAR, v2 = v0 - tv.y + bar + BSC;
            sta32(v0, lo, tv.y); sta32(v0 + 128, hi, tv.y);
            sta32(v1, lo, tv.w); sta32(v1 + 128, hi, tv.w);
            sts32(v2, lo); sts32(v2 + 128, hi);
            EV(2);
        }
        {
            if (q != 3) bar_arrive(NB_W1, 256);
            if (q == 3) {
                bar_sync(NB_W1, 256);
                unsigned char* const dst = g_qkv + (size_t)((__shfl_sync(0xffffffffu, lds32(sb + R_MISC + M_RING + (s & 1) * 4), 0) & 63) * 32 + blockIdx.x / 3) * 30720;
                const uint32_t so = sb + (s & 1) * PAR;
                fence_smem_async();
                asm volatile("{.reg .pred p; elect.sync _|p, 0xffffffff;\n"
                             "@p cp.async.bulk.global.shared::cta.bulk_group [%0], [%1], %2;\n"
                             "@p cp.async.bulk.global.shared::cta.bulk_group [%3], [%4], %5;\n"
                             "@p cp.async.bulk.global.shared::cta.bulk_group [%6], [%7], %8;\n"
                             "@p cp.async.bulk.commit_group;}"
                             :: "l"(dst + c * 7680), "r"(so + R_K - (c2 ? 2048 : 3072)), "r"(c2 ? 5120 : 7680),
                                "l"(dst + 20480 + c * 2048), "r"(so + R_V + c * 2048), "r"(c2 ? 4096 : 2048),
                                "l"(dst + 28672 + c * 512), "r"(so + R_VM + c * 512), "r"(c2 ? 1024 : 512) : "memory");
            } else if (q == 2) {
                const uint4 tz = lds128(lp + R_T0 + 1536);
                uint32_t z;
                asm volatile("atom.relaxed.gpu.global.exch.b32 %0, [%1], %2;" : "=r"(z) : "l"(mkptr(tz.x + acc_slot(s + 2), tz.y)), "r"(tz.w) : "memory");
                const uint32_t epoch = lds32(sb + R_MISC + M_EPOCH), done = ldg_rlx(&g_oflag[max(s + 1 - QR, 0)][blockIdx.x / 3][0]);
                sts32(sb + R_MISC + M_RING + 4 - (s & 1) * 4, epoch * 64 + ((s + 1) & (done == epoch ? QR - 1 : 63)));
                sts32(sb + R_MISC + M_SINK, z);
            }
        }
        continue;
      repair:
        {
            if (++pass > (1 << 20)) TRAP(1000);
#pragma unroll 1
            for (int i = 0; i < 2; i++) {
                const uint2 tb = tab2(ma + fresh(i * 512) + R_T1 + 256 + ((s - 1) & 3) * 2048);
                const uint32_t md = ma + (ma & 256) + R_MEM + i * 2048;
                const char* const ga = mkptr(tb.x, tb.y);
                cp16(md, ga); cp16(md + 256, ga + 1024); cp16(md + 4096, ga + 2048); cp16(md + 4352, ga + 3072);
                cp16(md + 8192, ga + 2560); cp16(md + 8448, ga + 3584);
            }
            asm volatile("cp.async.wait_all;" ::: "memory");
            __syncwarp();
            const uint32_t la = tab1(lp + fresh(wg * 512) + R_T4 + 128);
            LOAD_TRANSIENT(la)
            goto redo;
        }
    }
    if (wg == 1 && q == 3) PUBLISH(NSEG - 1)
#undef PUBLISH
}

DEVI void attn_loop(const uint32_t (&wo)[3][8][4], const CUtensorMap* xmap, const CUtensorMap* amap, unsigned char* smem, const uint32_t sb, const uint32_t c, const int q,
                    const uint32_t lane0, const uint32_t side, const uint32_t jw) {
    const uint32_t bar = sb + R_BAR;
    const bool c2 = c == 2;
    const uint32_t l16 = pin(sb + lane0 * 16);
    {
        const uint32_t lane = lane0, n = blockIdx.x, gl = (uint32_t)(uint64_t)(void*)g_acc, gh = (uint32_t)((uint64_t)(void*)g_acc >> 32);
        const uint32_t p0 = mapa(sb, c2 ? 0 : c + 1), p1 = mapa(sb, c == 0 ? 2 : c - 1), so = R_SC + lane * 4;
        if (q < 3) sts128(l16 + R_T0 + q * 512, p0 + so + (q == 2 ? 1536 : 512 + q * 256), p0 + R_BAR + BSC, p1 + so + (q == 2 ? 1664 : 1024 + q * 256), p1 + R_BAR + BSC);
        else {
            sts128(l16 + R_T0 + q * 512, gl + acc_line(n >> 4, (n >> 2) & 3, n & 3) + lane * 4, gh, gl + acc_stamp(lane & 1, n), (lane & 3) == 3 ? EMPTY : 0);
            stsm2(l16 + R_T2, gl + acc_stamp(side, (lane < 24 ? lane : 0) * 4), gh);
        }
        for (int i = 0; i < 4; i++)
            stsm4(l16 + R_T1 + i * 2048 + q * 512, gl + acc_slot(i) + acc_line(2 * jw, q, (lane >> 4) * 2 + ((lane >> 1) & 1)) + ((lane & 1) * 4 + ((lane >> 2) & 3)) * 16, gh,
                   gl + acc_slot(i) + acc_line(0, q, lane >> 3) + (lane & 7) * 16, gh);
        __syncwarp();
    }
    const uint32_t ls = pin(sb + (lane0 & 3) * 32);
#define UA(x) (l16 + fresh(x))
#pragma unroll 1
    for (int s = 0; s < NSEG - 1; s++) {
        const uint32_t par = (s & 1) * PAR;
        bar_sync(NB_TOK, 384);
#define SCORES()                                                                                                   \
    float x[2][3][4];                                                                                              \
    _Pragma("unroll") for (int t = 0; t < 3; t++) {                                                                \
        _Pragma("unroll") for (int j = 0; j < 4; j++) x[0][t][j] = x[1][t][j] = 0.f;                               \
        mma16(x[0][t], qf[t][0], qf[t][1], qf[t][2], qf[t][3], kf[t][0], kf[t][1]);                                \
        mma16(x[1][t], qf[t][0], qf[t][1], qf[t][2], qf[t][3], kf[t][2], kf[t][3]);                                \
    }                                                                                                              \
    bar_arrive(NB_G1 + (__float_as_uint(x[0][G1T][0]) & (l16 >> 31)), 256);                                         \
    const uint4 ta = lds128(UA(q * 512) + R_T0);                                                                            \
    float y[4];                                                                                                    \
    _Pragma("unroll") for (int j = 0; j < 4; j++)                                                                  \
        y[j] = ((x[j >> 1][0][j & 1] + x[j >> 1][0][2 + (j & 1)]) + (x[j >> 1][1][j & 1] + x[j >> 1][1][2 + (j & 1)])) + (x[j >> 1][2][j & 1] + x[j >> 1][2][2 + (j & 1)]);
        if (q < 2) {
            uint32_t qf[3][4], kf[3][4];
#pragma unroll
            for (int t = 0; t < 3; t++) ldsm4t(kf[t], UA(q * 512 + par) + R_K + t * 1536);
            bar_sync(NB_K, 384);
#pragma unroll
            for (int t = 0; t < 3; t++) ldsm4t(qf[t], l16 + R_QM + t * 512);
            SCORES()
            const uint32_t u0 = pack2(y[0], y[1]), u1 = pack2(y[2], y[3]);
            sta32(ta.x, u0, ta.y); sta32(ta.z, u0, ta.w);
            sta32(ta.x + 128, u1, ta.y); sta32(ta.z + 128, u1, ta.w);
            stsm2(UA(q * 256) + R_SC, u0, u1);
        } else if (q == 2) {
            if (s > 0 && s + 2 < NSEG) {
                const int xi = s - 1 - 3 * (((s - 1) * 43) >> 7);
                mbar_wait(bar + BME, s & 1);
                spin_until(clk() + XD);
                asm volatile("{.reg .pred p; elect.sync _|p, 0xffffffff;\n"
                             "@p mbarrier.arrive.expect_tx.shared::cta.b64 _, [%2], 36864;\n"
                             "@p cp.async.bulk.tensor.3d.shared::cluster.global.mbarrier::complete_tx::bytes.multicast::cluster [%0], [%1, {%3, %4, %5}], [%2], %6;}"
                             :: "r"(sb + xi * 36864 + c * 12288), "l"(xmap), "r"(bar + BX0 + xi * 8), "r"(0), "r"((s + 2) * 32), "r"(c * 3), "h"((uint16_t)7) : "memory");
            }
            uint32_t qf[3][4], kf[3][4];
            bar_sync(NB_K, 384);
#pragma unroll
            for (int t = 0; t < 3; t++) { ldsm4t(qf[t], l16 + R_QM + t * 512); ldsm4t(kf[t], UA(q * 512 + par) + R_K + t * 1536); }
            SCORES()
            const uint32_t u0 = pack2(y[0] + y[2], y[1] + y[3]);
            sta32(ta.x, u0, ta.y);
            sta32(ta.z, u0, ta.w);
            EV(4);
            stsm2(l16 + R_SC + 1792, u0, u0);
        } else {
            const uint4 ta = lds128(UA(q * 512) + R_T0);
            {
                const uint32_t vt = R_V + par + c * 2048, p0 = mapa(sb, c2 ? 0 : c + 1), p1 = mapa(sb, c == 0 ? 2 : c - 1);
                fence_smem_async();
                bulk_s2c_warp(p0 + vt, sb + vt, c2 ? 4096 : 2048, p0 + R_BAR + BVX + (s & 1) * 8);
                bulk_s2c_warp(p1 + vt, sb + vt, c2 ? 4096 : 2048, p1 + R_BAR + BVX + (s & 1) * 8);
            }
            {
                const int s3 = ((s + 1) * 43) >> 7;
                mbar_wait(bar + BX0 + (s + 1 - 3 * s3) * 8, s3 & 1);
                bar_arrive(NB_G1, 256);
            }
            sts32(sb + R_MISC + M_REF + 4, clock_offset());
            bar_sync(NB_K, 384);
            const uint32_t off = lds32(sb + R_MISC + M_REF + 4);
            const uint32_t t = off == 0x9e3779b9u ? 0u : clk();
            sts64(sb + R_MISC + M_REF, t, t + off);
            stg_rlx((uint32_t*)mkptr(ta.z + acc_slot(s), ta.y), ((t + off) & 0x3fffffu) | ((s + 1) << 22));
            mbar_wait(bar + BVX + (s & 1) * 8, (s >> 1) & 1);
        }
#undef SCORES
        bar_sync(NB_W1, 256);
        uint32_t vf[4][4];
        const uint32_t vo = par + q * 2048;
        float o0[4], o1[4], sum;
        uint2 tb;
        {
            uint32_t aw[5], bw[5], cw[5];
            ldsm4(aw, l16 + R_SC); aw[4] = tab1(l16 + R_SC + 1792);
            sts32(sb + R_MISC + M_SINK, aw[0] | aw[4]);
            mbar_wait(bar + BSC, s & 1);
            ldsm4(bw, l16 + R_SC + 512); ldsm4(cw, l16 + R_SC + 1024);
            { const uint2 t = tab2(l16 + R_SC + 1536); bw[4] = t.x; cw[4] = t.y; }
            EV(5);
            float x[10];
#pragma unroll
            for (int i = 0; i < 5; i++) { x[2 * i] = (bflo(aw[i]) + bflo(bw[i])) + bflo(cw[i]); x[2 * i + 1] = (bfhi(aw[i]) + bfhi(bw[i])) + bfhi(cw[i]); }
            float mx = fmaxf(fmaxf(fmaxf(fmaxf(x[0], x[1]), fmaxf(x[2], x[3])), fmaxf(fmaxf(x[4], x[5]), fmaxf(x[6], x[7]))), fmaxf(x[8], x[9]));
            const float m1 = __shfl_xor_sync(0xffffffffu, mx, 1), m2 = __shfl_xor_sync(0xffffffffu, mx, 2), m3 = __shfl_xor_sync(0xffffffffu, mx, 3);
            uint32_t vm[4];
            const uint32_t lv = l16 | (__float_as_uint(mx) & (l16 >> 31));
            ldsm4(vf[0], lv + fresh(vo) + R_V); ldsm4(vf[2], lv + fresh(vo) + R_V + 1024);
            ldsm4(vf[3], lv + fresh(vo) + R_V + 1536); ldsm4(vm, lv + fresh(q * 512 + par) + R_VM);
            tb = tab2(lv + fresh(q * 512 + (s & 3) * 2048) + R_T1);
            bar_arrive(NB_E0, 256);
            ldsm4(vf[1], lv + fresh(vo) + R_V + 512);
            mx = fmaxf(fmaxf(mx, m1), fmaxf(m2, m3));
            uint32_t pb[5];
            sum = 0.f;
#pragma unroll
            for (int i = 0; i < 5; i++) {
                const float e0 = ex2(x[2 * i] - mx), e1 = ex2(x[2 * i + 1] - mx);
                pb[i] = pack2(e0, e1);
                sum += e0 + e1;
            }
#pragma unroll
            for (int j = 0; j < 4; j++) o0[j] = o1[j] = 0.f;
            mma16(o0, vf[0][0], vf[0][1], vf[0][2], vf[0][3], pb[0], pb[1]);
            mma16(o1, vf[2][0], vf[2][1], vf[2][2], vf[2][3], pb[0], pb[1]);
            mma16(o0, vf[1][0], vf[1][1], vf[1][2], vf[1][3], pb[2], pb[3]);
            mma16(o1, vf[3][0], vf[3][1], vf[3][2], vf[3][3], pb[2], pb[3]);
            mma8(o0, vm[0], vm[1], pb[4]);
            mma8(o1, vm[2], vm[3], pb[4]);
        }
        asm volatile("stmatrix.sync.aligned.m8n8.x1.shared.b16 [%0], {%1};" :: "r"(l16 + R_Z), "r"(__float_as_uint(sum)) : "memory");
        const float4 s0 = lds128f(ls + R_Z), s1 = lds128f(ls + R_Z + 16);
        stsm4(UA(q * 512) + R_O8, pack2(o0[0], o0[1]), pack2(o0[2], o0[3]), pack2(o1[0], o1[1]), pack2(o1[2], o1[3]));
        EV(6);
        bar_sync(NB_W2, 128);
        uint32_t of[4][4];
#pragma unroll
        for (int i = 0; i < 4; i++) ldsm4t(of[i], l16 + R_O8 + i * 512);
        const float f0 = rcp_fast((s0.x + s0.y) + (s0.z + s0.w)), f1 = rcp_fast((s1.x + s1.y) + (s1.z + s1.w));
        float acc[3][2][4];
        uint32_t tie;
#pragma unroll
        for (int m = 0; m < 3; m++)
#pragma unroll
            for (int j = 0; j < 4; j++) acc[m][0][j] = acc[m][1][j] = 0.f;
#pragma unroll
        for (int i = 0; i < 4; i++)
#pragma unroll
            for (int m = 0; m < 3; m++)
#pragma unroll
                for (int e = 0; e < 2; e++) {
                    const int p = i ? 1 + (i + m + 2) % 3 : 0, kk = 2 * p + e;
                    if (i == 3 && m == 0 && e == 0)
                        tie = or3(or3(__float_as_uint(acc[0][0][0]), __float_as_uint(acc[0][1][0]), __float_as_uint(acc[1][0][0])),
                                  or3(__float_as_uint(acc[1][1][0]), __float_as_uint(acc[2][0][0]), __float_as_uint(acc[2][1][0])), __float_as_uint(f0) | __float_as_uint(f1));
                    mma16(acc[m][e], wo[m][kk][0], wo[m][kk][1], wo[m][kk][2], wo[m][kk][3], of[p][e * 2], of[p][e * 2 + 1]);
                }
        char* const gw = mkptr(tb.x, tb.y);
        bar_arrive(NB_GO + (tie & (l16 >> 31)), 384);
        const uint32_t one = lds32(sb + R_MISC + M_ONE);
        uint32_t wa[3], wb[3];
#pragma unroll
        for (int m = 0; m < 3; m++) {
            wa[m] = pack2(fmaf(acc[m][1][0], f0, acc[m][0][0] * f0), fmaf(acc[m][1][2], f0, acc[m][0][2] * f0));
            wb[m] = pack2(fmaf(acc[m][1][1], f1, acc[m][0][1] * f1), fmaf(acc[m][1][3], f1, acc[m][0][3] * f1));
        }
        red_b8(gw, wa[0], wa[1], wa[2], one); red_b8(gw + 1024, wb[0], wb[1], wb[2], one);
        const uint32_t t0 = clk();
        if (EVX(0)) EVV(7, t0);
        if (q < 2) {
            uint2 tg = lds64(sb + R_MISC + M_TGT);
            for (int n = 0; tg.y != s + 1; tg = lds64(sb + R_MISC + M_TGT)) if (++n > (1 << 26)) TRAP(1003);
            fine_until(t0 + max((int)(tg.x - t0), DMIN) - (q != side ? FE : 0) + (c ? DL : 0));
            asm volatile("{.reg .pred p; elect.sync _|p, 0xffffffff;\n"
                         "@p cp.async.bulk.tensor.5d.shared::cluster.global.mbarrier::complete_tx::bytes.multicast::cluster [%0], [%1, {%3, %4, %4, %4, %5}], [%2], %6;}"
                         :: "r"(sb + R_MEM + c * 4096 + q * 2048), "l"(amap + q), "r"(bar + (DL && c ? BML : BME)), "r"((s & 1) * 64), "r"(0), "r"((s & 2) * 64 + (c ? 6 + 2 * c : 0)), "h"((uint16_t)7) : "memory");
            EV(8);
        } else if (q == 2) {
            if (l16 == sb) {
                mbar_expect(bar + BME, DL ? 4096 : 12288);
                if (DL) mbar_expect(bar + BML, 8192);
                mbar_expect(bar + BSC, (c2 ? 1024 : 1536) + (s < NSEG - 2 ? 1280 : 0));
                mbar_expect(bar + BVX + 8 - (s & 1) * 8, c2 ? 4096 : 6144);
            }
        }
        EV(10);
    }
    bar_sync(NB_TOK, 384);
    bar_arrive(NB_K, 384);
    bar_arrive(NB_W1, 256);
    mbar_wait(bar + BSC, 1);
}

struct Maps { CUtensorMap x, acc[2]; };

__global__ void __launch_bounds__(384, 1)
rk_kernel(const __grid_constant__ Maps maps, const __nv_bfloat16* __restrict__ xraw, const __nv_bfloat16* __restrict__ mem0, const __nv_bfloat16* __restrict__ Wq,
          const __nv_bfloat16* __restrict__ Wk, const __nv_bfloat16* __restrict__ Wv, const __nv_bfloat16* __restrict__ Wo) {
    extern __shared__ __align__(1024) unsigned char smem[];
    const uint32_t sb = smem_u32(smem);
    const int tid = threadIdx.x;
    const int warp = __shfl_sync(0xffffffffu, tid >> 5, 0), q = warp & 3;
    const int h = blockIdx.x / 3;
    const uint32_t c = blockIdx.x - 3 * h;
    const uint32_t bar = sb + R_BAR;
    asm volatile("griddepcontrol.launch_dependents;");
    GT(0, 0);

    if (warp < 8) {
        asm volatile("setmaxnreg.inc.sync.aligned.u32 %0;" :: "n"(RP));
        const int wg = warp >> 2;
        const uint32_t lane = pin(tid & 31);
        uint32_t w[2][18][4];
        const uint32_t st = sb + R_STAGE + wg * 8192;
        const uint32_t la = st + (((lane >> 4) << 3) + (lane & 7)) * 128 + (((2 * q + ((lane >> 3) & 1)) ^ (lane & 7)) << 4);
        {
            const int t = tid & 127;
            const int r0 = t >> 3, ch = t & 7, p = (ch >> 1) ^ (2 * wg);
            const __nv_bfloat16* ta = c == 2 ? (p < 2 ? Wq : Wk) + 96 + (p & 1) * 16 : (p == 2 ? Wk : Wq) + c * 48 + min(p, 2) * 16;
            const __nv_bfloat16* tb = c == 2 ? Wv + 64 + p * 16 : (p >= 2 ? Wv + c * 32 + (p - 2) * 16 : Wk + c * 48 + p * 16);
            const size_t so = (size_t)(wg * 288 + r0) * HD + h * 128 + (ch & 1) * 8;
            const __nv_bfloat16* sp0 = ta + so;
            const __nv_bfloat16* sp1 = tb + so;
            const uint32_t dp = st + r0 * 128 + ((ch ^ (r0 & 7)) << 4);
#define ISSUE(KC, SLOT)                                                                                         \
    cp16(dp + (SLOT) * 16384, sp0 + (size_t)((KC) * 32) * HD); cp16(dp + (SLOT) * 16384 + 2048, sp0 + (size_t)((KC) * 32 + 16) * HD);               \
    cp16(dp + (SLOT) * 16384 + 4096, sp1 + (size_t)((KC) * 32) * HD); cp16(dp + (SLOT) * 16384 + 6144, sp1 + (size_t)((KC) * 32 + 16) * HD);        \
    cp_commit();
#pragma unroll
            for (int kc = 1; kc < 8; kc++) { ISSUE(kc, kc - 1) }
            ISSUE(0, 7)
            cluster_arrive_rlx(); cluster_wait();
#define LOADCHUNK(KC, SLOT, NWAIT)                                                   \
    cp_wait<NWAIT>(); bar_sync(NB_L0 + wg, 128);                                      \
    _Pragma("unroll") for (int i = 0; i < 4; i++) ldsm4t(w[i >> 1][(KC) * 2 + (i & 1)], la + (SLOT) * 16384 + i * 2048);
            LOADCHUNK(1, 0, 7)
            bar_sync(NB_L0 + wg, 128);
            ISSUE(8, 0)
            LOADCHUNK(2, 1, 7) LOADCHUNK(3, 2, 6) LOADCHUNK(4, 3, 5) LOADCHUNK(5, 4, 4) LOADCHUNK(6, 5, 3) LOADCHUNK(7, 6, 2) LOADCHUNK(0, 7, 1) LOADCHUNK(8, 0, 0)
#undef LOADCHUNK
#undef ISSUE
            fence_smem_async();
        }
        bar_sync(0, 384);
        cluster_arrive_rlx(); cluster_wait();

        GT(0, 1);
        if (c == 2) sts128(sb + (q == 3 ? R_QM + 1024 : R_K + 3072 + q * 512 + wg * PAR) + lane * 16, 0, 0, 0, 0);
        proj_loop(w, smem, sb, c, wg, q, lane);
    } else {
        asm volatile("setmaxnreg.dec.sync.aligned.u32 %0;" :: "n"(504 - 2 * RP));
        const uint32_t lane0 = pin(tid & 31);
        const uint32_t lane = lane0, n = blockIdx.x;
        volatile uint32_t* const misc = (volatile uint32_t*)(smem + R_MISC);
        const unsigned epoch = g_epoch[36 + n] + 1;
        uint32_t* const pa = (uint32_t*)((char*)g_acc + acc_blk(q & 1, n & 3) + 1536 + ((n >> 2) & 3) * 128 + ((n >> 4) & 1) * 32768 + (n >> 5) * 32);
        {
            const int t = tid - 256;
            if (t == 0) {
                mbar_init(bar + BX0, 1); mbar_init(bar + BX0 + 8, 1); mbar_init(bar + BX0 + 16, 1);
                mbar_init(bar + BSC, 1); mbar_init(bar + BME, 1); mbar_init(bar + BML, 1); mbar_arrive(bar + BME); mbar_arrive(bar + BML);
                mbar_init(bar + BVX, 1); mbar_init(bar + BVX + 8, 1);
                mbar_expect(bar + BSC, c == 2 ? 2304 : 2816); mbar_expect(bar + BVX, c == 2 ? 4096 : 6144);
                misc[M_TGT / 4 + 1] = 0; misc[M_ONE / 4] = 0x3f80u;
                misc[M_EPOCH / 4] = epoch; misc[M_RING / 4] = epoch * 64; g_epoch[36 + n] = epoch;
                asm volatile("fence.mbarrier_init.release.cluster;" ::: "memory");
            }
            __syncwarp();
            cluster_arrive_rlx();
            uint32_t z;
            asm volatile("atom.relaxed.gpu.global.exch.b32 %0, [%1], %2;" : "=r"(z) : "l"((char*)g_acc + acc_slot(q) + acc_line(n >> 4, (n >> 2) & 3, n & 3) + lane * 4), "r"((lane & 3) == 3 ? EMPTY : 0) : "memory");
            if (lane < 2) stg_rlx((uint32_t*)((char*)g_acc + acc_slot(q) + acc_stamp(lane, n)), 0u);
            if (q < 2 && lane < 8) stg_rlx(pa + lane, 0u);
            uint32_t m0[3][6];
#pragma unroll
            for (int i = 0; i < 18; i++) m0[i / 6][i % 6] = __ldg((const uint32_t*)mem0 + (lane >> 2) * 288 + (q * 18 + i) * 4 + (lane & 3));
            const __nv_bfloat16* src = Wo + (size_t)h * 128 * DM;
#pragma unroll 4
            for (int i = 0; i < 24; i++) {
                const int idx = i * 128 + t, r = idx / 24, ch = idx - r * 24, qq = ch / 6, jq = (c + 3 - qq % 3) % 3;
                cp16(sb + R_WO + r * 384 + ((ch ^ ((r >> 1) & 3) * 2) << 4), src + r * DM + ((qq >> 1) * 36 + jq * 12 + (qq & 1) * 6 + ch - qq * 6) * 8);
            }
            cp_commit();
            cluster_wait();
            if (t == 0) {
                mbar_expect(bar + BX0, 36864);
                x_tma(sb + R_X0 + c * 12288, &maps.x, bar + BX0, 0, c * 3);
            }
            __syncwarp();
            {
                const uint32_t a = sb + R_MEM + (q & 1) * 6144 + (q >> 1) * 1024 + lane * 16;
#pragma unroll
                for (int i = 0; i < 6; i++) sts128(a + (i >> 1) * 2048 + (i & 1) * 512, m0[i >> 1][(i & 1) * 2], m0[i >> 1][(i & 1) * 2 + 1], m0[i >> 1][4 + (i & 1)], z & (lane >> 5));
            }
            asm volatile("fence.acq_rel.gpu;" ::: "memory");
            cp_wait<0>();
            bar_sync(NB_W2, 128);
            if (t == 0) stg_rlx(&g_pub[n], epoch);
            if (t == 32) asm volatile("cp.async.bulk.prefetch.L2.global [%0], 24576;" :: "l"((const char*)xraw + n * 24576) : "memory");
        }
        uint32_t wo[3][8][4];
        {
            const uint32_t g = lane >> 2, tq = lane & 3;
#pragma unroll
            for (int m = 0; m < 3; m++) {
                const uint32_t ch = 6 * q + (m < 2 ? (g >> 2) * 2 + m : 4 + (g >> 2));
                const uint32_t a = sb + R_WO + tq * 768 + ((ch ^ tq * 2) << 4) + (g & 3) * 4;
#pragma unroll
                for (int kk = 0; kk < 16; kk++) {
                    const uint32_t x = lds32(a + kk * 3072), y = lds32(a + kk * 3072 + 384);
                    wo[m][kk >> 1][(kk & 1) * 2] = __byte_perm(x, y, 0x5410);
                    wo[m][kk >> 1][(kk & 1) * 2 + 1] = __byte_perm(x, y, 0x7632);
                }
            }
        }
        bar_sync(0, 384);
        cluster_arrive_rlx(); cluster_wait();
        bar_arrive(NB_G1, 256);
        bar_arrive(NB_E0, 256);
        bar_arrive(NB_GO, 384);
        if (q >= 2 && lane == 0) {
            mbar_expect(bar + BX0 + (q - 1) * 8, 36864);
            x_tma(sb + (q - 1) * 36864 + c * 12288, &maps.x, bar + BX0 + (q - 1) * 8, (q - 1) * 32, c * 3);
        }
        __syncwarp();
        if (q < 2) { const uint32_t r = probe_rtt(pa); if (lane == 0) misc[M_PROBE / 4 + q] = r; }
        if (q == 3) {
            int it = 0;
            while (!__all_sync(0xffffffffu, ldg_rlx(&g_pub[lane]) == epoch && ldg_rlx(&g_pub[32 + lane]) == epoch && ldg_rlx(&g_pub[64 + lane]) == epoch))
                if (++it > (1 << 22)) TRAP(2000 + __LINE__);
        }
        bar_sync(NB_W2, 128);
        const uint32_t side = __shfl_sync(0xffffffffu, misc[M_PROBE / 4 + 1] < misc[M_PROBE / 4], 0);
        attn_loop(wo, &maps.x, maps.acc, smem, sb, c, q, lane0, side, (c + 3 - q % 3) % 3);
    }
    cluster_arrive_rlx(); cluster_wait();
    GT(0, 2);
}

constexpr int H_USTR = 32 * 144 + 16;
constexpr int H_U = 0;
constexpr int H_Z = H_U + 16 * H_USTR;
constexpr int H_W = 74752;
constexpr int H_WSTR = (2048 + 64) * 4;
constexpr int H_PAR = H_W + 8 * H_WSTR;
constexpr int H_KD = H_PAR + 8 * 2048;
constexpr int H_S4END = H_KD + 8 * 648 * 4;
constexpr int NST = 6;
constexpr int H_RING = H_W;
constexpr int H_QKV = 180224;
constexpr int H_AO = H_QKV + 30720;
constexpr int H_BAR = H_AO + 8192;
constexpr int H_SMEM = H_BAR + 512;
static_assert(H_Z + 256 <= H_W && H_S4END <= H_QKV && H_RING + NST * 16384 <= H_QKV && H_SMEM <= 232448 && H_RING % 1024 == 0, "smem");
enum { HB_FULL = 0  , HB_EMPTY = 64  , HB_QF = 256, HB_VF = 264, HB_QE = 272, HB_VE = 280, HB_OF = 288, HB_OE = 296 };
enum { HN_U = 1, HN_Y = 2, HN_P = 3  , HN_G = 5   };

DEVI int slot_channel(int i) { return ((i >> 1) & 3) * 4 + (i >> 3) * 2 + (i & 1); }
#define LOAD_U(W)                                                                                                                      \
    _Pragma("unroll 1") for (int i0 = 0; i0 < 32; i0 += 4) {                                                                            \
        uint2 v[4][2];                                                                                                                  \
        _Pragma("unroll") for (int i = 0; i < 8; i++)                                                                                   \
            v[i >> 1][i & 1] = __ldg((const uint2*)(u + (size_t)(((W) * 32 + i0) * 16 + i * 8 + g) * DM + d0 + tq * 4));                \
        _Pragma("unroll") for (int i = 0; i < 4; i++) {                                                                                 \
            const int t0 = ((W) * 32 + i0 + i) * 16;                                                                                    \
            asm volatile("stmatrix.sync.aligned.m8n8.x4.trans.shared.b16 [%0], {%1,%2,%3,%4};"                                          \
                         :: "r"(sb + H_U + (lane & 15) * H_USTR + (t0 >> 6) * 144 + (t0 & 63) * 2 + (lane >> 4) * 16),                  \
                            "r"(v[i][0].x), "r"(v[i][0].y), "r"(v[i][1].x), "r"(v[i][1].y) : "memory");                                 \
        }                                                                                                                               \
    }
DEVI uint64_t desc_plain(uint32_t saddr, uint32_t lbo, uint32_t sbo) { return ((uint64_t)(sbo >> 4) << 32) | ((uint64_t)(lbo >> 4) << 16) | (uint64_t)((saddr & 0x3FFFF) >> 4); }
template <int ACC> DEVI void wgmma48_tt(float* d, uint64_t adesc, uint64_t bdesc) {
    asm volatile("wgmma.mma_async.sync.aligned.m64n48k16.f32.bf16.bf16 "
                 "{%0,%1,%2,%3,%4,%5,%6,%7,%8,%9,%10,%11,%12,%13,%14,%15,%16,%17,%18,%19,%20,%21,%22,%23}, %24, %25, %26, 1, 1, 1, 1;"
                 : "+f"(d[0]), "+f"(d[1]), "+f"(d[2]), "+f"(d[3]), "+f"(d[4]), "+f"(d[5]), "+f"(d[6]), "+f"(d[7]),
                   "+f"(d[8]), "+f"(d[9]), "+f"(d[10]), "+f"(d[11]), "+f"(d[12]), "+f"(d[13]), "+f"(d[14]), "+f"(d[15]),
                   "+f"(d[16]), "+f"(d[17]), "+f"(d[18]), "+f"(d[19]), "+f"(d[20]), "+f"(d[21]), "+f"(d[22]), "+f"(d[23])
                 : "l"(adesc), "l"(bdesc), "n"(ACC));
}
template <int ACC> DEVI void wgmma64(float* d, const uint32_t* a, uint64_t desc) {
    asm volatile("wgmma.mma_async.sync.aligned.m64n64k16.f32.bf16.bf16 "
                 "{%0,%1,%2,%3,%4,%5,%6,%7,%8,%9,%10,%11,%12,%13,%14,%15,%16,%17,%18,%19,%20,%21,%22,%23,%24,%25,%26,%27,%28,%29,%30,%31}, {%32,%33,%34,%35}, %36, %37, 1, 1, 0;"
                 : "+f"(d[0]), "+f"(d[1]), "+f"(d[2]), "+f"(d[3]), "+f"(d[4]), "+f"(d[5]), "+f"(d[6]), "+f"(d[7]),
                   "+f"(d[8]), "+f"(d[9]), "+f"(d[10]), "+f"(d[11]), "+f"(d[12]), "+f"(d[13]), "+f"(d[14]), "+f"(d[15]),
                   "+f"(d[16]), "+f"(d[17]), "+f"(d[18]), "+f"(d[19]), "+f"(d[20]), "+f"(d[21]), "+f"(d[22]), "+f"(d[23]),
                   "+f"(d[24]), "+f"(d[25]), "+f"(d[26]), "+f"(d[27]), "+f"(d[28]), "+f"(d[29]), "+f"(d[30]), "+f"(d[31])
                 : "r"(a[0]), "r"(a[1]), "r"(a[2]), "r"(a[3]), "l"(desc), "n"(ACC));
}
DEVI uint2 ldg_rlx2(const void* p) { uint2 v; asm volatile("ld.relaxed.gpu.global.v2.u32 {%0,%1}, [%2];" : "=r"(v.x), "=r"(v.y) : "l"(p) : "memory"); return v; }
DEVI unsigned ldg_acq(const unsigned* p) { unsigned v; asm volatile("ld.acquire.gpu.global.u32 %0, [%1];" : "=r"(v) : "l"(p) : "memory"); return v; }
DEVI void csq(float& x, float& y) { const float a = fmaf(x, x, -y * y), b = 2.f * x * y; x = a; y = b; }
DEVI uint32_t tf(float x) { return __float_as_uint(x); }
constexpr float TFC = 1.f + 6.77e-4f;
DEVI void cexp_turns(float l2mag, float turns, float& x, float& y) {
    const float m = ex2(l2mag), a = (turns - rintf(turns)) * 6.283185307179586f;
    x = m * __cosf(a); y = m * __sinf(a);
}

__global__ void __launch_bounds__(512, 1)
hk_kernel(const __nv_bfloat16* __restrict__ Wo, const __nv_bfloat16* __restrict__ u,
          const __nv_bfloat16* __restrict__ logA, const __nv_bfloat16* __restrict__ Aim, const __nv_bfloat16* __restrict__ Cre,
          const __nv_bfloat16* __restrict__ Cim, const __nv_bfloat16* __restrict__ logdt, const __nv_bfloat16* __restrict__ Dsk,
          __nv_bfloat16* __restrict__ out) {
    extern __shared__ __align__(1024) unsigned char smem[];
    const uint32_t sb = smem_u32(smem);
    const int tid = threadIdx.x, lane = tid & 31, warp = __shfl_sync(0xffffffffu, tid >> 5, 0), g = lane >> 2, tq = lane & 3;
    const int cta = blockIdx.x;
    const bool shared = cta < 32;
    const uint32_t bar = sb + H_BAR;
    const int d0 = cta * 16;
    const uint32_t tstart = clk();
    if (tid == 0) {
        for (int i = 0; i < NST; i++) { mbar_init(bar + HB_FULL + i * 8, 1); mbar_init(bar + HB_EMPTY + i * 8, shared ? 8 : 4); }
        mbar_init(bar + HB_QF, 1); mbar_init(bar + HB_VF, 1); mbar_init(bar + HB_QE, 4); mbar_init(bar + HB_VE, 4); mbar_init(bar + HB_OF, 4); mbar_init(bar + HB_OE, 1);
        asm volatile("fence.proxy.async.shared::cta;" ::: "memory");
    }
    const unsigned epoch = g_epoch[cta] + 1;
    __syncthreads();
    if (tid == 0) g_epoch[cta] = epoch;
    if (warp < 8) {
        asm volatile("setmaxnreg.inc.sync.aligned.u32 176;");
        HEV(0); GT(96, 0);
        const int pr = warp & 3, wb = warp >> 2;
        float4* const par = (float4*)(smem + H_PAR + warp * 2048);
        float* const kd = (float*)(smem + H_KD + warp * 648 * 4);
        uint32_t* const wz = (uint32_t*)(smem + H_W + warp * H_WSTR);
        wz[lane] = 0; wz[32 + lane] = 0;
        if (lane < 16) {
            const __nv_bfloat16* const pp = (lane & 3) == 0 ? logA : (lane & 3) == 1 ? Aim : (lane & 3) == 2 ? Cre : Cim;
            asm volatile("prefetch.global.L2 [%0];" :: "l"(pp + (d0 + warp * 2) * 128 + (lane >> 2) * 64));
        }
        HEV(1);
        if (!(HM & 1)) bar_sync(HN_U + wb * 8, 256);
#pragma unroll 1
        for (int it = 0; it < ((HM & 1) ? 2 + wb : 0); it++) {
            const int ch = (it ? 2 * it - wb : 0) * 4 + pr, d = d0 + slot_channel(ch);
            const float dt = bf2f(__float2bfloat16(expf(bf2f(logdt[d]))));
            const uint32_t dsk = ((const uint16_t*)Dsk)[d];
#pragma unroll
            for (int n = lane; n < 128; n += 32) {
                const float ar = -bf2f(__float2bfloat16(expf(bf2f(logA[d * 128 + n])))) * dt, ai = bf2f(Aim[d * 128 + n]) * dt;
                par[n] = make_float4(ar * 1.4426950408889634f, ai * 0.15915494309189535f, 2.f * TFC * (bf2f(Cre[d * 128 + n]) * dt), 2.f * TFC * (bf2f(Cim[d * 128 + n]) * dt));
            }
            __syncwarp();
            {
                float kacc[5][4], klast = 0.f;
#pragma unroll
                for (int i = 0; i < 5; i++) kacc[i][0] = kacc[i][1] = kacc[i][2] = kacc[i][3] = 0.f;
                const float fa = (float)g, fb = (float)(g + 8);
                const int k0 = it ? 0 : wb * 4, k1 = it ? 8 : k0 + 4;
                float4 pn[4];
#pragma unroll
                for (int i = 0; i < 4; i++) pn[i] = par[16 * k0 + 4 * i + tq];
#pragma unroll 1
                for (int k4 = k0; k4 < k1; k4++) {
#pragma unroll
                    for (int ks = 0; ks < 4; ks++) {
                        const float4 p = pn[ks];
                        pn[ks] = par[(16 * k4 + 4 * ks + 16 + tq) & 127];
                        float ax, ay, bx, by;
                        cexp_turns(p.x * fa, p.y * fa, ax, ay);
                        cexp_turns(p.x * fb, p.y * fb, bx, by);
                        uint32_t F[4][4];
#pragma unroll
                        for (int r = 0; r < 4; r++) {
                            F[r][0] = tf(ax); F[r][1] = tf(bx); F[r][2] = tf(ay); F[r][3] = tf(by);
                            csq(ax, ay); csq(bx, by);
                        }
                        mma_tf32(kacc[0], F[0][0], F[0][1], F[0][2], F[0][3], tf(fmaf(p.z, ax, -p.w * ay)), tf(fmaf(-p.z, ay, -p.w * ax)));
#pragma unroll
                        for (int r = 0; r < 4; r++) {
                            mma_tf32(kacc[r + 1], F[r][0], F[r][1], F[r][2], F[r][3], tf(fmaf(p.z, bx, -p.w * by)), tf(fmaf(-p.z, by, -p.w * bx)));
                            csq(bx, by);
                        }
                        klast = fmaf(p.z, bx, fmaf(-p.w, by, klast));
                    }
                }
                klast += __shfl_xor_sync(0xffffffffu, klast, 1);
                klast += __shfl_xor_sync(0xffffffffu, klast, 2);
                klast *= 1.f / TFC;
                float* const kp = kd + 32 * tq + g;
                if (it == 0 && wb == 0) {
                    bar_sync(HN_G + pr, 64);
#pragma unroll
                    for (int i = 0; i < 5; i++) { kacc[i][0] += kp[i * 128]; kacc[i][1] += kp[i * 128 + 16]; kacc[i][2] += kp[i * 128 + 8]; kacc[i][3] += kp[i * 128 + 24]; }
                    klast += kd[640];
                    __syncwarp();
                }
                const int ko = it == 0 && wb ? -4 * 648 : 0;
#pragma unroll
                for (int i = 0; i < 5; i++) { kp[ko + i * 128] = kacc[i][0]; kp[ko + i * 128 + 16] = kacc[i][1]; kp[ko + i * 128 + 8] = kacc[i][2]; kp[ko + i * 128 + 24] = kacc[i][3]; }
                if (lane == 0) kd[ko + 640] = klast;
                if (ko) { bar_arrive(HN_G + pr, 64); continue; }
                __syncwarp();
            }
#pragma unroll
            for (int h = 0; h < 2; h++) {
                const int i = lane + 32 * h;
                const uint32_t wa = sb + H_W + warp * H_WSTR + 256;
                const float4 v = *(const float4*)(kd + 4 * i);
                sts128(wa + i * 16, pack2(v.x, i ? kd[4 * i - 1] : 0.f), pack2(v.y, v.x), pack2(v.z, v.y), pack2(v.w, v.z));
#pragma unroll
                for (int r = 1; r < 4; r++) {
                    const float2 ab = *(const float2*)(kd + 128 + r * 128 + 2 * i);
                    const float c = kd[130 + r * 128 + 2 * i];
                    const uint32_t ba = pack2(ab.y, ab.x), cb = pack2(c, ab.y);
                    const uint32_t aa = __byte_perm(ba, 0, 0x3232), bb = __byte_perm(ba, 0, 0x1010), cc = __byte_perm(cb, 0, 0x1010);
                    const uint32_t p = wa + (512 << r) + i * (8 << r);
                    if (r == 1) sts128(p, i ? aa : pack2(ab.x, kd[255]), aa, ba, cb);
                    if (r == 2) { sts128(p, aa, aa, aa, ba); sts128(p + 16, bb, bb, cb, cc); }
                    if (r == 3) { sts128(p, aa, aa, aa, aa); sts128(p + 16, aa, ba, bb, bb); sts128(p + 32, bb, bb, bb, bb); sts128(p + 48, cb, cc, cc, cc); }
                }
            }
            __syncwarp();
            if (it == wb) bar_sync(HN_U + wb * 8, 256);
            if (it == 0) HEV(2);
            float acc[4][4][4];
            const uint32_t ub = sb + H_U + ch * H_USTR + (lane >> 3) * 16, zb = sb + H_Z + (lane >> 3) * 16;
            uint32_t bn[2][2][4];
            {
                const uint32_t dg = g == 2 * tq ? dsk : (g == 2 * tq + 1 ? dsk << 16 : 0u);
#pragma unroll
                for (int G = 0; G < 4; G++) {
                    ldsm4(bn[0][0], ub + (8 * G + (lane & 7)) * 144); ldsm4(bn[0][1], ub + (8 * G + (lane & 7)) * 144 + 64);
#pragma unroll
                    for (int i = 0; i < 4; i++) {
                        acc[G][i][0] = acc[G][i][1] = acc[G][i][2] = acc[G][i][3] = 0.f;
                        mma16(acc[G][i], dg, 0, 0, dg, bn[0][i >> 1][(i & 1) * 2], bn[0][i >> 1][(i & 1) * 2 + 1]);
                    }
                }
            }
            const volatile uint32_t* wp = wz + 64 - 56 + g - 2 * tq;
            uint32_t A[8][4];
#pragma unroll
            for (int m = 0; m < 7; m++) { A[m][0] = wp[16 * m + 8]; A[m][3] = wp[16 * m + 8]; A[m][1] = wp[16 * m + 16]; A[m][2] = wp[16 * m]; }
#define CONV_STEP(G0, E)                                                                                                 \
    {                                                                                                                    \
        uint32_t b[3][2][4];                                                                                             \
        _Pragma("unroll") for (int G = 2; G >= (G0); G--) {                                                              \
            const int cidx = 8 * G + (lane & 7) - s - (E);                                                               \
            const uint32_t ba = (G > (G0) || cidx >= 0) ? ub + cidx * 144 : zb;                                          \
            ldsm4(b[G][0], ba); ldsm4(b[G][1], ba + 64);                                                                 \
        }                                                                                                                \
        {                                                                                                                \
            const int cidx = 23 + (lane & 7) - s - (E);                                                                  \
            const uint32_t ba = ((G0) < 2 || cidx >= 0) ? ub + cidx * 144 : zb;                                          \
            ldsm4(bn[1 - (E)][0], ba); ldsm4(bn[1 - (E)][1], ba + 64);                                                   \
        }                                                                                                                \
        const volatile uint32_t* const wn = wp + 64 * min(s + (E) + 1, 31);                                              \
        _Pragma("unroll") for (int ph = 0; ph < 2; ph++) {                                                               \
            _Pragma("unroll") for (int G = 3; G >= (G0); G--)                                                            \
                _Pragma("unroll") for (int j = 3; j >= 0; j--)                                                           \
                    _Pragma("unroll") for (int i = 0; i < 4; i++) {                                                      \
                        if ((i - j + 3 >= 3) != ph) continue;                                                            \
                        const uint32_t* const a = A[(i - j + 3 + 4 * (E)) & 7];                                          \
                        const uint32_t* const bq = G == 3 ? bn[E][j >> 1] : b[G][j >> 1];                                \
                        mma16(acc[G][i], a[0], a[1], a[2], a[3], bq[(j & 1) * 2], bq[(j & 1) * 2 + 1]);                  \
                    }                                                                                                    \
            if (ph == 0) {                                                                                               \
                _Pragma("unroll") for (int m = 3; m < 7; m++) {                                                          \
                    uint32_t* const a = A[(m + 4 + 4 * (E)) & 7];                                                        \
                    a[0] = wn[16 * m + 8]; a[1] = wn[16 * m + 16];                                                       \
                    if (DUPL) { a[2] = wn[16 * m]; a[3] = wn[16 * m + 8]; } else { a[2] = A[(m + 3 + 4 * (E)) & 7][1]; a[3] = a[0]; } \
                }                                                                                                        \
            }                                                                                                            \
        }                                                                                                                \
    }
#define CONV_RANGE(G0) _Pragma("unroll 1") for (int s = 8 * (G0); s < 8 * (G0) + 8; s += 2) { CONV_STEP(G0, 0) CONV_STEP(G0, 1) }
            CONV_RANGE(0) CONV_RANGE(1) CONV_RANGE(2) CONV_RANGE(3)
#undef CONV_RANGE
#undef CONV_STEP
            __syncwarp();
            if (it == 0) HEV(3);
#pragma unroll
            for (int G = 0; G < 4; G++)
#pragma unroll
                for (int i = 0; i < 4; i += 2)
                    asm volatile("stmatrix.sync.aligned.m8n8.x4.trans.shared.b16 [%0], {%1,%2,%3,%4};"
                                 :: "r"(ub + (8 * G + (lane & 7)) * 144 + i * 32), "r"(pack2(acc[G][i][0], acc[G][i][1])), "r"(pack2(acc[G][i][2], acc[G][i][3])),
                                    "r"(pack2(acc[G][i + 1][0], acc[G][i + 1][1])), "r"(pack2(acc[G][i + 1][2], acc[G][i + 1][3])) : "memory");
        }
        HEV(4); GT(96, 1);
        const int wg = warp >> 2, q = warp & 3, t = tid & 127;
        const int nt = shared ? (cta & 3) * 2 + wg : 8, kg = shared ? cta >> 2 : (cta - 32) * 2 + wg;
        fence_smem_async();
        bar_arrive(HN_Y, 320);
        uint32_t w[32][4];
        {
            const uint32_t* src = (const uint32_t*)(Wo + (size_t)(kg * 512 + tq * 8) * DM + nt * 64 + q * 16) + g;
#pragma unroll
            for (int i = 0; i < 64; i++) {
                const int row = (i >> 2) * 32 + (i & 3) * 2;
                const uint32_t x = __ldg(src + row * (DM / 2)), y = __ldg(src + (row + 1) * (DM / 2));
                w[i >> 1][(i & 1) * 2] = __byte_perm(x, y, 0x5410);
                w[i >> 1][(i & 1) * 2 + 1] = __byte_perm(x, y, 0x7632);
            }
        }
        HEV(5);
        if (wg == 1) bar_arrive(HN_P, 256);
        uint32_t* const px = &g_part[0][nt][0][0][t];
        uint32_t* const dst = (uint32_t*)(out + (size_t)((kg >> 1) * 8 + 2 * tq + (kg & 1)) * OUTW + nt * 64 + q * 16) + g;
#pragma unroll 1
        for (int s = 0; s < ((HM & 4) ? NSEG + LAG : 0); s++) {
            const int f = s - LAG;
            const uint32_t* const src = px + (f & 7) * (9 * 8192) + kg * 1024;
            uint32_t v[8];
#pragma unroll
            for (int i = 0; i < 8; i++) v[i] = ldg_rlx(src + i * 128);
            float d[16];
            if (s < NSEG) {
                const int n = shared ? 2 * s : 4 * s + 2 * wg, r = n / NST, st = n - r * NST;
                const uint32_t dl = desc_lo(sb + H_RING + st * 16384);
                if (wg == 0) HS(0);
                mbar_wait(bar + HB_FULL + st * 8, r & 1);
                bar_sync(HN_P + wg, 256);
                if (wg == 0) HS(1);
                wg_fence();
                wgmma32<0>(d, w[0], desc_of(dl));
#pragma unroll
                for (int i = 1; i < 16; i++) wgmma32<1>(d, w[i], desc_of(dl + (i >> 2) * 256 + (i & 3) * 2));
                wg_commit();
                mbar_wait(bar + HB_FULL + st * 8 + 8, r & 1);
                wg_fence();
#pragma unroll
                for (int i = 16; i < PPT; i++) wgmma32<1>(d, w[i], desc_of(dl + (i >> 2) * 256 + (i & 3) * 2));
                bar_arrive(HN_P + (wg ^ 1), 256);
#pragma unroll
                for (int i = PPT; i < 32; i++) wgmma32<1>(d, w[i], desc_of(dl + (i >> 2) * 256 + (i & 3) * 2));
                wg_commit();
                asm volatile("wgmma.wait_group.sync.aligned 1;" ::: "memory");
                mbar_arrive_warp(bar + HB_EMPTY + st * 8);
                wg_wait0();
                mbar_arrive_warp(bar + HB_EMPTY + st * 8 + 8);
                if (wg == 0) HS(2);
                const uint32_t ph = ((s >> 3) + 1) & 1, rnd = ph ? 0u : 0x10000u;
                uint32_t* const p = px + (s & 7) * (9 * 8192) + kg * 128;
#pragma unroll
                for (int r = 0; r < 8; r++) {
                    const uint32_t lo = __float_as_uint(d[4 * (r >> 1) + (r & 1)]) + rnd, hi = __float_as_uint(d[4 * (r >> 1) + 2 + (r & 1)]) + 0x8000u;
                    stg_rlx(p + r * 1024, (__byte_perm(lo, hi, 0x7632) & 0xfffffffeu) | ph);
                }
                if (wg == 0) HS(3);
            }
            if (s >= LAG) {
                const uint32_t ph = ((f >> 3) + 1) & 1;
                for (int it = 0; __any_sync(0xffffffffu, (or3(diff2(v[0], v[1], ph), diff2(v[2], v[3], ph), diff2(v[4], v[5], ph)) | diff2(v[6], v[7], ph)) & 1);) {
#pragma unroll
                    for (int i = 0; i < 8; i++) v[i] = ldg_rlx(src + i * 128);
                    if (++it > (1 << 22)) TRAP(2000 + __LINE__);
                }
            }
            if (s >= LAG)
                dst[(size_t)f * 32 * (OUTW / 2)] = pack2(((bflo(v[0]) + bflo(v[1])) + (bflo(v[2]) + bflo(v[3]))) + ((bflo(v[4]) + bflo(v[5])) + (bflo(v[6]) + bflo(v[7]))),
                                                         ((bfhi(v[0]) + bfhi(v[1])) + (bfhi(v[2]) + bfhi(v[3]))) + ((bfhi(v[4]) + bfhi(v[5])) + (bfhi(v[6]) + bfhi(v[7]))));
            if (wg == 0) HS(4);
        }
        if ((HM & 4) && wg == 0) bar_sync(HN_P, 256);
    } else if (warp < 12) {
        asm volatile("setmaxnreg.dec.sync.aligned.u32 48;");
        if (tid - 256 < 64) ((uint32_t*)(smem + H_Z))[tid - 256] = 0;
        spin_until(tstart + UDLY);
        LOAD_U(warp - 8)
        bar_arrive(HN_U, 256);
        bar_arrive(HN_U + 8, 256);
        const int hd = cta, h0 = shared ? cta & 28 : (cta - 32) * 8, nst = shared ? 2 : 4;
        if (warp == 8) {
            bar_sync(HN_Y, 320);
            int ready = 0;
#pragma unroll 1
            for (int s = 0; s < ((HM & 4) ? NSEG : 0); s++) {
                for (int it = 0; ready <= s;) {
                    unsigned v = epoch;
                    if (s + (lane >> 3) < NSEG) v = ldg_acq(&g_oflag[s + (lane >> 3)][h0 + (lane & (2 * nst - 1))][0]);
                    const uint32_t miss = ~__ballot_sync(0xffffffffu, v == epoch);
                    ready = s + (miss ? (__ffs(miss) - 1) >> 3 : 4);
                    if (++it > (1 << 24)) TRAP(2000 + __LINE__);
                }
                asm volatile("fence.proxy.async.global;" ::: "memory");
#pragma unroll 1
                for (int i = 0; i < nst; i++) {
                    const int n = nst * s + i, r = n / NST, st = n - r * NST;
                    if (r > 0) mbar_wait(bar + HB_EMPTY + st * 8, (r - 1) & 1);
                    if (lane == 0) {
                        mbar_expect(bar + HB_FULL + st * 8, 16384);
                        bulk_g2s(sb + H_RING + st * 16384, (const char*)g_o + (size_t)(s * 64 + h0 * 2 + i * 4) * 4096, 16384, bar + HB_FULL + st * 8);
                    }
                    __syncwarp();
                }
                HS(7);
            }
        } else if (warp == 9) {
#pragma unroll 1
            for (int s = 0; s < ((HM & 2) && shared ? NSEG : 0); s++) {
                const int c = lane % 3;
                unsigned v;
                for (int it = 0; v = ldg_acq(&g_qflag[s][hd][c * 8]), !__all_sync(0xffffffffu, (v ^ (epoch * 64)) < 64);)
                    if (++it > (1 << 24)) TRAP(2000 + __LINE__);
                HS(5);
                asm volatile("fence.proxy.async.global;" ::: "memory");
                const uint32_t off = lane < 3 ? c * 7680 : lane < 6 ? 20480 + c * 2048 : 28672 + c * 512;
                const unsigned char* const src = g_qkv + (size_t)((v & 63) * 32 + hd) * 30720 + off;
                if (s > 0) mbar_wait(bar + HB_QE, (s - 1) & 1);
                if (lane == 0) mbar_expect(bar + HB_QF, 20480);
                if (lane < 3) bulk_g2s(sb + H_QKV + off, src, c == 2 ? 5120 : 7680, bar + HB_QF);
                __syncwarp();
                if (s > 0) mbar_wait(bar + HB_VE, (s - 1) & 1);
                if (lane == 0) mbar_expect(bar + HB_VF, 10240);
                if (lane >= 3 && lane < 9) bulk_g2s(sb + H_QKV + off, src, (lane < 6 ? 2048 : 512) << (c >> 1), bar + HB_VF);
                __syncwarp();
            }
        } else if (warp == 10) {
#pragma unroll 1
            for (int s = 0; s < ((HM & 2) && shared ? NSEG : 0); s++) {
                mbar_wait(bar + HB_OF, s & 1);
                if (lane == 0) {
                    bulk_s2g((char*)g_o + (size_t)(s * 64 + hd * 2) * 4096, sb + H_AO, 8192);
                    asm volatile("cp.async.bulk.commit_group;" ::: "memory");
                    asm volatile("cp.async.bulk.wait_group.read 0;" ::: "memory");
                    mbar_arrive(bar + HB_OE);
                    asm volatile("cp.async.bulk.wait_group 0;" ::: "memory");
                    stg_rlx(&g_oflag[s][hd][0], epoch);
                }
                __syncwarp();
                HS(6);
            }
        } else {
            bar_sync(HN_Y, 320);
#pragma unroll 1
            for (int i = 0; i < 128; i++) {
                const uint32_t t0 = clk();
                uint32_t v[4];
                ldsm4t(v, sb + H_U + (lane & 15) * H_USTR + (i >> 2) * 144 + (i & 3) * 32 + (lane >> 4) * 16);
                uint2* const p = (uint2*)(out + (size_t)(i * 16 + g) * OUTW + DM + d0 + tq * 4);
                p[0] = make_uint2(v[0], v[1]);
                p[8 * (OUTW / 4)] = make_uint2(v[2], v[3]);
                spin_until(t0 + YDLY);
            }
            asm volatile("griddepcontrol.wait;" ::: "memory");
        }
    } else {
        asm volatile("setmaxnreg.dec.sync.aligned.u32 112;");
        const uint32_t qk = sb + H_QKV;
        const int dg = 8 * (warp & 3) + g - 2 * tq;
        const uint32_t oa = pin(sb + H_AO + (8 * (warp & 3) + g) * 128);
#pragma unroll 1
        for (int s = 0; s < ((HM & 2) && shared ? NSEG : 0); s++) {
            float x[24];
            mbar_wait(bar + HB_QF, s & 1);
            wg_fence();
#pragma unroll
            for (int i = 0; i < 8; i++) {
                constexpr int QO[8] = {0, 1024, 2048, 7680, 8704, 9728, 15360, 16384}, KO[8] = {3072, 4608, 6144, 10752, 12288, 13824, 17408, 18944};
                if (i == 0) wgmma48_tt<0>(x, desc_plain(qk + QO[i], 128, 128), desc_plain(qk + KO[i], 128, 256));
                else wgmma48_tt<1>(x, desc_plain(qk + QO[i], 128, 128), desc_plain(qk + KO[i], 128, 256));
            }
            wg_commit();
            wg_wait0();
            mbar_arrive_warp(bar + HB_QE);
            x[16] += x[20]; x[17] += x[21];
            float m = fmaxf(x[16], x[17]);
#pragma unroll
            for (int b = 0; b < 4; b++) {
                if (8 * b > dg) x[4 * b] = NEG;
                if (8 * b + 1 > dg) x[4 * b + 1] = NEG;
                m = fmaxf(m, fmaxf(x[4 * b], x[4 * b + 1]));
            }
            m = fmaxf(m, __shfl_xor_sync(0xffffffffu, m, 1));
            m = fmaxf(m, __shfl_xor_sync(0xffffffffu, m, 2));
            float l = 0.f;
            uint32_t pa[3][4];
#pragma unroll
            for (int b = 0; b < 5; b++) {
                const float e0 = ex2(x[4 * b] - m), e1 = ex2(x[4 * b + 1] - m);
                l += e0 + e1;
                pa[b >> 1][(b & 1) * 2] = pack2(e0, e1);
                pa[b >> 1][(b & 1) * 2 + 1] = 0;
            }
            pa[2][2] = pa[2][3] = 0;
            l += __shfl_xor_sync(0xffffffffu, l, 1);
            l = rcp_fast(l + __shfl_xor_sync(0xffffffffu, l, 2));
            uint32_t ow[2][8];
            mbar_wait(bar + HB_VF, s & 1);
#pragma unroll
            for (int hf = 0; hf < 2; hf++) {
                float o[32];
                wg_fence();
                wgmma64<0>(o, pa[0], desc_plain(qk + 20480 + hf * 128, 256, 1024));
                wgmma64<1>(o, pa[1], desc_plain(qk + 20480 + 512 + hf * 128, 256, 1024));
                wgmma64<1>(o, pa[2], desc_plain(qk + 28672 + hf * 128, 0, 256));
                wg_commit();
                if (hf == 0 && s > 0) mbar_wait(bar + HB_OE, (s - 1) & 1);
                wg_wait0();
#pragma unroll
                for (int i = 0; i < 8; i++) ow[hf][i] = pack2(o[4 * i] * l, o[4 * i + 1] * l);
            }
            mbar_arrive_warp(bar + HB_VE);
#pragma unroll
            for (int grp = 0; grp < 4; grp++)
                sts128(oa + (grp >> 1) * 4096 + ((((grp & 1) * 4 + tq) ^ g) << 4), ow[0][2 * grp], ow[1][2 * grp], ow[0][2 * grp + 1], ow[1][2 * grp + 1]);
            fence_smem_async();
            mbar_arrive_warp(bar + HB_OF);
        }
    }
}

typedef CUresult (*EncodeFn)(CUtensorMap*, CUtensorMapDataType, cuuint32_t, void*, const cuuint64_t*, const cuuint64_t*, const cuuint32_t*,
                             const cuuint32_t*, CUtensorMapInterleave, CUtensorMapSwizzle, CUtensorMapL2promotion, CUtensorMapFloatOOBfill);

static void make_map(EncodeFn enc, CUtensorMap* m, void* base, int width, int boxchunks) {
    cuuint64_t dims[3] = {64, 2048, (cuuint64_t)(width / 64)};
    cuuint64_t strides[2] = {(cuuint64_t)width * 2, 128};
    cuuint32_t box[3] = {64, 32, (cuuint32_t)boxchunks};
    cuuint32_t es[3] = {1, 1, 1};
    enc(m, CU_TENSOR_MAP_DATA_TYPE_BFLOAT16, 3, base, dims, strides, box, es, CU_TENSOR_MAP_INTERLEAVE_NONE, CU_TENSOR_MAP_SWIZZLE_128B,
        CU_TENSOR_MAP_L2_PROMOTION_L2_256B, CU_TENSOR_MAP_FLOAT_OOB_FILL_NONE);
}

extern "C" void kernel_launch(void* const* d_in, const int* in_sizes, int n_in, void* d_out, int out_size) {
    typedef const __nv_bfloat16* P;
    static EncodeFn enc = nullptr;
    if (!enc) {
        void* fn = nullptr;
        cudaDriverEntryPointQueryResult st;
        cudaGetDriverEntryPoint("cuTensorMapEncodeTiled", &fn, cudaEnableDefault, &st);
        enc = (EncodeFn)fn;
        cudaFuncSetAttribute(rk_kernel, cudaFuncAttributeMaxDynamicSharedMemorySize, R_SMEM);
        cudaFuncSetAttribute(hk_kernel, cudaFuncAttributeMaxDynamicSharedMemorySize, H_SMEM);
    }
    Maps maps;
    make_map(enc, &maps.x, d_in[0], DM, 3);
    {
        void* acc = nullptr;
        cudaGetSymbolAddress(&acc, g_acc);
        for (int m = 0; m < 2; m++) {
            cuuint64_t dims[5] = {128, 2, 2, 2, 144};
            cuuint64_t strides[4] = {(cuuint64_t)(m ? 4096 : 12288), 1024, 16384, 256};
            cuuint32_t box[5] = {64, 2, 2, 2, 2}, es[5] = {1, 1, 1, 1, 1};
            enc(&maps.acc[m], CU_TENSOR_MAP_DATA_TYPE_BFLOAT16, 5, (char*)acc + m * 4096, dims, strides, box, es, CU_TENSOR_MAP_INTERLEAVE_NONE,
                CU_TENSOR_MAP_SWIZZLE_NONE, CU_TENSOR_MAP_L2_PROMOTION_NONE, CU_TENSOR_MAP_FLOAT_OOB_FILL_NONE);
        }
    }

    cudaLaunchConfig_t cfg = {};
    cudaLaunchAttribute at[1];
    cfg.gridDim = dim3(96); cfg.blockDim = dim3(384); cfg.dynamicSmemBytes = R_SMEM; cfg.stream = cudaStreamPerThread;
    at[0].id = cudaLaunchAttributeClusterDimension; at[0].val.clusterDim.x = 3; at[0].val.clusterDim.y = 1; at[0].val.clusterDim.z = 1;
    cfg.attrs = at; cfg.numAttrs = 1;
    cudaLaunchKernelEx(&cfg, rk_kernel, maps, (P)d_in[0], (P)d_in[1], (P)d_in[2], (P)d_in[3], (P)d_in[4], (P)d_in[5]);

    cfg.gridDim = dim3(36); cfg.blockDim = dim3(512); cfg.dynamicSmemBytes = H_SMEM;
    at[0].id = cudaLaunchAttributeProgrammaticStreamSerialization; at[0].val.programmaticStreamSerializationAllowed = 1;
    cudaLaunchKernelEx(&cfg, hk_kernel, (P)d_in[5], (P)d_in[7], (P)d_in[8], (P)d_in[9], (P)d_in[10], (P)d_in[11], (P)d_in[12], (P)d_in[13],
                       (__nv_bfloat16*)d_out);
}
```

```cpp
#include <cuda_runtime.h>
#include <cuda_bf16.h>
#include <cuda_fp16.h>
#include <cuda.h>
#include <stdint.h>

#define DEVI __device__ __forceinline__

#define NEG __int_as_float(0xff800000)
constexpr int DM = 576, NSEG = 64, HD = 4096, OUTW = 1152;

#define HM 7
#define QW 4000
#define NPROBE 4
#define CT 1600
#define FE 85
#define DL 0
#define DMIN 150
#define DMAX 4000
#define BACKOFF 200
#define LW 3
#define TIE 0
#define C2ADJ 80
#define DST 120
#define VFE 0
#define EW 0
#define LB 12
#define NTR 3
#define RP 176
#define NW2 3
#define KT 4
#define DDUMP 200
#define DPUSH 300
#define GOE 21
#define LDM 2
#define XD 50
#define G1T 0
#define F0T 14
#define F1T 16
#define SUMV 0
#define UDLY 0
#define YDLY 300
#define PPT 32
#define LAG 3
#define QR 4
#define DUPL 1
#define WPF 3
#define XPF 0
#define SSP 10
#define TR0 0
#define KB 0
#define NCH 4
#define NS 4
#define N0 3
#define P2 9
#define VW 0
#define VD 0
#define VT 1
#define PE 1
#define DUMPX 0
#define NPOLL 3
#define DSTI 150
#define ONE 1
#define OB 1
#define TR1 2
#define MW 2
#define N1 8

__device__ __align__(1024) __nv_bfloat16 g_o[2048 * HD];
__device__ __align__(65536) uint32_t g_acc[16384];
__device__ __align__(128) unsigned g_pub[96];
__device__ __align__(128) uint32_t g_part[8][9][8][8][128];
__device__ __align__(1024) unsigned char g_qkv[(size_t)NSEG * 32 * 30720];
__device__ __align__(128) unsigned g_qflag[NSEG][32][32];
__device__ __align__(128) unsigned g_oflag[NSEG][32][8];
__device__ unsigned g_epoch[36 + 96];
#define EV(i)
#define EVV(i, v)
#define EVX(i) 0
#define EVADD(i, v)
#define HS(i)
#define PT(i)
#define HEV(i)
#define GT(b, i)

#define TRAP(code) __trap()
#define LOC(v)
DEVI uint32_t smem_u32(const void* p) { return (uint32_t)__cvta_generic_to_shared(p); }
DEVI uint32_t clk() { uint64_t t; asm volatile("mov.u64 %0, %%clock64;" : "=l"(t) :: "memory"); return (uint32_t)t; }
DEVI uint32_t gtime() { uint64_t t; asm volatile("mov.u64 %0, %%globaltimer;" : "=l"(t) :: "memory"); return (uint32_t)t; }
DEVI void spin_until(uint32_t t) { while ((int)(clk() - t) < 0) {} }
DEVI void jit() {}
DEVI uint32_t mapa(uint32_t a, uint32_t r) { uint32_t o; asm("mapa.shared::cluster.u32 %0, %1, %2;" : "=r"(o) : "r"(a), "r"(r)); return o; }
DEVI void mbar_init(uint32_t b, uint32_t n) { asm volatile("mbarrier.init.shared::cta.b64 [%0], %1;" :: "r"(b), "r"(n) : "memory"); }
DEVI void mbar_expect(uint32_t b, uint32_t bytes) { asm volatile("mbarrier.arrive.expect_tx.shared::cta.b64 _, [%0], %1;" :: "r"(b), "r"(bytes) : "memory"); }
DEVI void mbar_arrive(uint32_t b) { asm volatile("mbarrier.arrive.shared::cta.b64 _, [%0];" :: "r"(b) : "memory"); }
DEVI bool mbar_try(uint32_t b, uint32_t parity) {
    uint32_t ok;
    asm volatile("{.reg .pred p; mbarrier.try_wait.parity.shared::cta.b64 p, [%1], %2; selp.u32 %0, 1, 0, p;}" : "=r"(ok) : "r"(b), "r"(parity) : "memory");
    return ok;
}
DEVI void mbar_wait(uint32_t b, uint32_t parity) {
    LOC(0x100 | (b & 0xff) | (parity << 12));
    asm volatile("{.reg .pred p, q; .reg .u32 n; mov.u32 n, 0;\n W: mbarrier.try_wait.parity.shared::cta.b64 p, [%0], %1;\n"
                 "add.u32 n, n, 1; setp.lt.and.u32 q, n, 0x40000, !p; @q bra W;}" :: "r"(b), "r"(parity) : "memory");
    LOC(0x300 | (b & 0xff));
    jit();
}
DEVI void bar_sync(int id, int n) { jit(); LOC(0x200 | id); asm volatile("bar.sync %0, %1;" :: "r"(id), "r"(n) : "memory"); LOC(0x400 | id); jit(); }
DEVI void bar_arrive(int id, int n) { jit(); asm volatile("bar.arrive %0, %1;" :: "r"(id), "r"(n) : "memory"); jit(); }
DEVI void cluster_sync() { asm volatile("barrier.cluster.arrive.release.aligned; barrier.cluster.wait.acquire.aligned;" ::: "memory"); }
DEVI void cluster_arrive_rlx() { asm volatile("barrier.cluster.arrive.relaxed.aligned;" ::: "memory"); }
DEVI void cluster_wait() { asm volatile("barrier.cluster.wait.aligned;" ::: "memory"); }
DEVI void fence_async() { asm volatile("fence.proxy.async;" ::: "memory"); }
DEVI void cp16(uint32_t dst, const void* src) { asm volatile("cp.async.cg.shared.global [%0], [%1], 16;" :: "r"(dst), "l"(src) : "memory"); }
DEVI void cp_commit() { asm volatile("cp.async.commit_group;" ::: "memory"); }
template <int N> DEVI void cp_wait() { asm volatile("cp.async.wait_group %0;" :: "n"(N) : "memory"); }
DEVI void ldsm4(uint32_t* r, uint32_t a) {
    asm volatile("ldmatrix.sync.aligned.m8n8.x4.shared.b16 {%0,%1,%2,%3}, [%4];" : "=r"(r[0]), "=r"(r[1]), "=r"(r[2]), "=r"(r[3]) : "r"(a) : "memory");
}
DEVI uint32_t tab1(uint32_t a) { uint32_t r; asm volatile("ldmatrix.sync.aligned.m8n8.x1.shared.b16 {%0}, [%1];" : "=r"(r) : "r"(a) : "memory"); return r; }
DEVI uint2 tab2(uint32_t a) { uint2 r; asm volatile("ldmatrix.sync.aligned.m8n8.x2.shared.b16 {%0,%1}, [%2];" : "=r"(r.x), "=r"(r.y) : "r"(a) : "memory"); return r; }
DEVI void ldsm4t(uint32_t* r, uint32_t a) {
    asm volatile("ldmatrix.sync.aligned.m8n8.x4.trans.shared.b16 {%0,%1,%2,%3}, [%4];" : "=r"(r[0]), "=r"(r[1]), "=r"(r[2]), "=r"(r[3]) : "r"(a) : "memory");
}
DEVI void mma16(float* d, uint32_t a0, uint32_t a1, uint32_t a2, uint32_t a3, uint32_t b0, uint32_t b1) {
    asm volatile("mma.sync.aligned.m16n8k16.row.col.f32.bf16.bf16.f32 {%0,%1,%2,%3}, {%4,%5,%6,%7}, {%8,%9}, {%0,%1,%2,%3};"
                 : "+f"(d[0]), "+f"(d[1]), "+f"(d[2]), "+f"(d[3]) : "r"(a0), "r"(a1), "r"(a2), "r"(a3), "r"(b0), "r"(b1));
}
DEVI void mma8(float* d, uint32_t a0, uint32_t a1, uint32_t b0) {
    asm volatile("mma.sync.aligned.m16n8k8.row.col.f32.bf16.bf16.f32 {%0,%1,%2,%3}, {%4,%5}, {%6}, {%0,%1,%2,%3};"
                 : "+f"(d[0]), "+f"(d[1]), "+f"(d[2]), "+f"(d[3]) : "r"(a0), "r"(a1), "r"(b0));
}
DEVI void mma_tf32(float* d, uint32_t a0, uint32_t a1, uint32_t a2, uint32_t a3, uint32_t b0, uint32_t b1) {
    asm volatile("mma.sync.aligned.m16n8k8.row.col.f32.tf32.tf32.f32 {%0,%1,%2,%3}, {%4,%5,%6,%7}, {%8,%9}, {%0,%1,%2,%3};"
                 : "+f"(d[0]), "+f"(d[1]), "+f"(d[2]), "+f"(d[3]) : "r"(a0), "r"(a1), "r"(a2), "r"(a3), "r"(b0), "r"(b1));
}
template <int ACC> DEVI void wgmma32(float* d, const uint32_t* a, uint64_t desc) {
    asm volatile("wgmma.mma_async.sync.aligned.m64n32k16.f32.bf16.bf16 "
                 "{%0,%1,%2,%3,%4,%5,%6,%7,%8,%9,%10,%11,%12,%13,%14,%15}, {%16,%17,%18,%19}, %20, %21, 1, 1, 0;"
                 : "+f"(d[0]), "+f"(d[1]), "+f"(d[2]), "+f"(d[3]), "+f"(d[4]), "+f"(d[5]), "+f"(d[6]), "+f"(d[7]),
                   "+f"(d[8]), "+f"(d[9]), "+f"(d[10]), "+f"(d[11]), "+f"(d[12]), "+f"(d[13]), "+f"(d[14]), "+f"(d[15])
                 : "r"(a[0]), "r"(a[1]), "r"(a[2]), "r"(a[3]), "l"(desc), "n"(ACC));
}
template <int ACC> DEVI void wgmma32_ss(float* d, uint64_t adesc, uint64_t desc) {
    asm volatile("wgmma.mma_async.sync.aligned.m64n32k16.f32.bf16.bf16 "
                 "{%0,%1,%2,%3,%4,%5,%6,%7,%8,%9,%10,%11,%12,%13,%14,%15}, %16, %17, %18, 1, 1, 1, 0;"
                 : "+f"(d[0]), "+f"(d[1]), "+f"(d[2]), "+f"(d[3]), "+f"(d[4]), "+f"(d[5]), "+f"(d[6]), "+f"(d[7]),
                   "+f"(d[8]), "+f"(d[9]), "+f"(d[10]), "+f"(d[11]), "+f"(d[12]), "+f"(d[13]), "+f"(d[14]), "+f"(d[15])
                 : "l"(adesc), "l"(desc), "n"(ACC));
}
DEVI void wg_fence() { asm volatile("wgmma.fence.sync.aligned;" ::: "memory"); }
DEVI void wg_commit() { asm volatile("wgmma.commit_group.sync.aligned;" ::: "memory"); }
DEVI void wg_wait0() { asm volatile("wgmma.wait_group.sync.aligned 0;" ::: "memory"); }
DEVI uint64_t desc_sw128(uint32_t saddr) { return ((uint64_t)1 << 62) | ((uint64_t)64 << 32) | ((uint64_t)1 << 16) | (uint64_t)((saddr & 0x3FFFF) >> 4); }
DEVI uint32_t desc_lo(uint32_t saddr) { return (1u << 16) | ((saddr & 0x3FFFF) >> 4); }
DEVI uint64_t desc_of(uint32_t lo) { uint64_t d; asm("mov.b64 %0, {%1, 0x40000040};" : "=l"(d) : "r"(lo)); return d; }
DEVI uint64_t desc_sw32(uint32_t lo) { uint64_t d; asm("mov.b64 %0, {%1, 0xc0000010};" : "=l"(d) : "r"(lo)); return d; }
DEVI uint32_t pack2(float lo, float hi) { uint32_t r; asm("cvt.rn.bf16x2.f32 %0, %1, %2;" : "=r"(r) : "f"(hi), "f"(lo)); return r; }
DEVI void sts32(uint32_t a, uint32_t v) { asm volatile("st.shared.u32 [%0], %1;" :: "r"(a), "r"(v) : "memory"); }
DEVI void sts64f(uint32_t a, float x, float y) { asm volatile("st.shared.v2.f32 [%0], {%1,%2};" :: "r"(a), "f"(x), "f"(y) : "memory"); }
DEVI void sts128f(uint32_t a, float x, float y, float z, float w) { asm volatile("st.shared.v4.f32 [%0], {%1,%2,%3,%4};" :: "r"(a), "f"(x), "f"(y), "f"(z), "f"(w) : "memory"); }
DEVI float2 lds64f(uint32_t a) { float2 v; asm volatile("ld.shared.v2.f32 {%0,%1}, [%2];" : "=f"(v.x), "=f"(v.y) : "r"(a) : "memory"); return v; }
DEVI float4 lds128f(uint32_t a) { float4 v; asm volatile("ld.shared.v4.f32 {%0,%1,%2,%3}, [%4];" : "=f"(v.x), "=f"(v.y), "=f"(v.z), "=f"(v.w) : "r"(a) : "memory"); return v; }
DEVI uint4 lds128(uint32_t a) { uint4 v; asm volatile("ld.shared.v4.u32 {%0,%1,%2,%3}, [%4];" : "=r"(v.x), "=r"(v.y), "=r"(v.z), "=r"(v.w) : "r"(a) : "memory"); return v; }
DEVI uint4 ldm128(uint32_t a) {
    uint4 v;
    asm volatile("ld.volatile.shared.v4.u32 {%0,%1,%2,%3}, [%4];" : "=r"(v.x), "=r"(v.y), "=r"(v.z), "=r"(v.w) : "r"(a) : "memory");
    return v;
}
DEVI void sta32(uint32_t a, uint32_t v, uint32_t bar) { asm volatile("st.async.weak.shared::cluster.mbarrier::complete_tx::bytes.b32 [%0], %1, [%2];" :: "r"(a), "r"(v), "r"(bar) : "memory"); }
DEVI void sta64f(uint32_t a, float x, float y, uint32_t bar) { asm volatile("st.async.weak.shared::cluster.mbarrier::complete_tx::bytes.v2.f32 [%0], {%1,%2}, [%3];" :: "r"(a), "f"(x), "f"(y), "r"(bar) : "memory"); }
DEVI void sta128f(uint32_t a, float x, float y, float z, float w, uint32_t bar) {
    asm volatile("st.async.weak.shared::cluster.mbarrier::complete_tx::bytes.v4.f32 [%0], {%1,%2,%3,%4}, [%5];" :: "r"(a), "f"(x), "f"(y), "f"(z), "f"(w), "r"(bar) : "memory");
}
DEVI void stg_rlx(uint32_t* p, uint32_t v) { asm volatile("st.relaxed.gpu.global.u32 [%0], %1;" :: "l"(p), "r"(v) : "memory"); }
DEVI void stg_release(unsigned* p, unsigned v) { asm volatile("st.release.gpu.global.u32 [%0], %1;" :: "l"(p), "r"(v) : "memory"); }
DEVI uint32_t ldg_rlx(const uint32_t* p) { uint32_t v; asm volatile("ld.relaxed.gpu.global.u32 %0, [%1];" : "=r"(v) : "l"(p) : "memory"); return v; }
DEVI void bulk_g2s(uint32_t dst, const void* src, uint32_t bytes, uint32_t bar) {
    asm volatile("cp.async.bulk.shared::cluster.global.mbarrier::complete_tx::bytes [%0], [%1], %2, [%3];" :: "r"(dst), "l"(src), "r"(bytes), "r"(bar) : "memory");
}
DEVI void bulk_s2c(uint32_t dst, uint32_t src, uint32_t bytes, uint32_t bar) {
    asm volatile("cp.async.bulk.shared::cluster.shared::cta.mbarrier::complete_tx::bytes [%0], [%1], %2, [%3];" :: "r"(dst), "r"(src), "r"(bytes), "r"(bar) : "memory");
}
DEVI float ex2(float x) { float y; asm("ex2.approx.ftz.f32 %0, %1;" : "=f"(y) : "f"(x)); return y; }
DEVI float ex2v(float x) { float y; asm volatile("ex2.approx.ftz.f32 %0, %1;" : "=f"(y) : "f"(x)); return y; }
DEVI float bf2f(__nv_bfloat16 v) { return __bfloat162float(v); }

DEVI uint32_t pin(uint32_t v) { return __shfl_sync(0xffffffffu, v, threadIdx.x & 31); }
template <typename T> DEVI T* pinp(T* p) { const uint64_t v = (uint64_t)p; return (T*)(((uint64_t)pin((uint32_t)(v >> 32)) << 32) | pin((uint32_t)v)); }
DEVI uint32_t fresh(uint32_t v) { uint32_t r; asm volatile("mov.u32 %0, %1;" : "=r"(r) : "r"(v)); return r; }
DEVI uint64_t fresh64(uint64_t v) { uint64_t r; asm volatile("mov.u64 %0, %1;" : "=l"(r) : "l"(v)); return r; }
DEVI uint32_t or3(uint32_t a, uint32_t b, uint32_t c) { uint32_t d; asm("lop3.b32 %0, %1, %2, %3, 0xfe;" : "=r"(d) : "r"(a), "r"(b), "r"(c)); return d; }
DEVI uint32_t orand(uint32_t a, uint32_t b, uint32_t c) { uint32_t d; asm("lop3.b32 %0, %1, %2, %3, 0xf8;" : "=r"(d) : "r"(a), "r"(b), "r"(c)); return d; }
DEVI uint32_t and3(uint32_t a, uint32_t b, uint32_t c) { uint32_t d; asm("lop3.b32 %0, %1, %2, %3, 0x80;" : "=r"(d) : "r"(a), "r"(b), "r"(c)); return d; }
DEVI uint32_t diff2(uint32_t a, uint32_t b, uint32_t p) { uint32_t d; asm("lop3.b32 %0, %1, %2, %3, 0x7e;" : "=r"(d) : "r"(a), "r"(b), "r"(p)); return d; }
DEVI int lds32(uint32_t a) { int v; asm volatile("ld.volatile.shared.s32 %0, [%1];" : "=r"(v) : "r"(a) : "memory"); return v; }
DEVI uint2 lds64(uint32_t a) { uint2 v; asm volatile("ld.shared.v2.u32 {%0,%1}, [%2];" : "=r"(v.x), "=r"(v.y) : "r"(a) : "memory"); return v; }
DEVI void sts64(uint32_t a, uint32_t x, uint32_t y) { asm volatile("st.shared.v2.u32 [%0], {%1,%2};" :: "r"(a), "r"(x), "r"(y) : "memory"); }
DEVI void sta64(uint32_t a, uint32_t x, uint32_t y, uint32_t bar) { asm volatile("st.async.weak.shared::cluster.mbarrier::complete_tx::bytes.v2.b32 [%0], {%1,%2}, [%3];" :: "r"(a), "r"(x), "r"(y), "r"(bar) : "memory"); }
DEVI float rcp_fast(float x) { float y; asm("rcp.approx.ftz.f32 %0, %1;" : "=f"(y) : "f"(x)); return y; }
DEVI uint4 ldg_rlx4(const void* p) { uint4 v; asm volatile("ld.relaxed.gpu.global.v4.u32 {%0,%1,%2,%3}, [%4];" : "=r"(v.x), "=r"(v.y), "=r"(v.z), "=r"(v.w) : "l"(p) : "memory"); return v; }
DEVI void sts128(uint32_t a, uint32_t x, uint32_t y, uint32_t z, uint32_t w) { asm volatile("st.shared.v4.u32 [%0], {%1,%2,%3,%4};" :: "r"(a), "r"(x), "r"(y), "r"(z), "r"(w) : "memory"); }
DEVI void stsm4(uint32_t a, uint32_t x, uint32_t y, uint32_t z, uint32_t w) { asm volatile("stmatrix.sync.aligned.m8n8.x4.shared.b16 [%0], {%1,%2,%3,%4};" :: "r"(a), "r"(x), "r"(y), "r"(z), "r"(w) : "memory"); }
DEVI void stsm2(uint32_t a, uint32_t x, uint32_t y) { asm volatile("stmatrix.sync.aligned.m8n8.x2.shared.b16 [%0], {%1,%2};" :: "r"(a), "r"(x), "r"(y) : "memory"); }
DEVI void fence_smem_async() { asm volatile("fence.proxy.async.shared::cta;" ::: "memory"); }
DEVI uint32_t packh2(float lo, float hi) { uint32_t r; asm("cvt.rn.f16x2.f32 %0, %1, %2;" : "=r"(r) : "f"(hi), "f"(lo)); return r; }
DEVI uint32_t h2_to_bf2(uint32_t w) {
    uint32_t r;
    asm("{.reg .f16 l, h; .reg .f32 a, b; mov.b32 {l, h}, %1; cvt.f32.f16 a, l; cvt.f32.f16 b, h; cvt.rn.bf16x2.f32 %0, b, a;}" : "=r"(r) : "r"(w));
    return r;
}
DEVI uint32_t amax2(uint32_t m, uint32_t w) { return __vmaxu2(m, w & 0x7fff7fffu); }
DEVI uint32_t amax_fold(uint32_t m) { return __reduce_max_sync(0xffffffffu, max(m & 0xffffu, m >> 16)); }
DEVI float bflo(uint32_t w) { return __uint_as_float(w << 16); }
DEVI float bfhi(uint32_t w) { return __uint_as_float(w & 0xffff0000u); }
DEVI void red_b8(void* p, uint32_t a, uint32_t b, uint32_t c, uint32_t d) {
    asm volatile("red.relaxed.gpu.global.add.noftz.v4.bf16x2 [%0], {%1,%2,%3,%4};" :: "l"(p), "r"(a), "r"(b), "r"(c), "r"(d) : "memory");
}
DEVI void red_h8_if(bool on, void* p, uint32_t a, uint32_t b, uint32_t c, uint32_t d) {
    asm volatile("{.reg .pred p; setp.ne.u32 p, %5, 0; @p red.relaxed.gpu.global.add.noftz.v4.bf16x2 [%0], {%1,%2,%3,%4};}" :: "l"(p), "r"(a), "r"(b), "r"(c), "r"(d), "r"((uint32_t)on) : "memory");
}
DEVI void mbar_arrive_warp(uint32_t b) { asm volatile("{.reg .pred p; elect.sync _|p, 0xffffffff; @p mbarrier.arrive.shared::cta.b64 _, [%0];}" :: "r"(b) : "memory"); }
DEVI void bulk_s2c_warp(uint32_t dst, uint32_t src, uint32_t bytes, uint32_t bar) {
    asm volatile("{.reg .pred p; elect.sync _|p, 0xffffffff; @p cp.async.bulk.shared::cluster.shared::cta.mbarrier::complete_tx::bytes [%0], [%1], %2, [%3];}" :: "r"(dst), "r"(src), "r"(bytes), "r"(bar) : "memory");
}
DEVI char* mkptr(uint32_t lo, uint32_t hi) { uint64_t p; asm("mov.b64 %0, {%1, %2};" : "=l"(p) : "r"(lo), "r"(hi)); return (char*)p; }
DEVI void bulk_s2g(void* dst, uint32_t src, uint32_t bytes) { asm volatile("cp.async.bulk.global.shared::cta.bulk_group [%0], [%1], %2;" :: "l"(dst), "r"(src), "r"(bytes) : "memory"); }
DEVI void x_tma(uint32_t dst, const CUtensorMap* m, uint32_t xb, int row, int chunk) {
    asm volatile("cp.async.bulk.tensor.3d.shared::cluster.global.mbarrier::complete_tx::bytes.multicast::cluster [%0], [%1, {%3, %4, %5}], [%2], %6;"
                 :: "r"(dst), "l"(m), "r"(xb), "r"(0), "r"(row), "r"(chunk), "h"((uint16_t)7) : "memory");
}
#define RUNG_(A, B, PA, PB) "mov.u64 " A ", %%clock64;\n cvt.u32.u64 l, " B ";\n sub.s32 l, l, %0;\n setp.ge.s32 " PB ", l, 0;\n @" PA " bra.uni DONE;\n"
DEVI void fine_until(uint32_t t) {
    asm volatile("{.reg .pred p0, p1; .reg .b64 t0, t1; .reg .b32 l;\n setp.ne.u32 p0, 0, 0;\n mov.u64 t1, %%clock64;\n LOOP:\n"
                 RUNG_("t0", "t1", "p0", "p1") RUNG_("t1", "t0", "p1", "p0") RUNG_("t0", "t1", "p0", "p1") RUNG_("t1", "t0", "p1", "p0")
                 RUNG_("t0", "t1", "p0", "p1") RUNG_("t1", "t0", "p1", "p0") RUNG_("t0", "t1", "p0", "p1") RUNG_("t1", "t0", "p1", "p0")
                 "bra.uni LOOP;\n DONE:\n}" :: "r"(t) : "memory");
}
DEVI uint32_t clock_offset() {
    const uint32_t g0 = gtime();
    uint32_t e = clk();
#pragma unroll
    for (int i = 0; i < 7; i++) { const uint32_t g = gtime(), t = clk(); e = g == g0 ? t : e; }
    return ((((g0 >> 5) + 1) * 3686u) >> 6) - e;
}
constexpr int R_X0 = 0;
constexpr int R_K = 110592 + 3072;
constexpr int R_V = R_K + 4608;
constexpr int R_VM = R_V + 8192;
constexpr int PAR = 17920;
constexpr int R_QM = R_VM + 2048 + PAR;
constexpr int R_SC = R_QM + 1536;
constexpr int R_O8 = R_SC + 2048;
constexpr int R_PX = R_O8 + 2048;
constexpr int R_PV = R_PX + 8192;
constexpr int R_Z = R_PV + 4096;
constexpr int R_END = R_Z + 512;
constexpr int R_STAGE = 36864;
constexpr int R_RES = R_STAGE + 8 * 16384;
constexpr int R_WO = R_RES + 16384;
constexpr int R_T4 = R_WO;
constexpr int R_T5 = R_T4 + 4096;
constexpr int R_T6 = R_T5 + 4096;
constexpr int R_DBG = R_T6 + 4096;
constexpr int R_T0 = R_WO + 24576;
constexpr int R_T1 = R_T0 + 2048;
constexpr int R_T2 = R_T1 + 8192;
constexpr int R_MEM = R_T2 + 256;
constexpr int R_BAR = R_MEM + 12288;
constexpr int R_MISC = R_BAR + 384;
constexpr int R_SMEM = R_MISC + 128;
static_assert(R_END <= R_RES && R_SMEM <= 232448, "smem");
enum { BX0 = 0  , BME = 32, BSC = 40  , BML = 56, BW = 64   };
enum { NB_F1 = 1, NB_D = 2, NB_K = 5, NB_G1 = 6, NB_E0 = 7, NB_GO = 8, NB_W1 = 9, NB_H1 = 10, NB_TOK = 11, NB_W2 = 12, NB_F0 = 13 };
enum { M_EPOCH = 0, M_SINK = 4,  M_PASS = 8, M_TGT = 16  , M_RING = 40, M_REF = 48  , M_PROBE = 56  , M_DONE = 64   };
constexpr uint32_t EMPTY = 0xc200u;
constexpr float QS = 0.08838834764831845f * 1.4426950408889634f;

DEVI uint32_t acc_slot(uint32_t s) { return (s & 1) * 128 + (s & 2) * 16384; }
DEVI uint32_t acc_blk(uint32_t m, uint32_t l) { return (((l >> 1) << 2) | ((l & 1) << 1) | ((l & 1) ^ m)) * 4096; }
DEVI uint32_t acc_line(uint32_t i, uint32_t q, uint32_t l) { return acc_blk(q & 1, l) + (q >> 1) * 256 + (i < 4 ? i * 1024 : i * 1024 - 1536); }
DEVI uint32_t acc_stamp(uint32_t m, uint32_t n) { return acc_blk(m, (n >> 3) & 3) + 512 + ((n >> 5) & 1) * 256 + (n >> 6) * 1024 + (n & 7) * 16; }

#define LOAD_TRANSIENT(LA) { _Pragma("unroll") for (int i_ = 0; i_ < NTR; i_++) ldsm4t(w[i_ & 1][i_ >> 1], (LA) + (i_ & 1) * 4096 + (i_ >> 1) * 512); }
#define PIN() asm volatile("{.reg .b64 t; .reg .b32 l, h; mov.u64 t, %%clock64; mov.b64 {l, h}, t; xor.b32 %0, %0, l;}" : "+r"(junk) :: "memory")
#define MMAW(D, T, K, B0, B1) mma16(D, w[T][K][0], w[T][K][1], w[T][K][2], w[T][K][3], B0, B1)

DEVI void bulk_s2g_warp(void* dst, uint32_t src, uint32_t bytes) {
    asm volatile("{.reg .pred p; elect.sync _|p, 0xffffffff; @p cp.async.bulk.global.shared::cta.bulk_group [%0], [%1], %2;}" :: "l"(dst), "r"(src), "r"(bytes) : "memory");
}
DEVI void bulk_commit_warp() { asm volatile("{.reg .pred p; elect.sync _|p, 0xffffffff; @p cp.async.bulk.commit_group;}" ::: "memory"); }
#define PUBLISH(S) { asm volatile("cp.async.bulk.wait_group 0;" ::: "memory"); bar_sync(NB_D, 64); stg_rlx(&g_qflag[S][blockIdx.x / 3][c * 8], lds32(sb + R_MISC + M_RING)); }

DEVI void proj_loop(uint32_t (&w)[2][18][4], unsigned char* smem, const uint32_t sb, const uint32_t c, const int wg, const int q, const uint32_t lane0,
                    const uint32_t la) {
    const uint32_t bar = sb + R_BAR;
    const int p = q ^ (2 * wg);
    const bool c2 = c == 2, both = !c2 && p < 2, aq = c2 ? p < 2 : p != 2;
    const uint32_t lp = pin(sb + lane0 * 16 + p * 1024), ma = pin(sb + lane0 * 16 + wg * 1024);
    {
        const uint32_t l16 = sb + lane0 * 16;
        const int ia = c2 ? p & 1 : min(p, 2), vt = c2 ? 4 + p : 2 * c + p - 2;
        const uint32_t dtok = l16 + (wg ? (aq ? R_K - ((c2 ? 2 : 3) - ia) * 1024 : R_K + ia * 1536) : (both ? R_K + p * 1536 : R_V + vt * 1024));
                const bool lo = lane0 < 16, mq = aq && lo, mv = !both && !lo;
        const uint32_t dmem = sb + (mq ? R_QM + ia * 512 + (lane0 & 8) * 32 + wg * 128 : (mv ? R_PV + p * 1024 : R_K + ia * 1536 + 1024) + wg * 256 + (lane0 & 8) * 16) + (lane0 & 7) * 16;
        stsm4(lp + R_T4 + wg * 512, dtok, la, dmem, dmem + (mq || mv ? 0 : PAR));
        const uint32_t p0 = mapa(sb, c2 ? 0 : c + 1), p1 = mapa(sb, c == 0 ? 2 : c - 1), d = R_VM + vt * 256 + lane0 * 4;
        sts128(lp + R_T5 + wg * 512, p0 + d + wg * PAR, p0 + R_BAR + BSC + wg * 8, p1 + d + wg * PAR, p1 + R_BAR + BSC + wg * 8);
        __syncwarp();
        mbar_wait(bar + BX0, 0);
    }
#pragma unroll 1
    for (int s = 0; s < NSEG; s++) {
        const int xi = s - 3 * ((s * 43) >> 7);
        {
            float d[16];
#define TOKEN(WG, T, AT, NB, ZERO)                                                                                          \
    {                                                                                                                       \
    const uint32_t xd = fresh(desc_lo(sb + xi * 36864)), ad = fresh((64u << 16) | (((sb + R_RES) & 0x3FFFF) >> 4));                     \
    wg_fence();                                                                                                             \
    _Pragma("unroll") for (int i = 0; i < 18; i++) {                                                                        \
        if (i == (AT)) bar_arrive(NB, 256);                                                                                 \
        const int j = i < SSP ? i + 2 : (i < SSP + 2 ? i - SSP : i), g = 18 * WG + j;                                              \
        const uint64_t bd = desc_of(xd + (g >> 2) * 256 + (g & 3) * 2);                                                     \
        if (2 * j + (T) < NTR) wgmma32_ss<1>(d, desc_sw32(ad + ((WG * 8192 + (T) * 4096 + j * 512) >> 4)), bd);                          \
        else if (i == 0 && ZERO) wgmma32<0>(d, w[T][j], bd);                                                                \
        else wgmma32<1>(d, w[T][j], bd);                                                                                    \
    }                                                                                                                       \
    wg_commit();                                                                                                            \
    if ((AT) == 18) bar_arrive(NB, 256);                                                                                    \
    }
#define HANDOVER(WG)                                                                                                        \
    {                                                                                                                       \
        const uint32_t xa = lp + R_PX + WG * 4096;                                                                          \
        sts128(xa, pack2(d[0], d[1]), pack2(d[2], d[3]), pack2(d[4], d[5]), pack2(d[6], d[7]));                             \
        sts128(xa + 512, pack2(d[8], d[9]), pack2(d[10], d[11]), pack2(d[12], d[13]), pack2(d[14], d[15]));                 \
    }
            if (wg == 0) {
                bar_sync(NB_G1, 256);
                TOKEN(0, 0, -1, 0, 1)
                const uint32_t la = tab1(lp + R_T4 + 128);
                if (!PE) wg_wait0();
                if (q == 1 && s > 0 && (!ONE || c == 0)) {
                    const uint2 tt = tab2(lp + R_T2 - 1024), rt = lds64(sb + R_MISC + M_PROBE);
                    const uint32_t tag = (lds32(sb + R_MISC + M_EPOCH) * 64 + s) << 22, side = rt.y < rt.x;
                    const uint32_t* const sp = (const uint32_t*)mkptr((tt.x ^ (side << 12)) + acc_slot(s - 1), tt.y);
                    uint32_t v0 = ldg_rlx(sp), v1 = ldg_rlx(sp + 64), v2 = ldg_rlx(sp + 256);
                    if (PE) wg_wait0();
                    bar_sync(NB_E0, 256);
                    HANDOVER(0)
                    bar_arrive(NB_GO, 384);
                    if (!TR0) LOAD_TRANSIENT(la)
                    const uint2 tr = lds64(sb + R_MISC + M_REF);
                    int n = 0;
                    while (__any_sync(0xffffffffu, (diff2(v0, v1, tag) | (v2 ^ tag)) >> 22)) {
                        v0 = ldg_rlx(sp); v1 = ldg_rlx(sp + 64); v2 = ldg_rlx(sp + 256);
                        if (++n > (1 << 22)) TRAP(1002);
                    }
                    const int m = __reduce_max_sync(0xffffffffu, max(max((int)((v0 - tr.y) << 10), (int)((v1 - tr.y) << 10)), (int)((v2 - tr.y) << 10))) >> 10;
                    const uint32_t tn = tr.x + min(m, DMAX) + (CT - 65), tf = tn - (s > 2 ? FE : 0);
                    sts128(sb + R_MISC + M_TGT, side ? tf : tn, s, side ? tn : tf, s);
                    EV(0);
                    if (EVX(0)) { EVV(11, m); EVV(10, tr.x); }
                } else {
                    if (PE) wg_wait0();
                    EV(3);
                    bar_sync(NB_E0, 256);
                    HANDOVER(0)
                    bar_arrive(NB_GO, 384);
                    if (!TR0) LOAD_TRANSIENT(la)
                }
                bar_sync(NB_F0, 256);
                TOKEN(0, 1, F1T, NB_F1, 1)
                const uint32_t dtok = tab1(lp + R_T4) + (s & 1) * PAR;
                bar_sync(NB_H1, 256);
                const uint4 oa = lds128(lp + R_PX + 4096);
                const uint4 ob = lds128(lp + R_PX + 4608);
                wg_wait0();
                const uint32_t u0 = pack2(d[0] + bflo(oa.x), d[1] + bfhi(oa.x)), u1 = pack2(d[2] + bflo(oa.y), d[3] + bfhi(oa.y));
                stsm4(dtok, u0, u1, pack2(d[4] + bflo(oa.z), d[5] + bfhi(oa.z)), pack2(d[6] + bflo(oa.w), d[7] + bfhi(oa.w)));
                stsm4(dtok + 512, pack2(d[8] + bflo(ob.x), d[9] + bfhi(ob.x)), pack2(d[10] + bflo(ob.y), d[11] + bfhi(ob.y)),
                      pack2(d[12] + bflo(ob.z), d[13] + bfhi(ob.z)), pack2(d[14] + bflo(ob.w), d[15] + bfhi(ob.w)));
                bar_arrive(NB_TOK, 384);
                if (TR0) LOAD_TRANSIENT(la)
                mbar_wait(bar + BME, s & 1);
            } else {
                const uint2 tw = tab2(lp + R_T4 + 512);
                bar_sync(NB_GO, 384);
                TOKEN(1, 1, F0T, NB_F0, 1)
                const uint4 oa = lds128(lp + R_PX), ob = lds128(lp + R_PX + 512);
                wg_wait0();
                HANDOVER(1)
                bar_arrive(NB_H1, 256);
                {
                    const uint32_t ox[8] = {oa.x, oa.y, oa.z, oa.w, ob.x, ob.y, ob.z, ob.w};
#pragma unroll
                    for (int j = 0; j < 8; j++) { d[2 * j] = bflo(ox[j]); d[2 * j + 1] = bfhi(ox[j]); }
                }
                if (!TR1) LOAD_TRANSIENT(tw.y)
                bar_sync(NB_F1, 256);
                TOKEN(1, 0, -1, 0, 0)
                if (TR1 == 1) LOAD_TRANSIENT(tw.y)
                if (q == 3 && s > 0) PUBLISH(s - 1)
                if (TR1 == 2) LOAD_TRANSIENT(tw.y)
                const float qs = aq ? QS : 1.f;
                const uint32_t dtok = tw.x + (s & 1) * PAR;
                if (MW == 1) mbar_wait(bar + BME, s & 1);
                uint32_t there = 0;
                if (MW == 2) asm volatile("{.reg .pred p; mbarrier.test_wait.parity.shared::cta.b64 p, [%1], %2; selp.u32 %0, 1, 0, p;}" : "=r"(there) : "r"(bar + BME), "r"(s & 1) : "memory");
                wg_wait0();
                EV(13);
#pragma unroll
                for (int hf = 0; hf < 2; hf++) {
                    const float* e = d + 8 * hf;
                    stsm4(dtok + hf * 512, pack2(e[0] * qs, e[1] * qs), pack2(e[2] * qs, e[3] * qs), pack2(e[4] * qs, e[5] * qs), pack2(e[6] * qs, e[7] * qs));
                }
                EV(12);
                bar_arrive(NB_TOK, 384);
                if (MW != 1 && !there) mbar_wait(bar + BME, s & 1);
            }
#undef TOKEN
#undef HANDOVER
        }
        uint4 b[12];
        float a[4][4];
      redo:
#pragma unroll
        for (int j = 0; j < 4; j++) a[0][j] = a[1][j] = a[2][j] = a[3][j] = 0.f;
#define LD(i) b[i] = ldm128(ma + R_MEM + ((i) >> 1) * 2048 + ((i) & 1) * 512);
#define BK0(k) ((k) % 3 == 2 ? b[(k) / 3 * 2].z : b[(k) / 3 * 2 + (k) % 3].x)
#define BK1(k) ((k) % 3 == 2 ? b[(k) / 3 * 2].w : b[(k) / 3 * 2 + (k) % 3].y)
#define KS(T, k) MMAW(a[2 * (T) + ((k) & 1)], T, k, BK0(k), BK1(k));
        uint32_t chk = 0, dmem;
        uint4 tv;
#pragma unroll
        for (int i = 0; i < 4; i++) LD(i)
#pragma unroll
        for (int k = 0; k < LW; k++) {
            if (k % 3 == 2) { chk = or3(chk, b[k / 3 * 2].w, b[k / 3 * 2 + 1].w); b[k / 3 * 2].w = b[k / 3 * 2 + 1].z | chk; }
            KS(0, k) KS(1, k)
        }
        if (DL) mbar_wait(bar + BML, s & 1);
#pragma unroll
        for (int i = 4; i < 12; i++) LD(i)
        tv = lds128(lp + fresh((s & 1) * 512) + R_T5); dmem = tab1(lp + fresh(wg * 512 + (s & 1) * 128) + R_T4 + 256);
#pragma unroll
        for (int k = LW; k < 18; k++) {
            if (k % 3 == 2) { chk = or3(chk, b[k / 3 * 2].w, b[k / 3 * 2 + 1].w); b[k / 3 * 2].w = b[k / 3 * 2 + 1].z | chk; }
            KS(0, k) KS(1, k)
        }
        float r[4];
        {
            const float s0 = aq ? QS : 1.f;
#pragma unroll
            for (int j = 0; j < 4; j++) { r[j] = a[3][j] + a[2][j]; a[0][j] = fmaf(a[1][j], s0, a[0][j] * s0); }
            stsm4(dmem, pack2(a[0][0], a[0][1]), pack2(a[0][2], a[0][3]), pack2(r[0], r[1]), pack2(r[2], r[3]));
            const uint32_t bad = __any_sync(0xffffffffu, chk);
            asm volatile("{.reg .pred p; setp.eq.u32 p, %0, 0; @p bar.sync %1, 384;}" :: "r"(bad), "n"((int)NB_K) : "memory");
            const uint2 o = tab2(lp + R_PV);
            if (!(bad | (wg ^ 1) | both)) {
                const uint32_t lo = pack2(r[0] + bflo(o.x), r[1] + bfhi(o.x)), hi = pack2(r[2] + bflo(o.y), r[3] + bfhi(o.y)), v2 = (tv.x & 0xffffffu) | (sb & 0xff000000u);
                sta32(tv.x, lo, tv.y); sta32(tv.z, lo, tv.w);
                sta32(tv.x + 128, hi, tv.y); sta32(tv.z + 128, hi, tv.w);
                sts32(v2, lo); sts32(v2 + 128, hi);
            }
            if (__builtin_expect(bad, 0)) goto repair;
        }
#undef LD
#undef KS
#undef BK0
#undef BK1
        if (wg == 0) { EV(1); continue; }
        EV(2);
        {
            if (q != 3) bar_arrive(NB_W1, 256);
            if (q == 3) {
                const uint32_t area = __shfl_sync(0xffffffffu, lds32(sb + R_MISC + M_RING), 0) & 63, so = sb + (s & 1) * PAR;
                unsigned char* const dst = g_qkv + (size_t)(area * 32 + blockIdx.x / 3) * 30720;
                unsigned char* const dk = dst + c * 7680 + (c2 ? 3072 : 4096);
                sts32(sb + R_MISC + M_SINK, clk());
                bar_sync(NB_W1, 256);
                fence_smem_async();
                bulk_s2g_warp(dst + 20480 + c * 2048, so + R_V + c * 2048, c2 ? 4096 : 2048);
                bulk_s2g_warp(dst + 28672 + c * 512, so + R_VM + c * 512, c2 ? 1024 : 512);
                bulk_s2g_warp(dk, so + R_K + 1024, 512);
                bulk_s2g_warp(dk + 1536, so + R_K + 2560, 512);
                if (!c2) bulk_s2g_warp(dk + 3072, so + R_K + 4096, 512);
                bulk_commit_warp();
            } else if (q == 2) {
                const uint4 tz = lds128(lp + R_T0 + 1536);
                const uint32_t pa = sb + R_MISC + M_PROBE + (((blockIdx.x >> 2) ^ s) & 1) * 4, best = lds32(pa);
                char* const zp = mkptr((tz.x ^ ((s & 1) << 12)) + acc_slot(s + 2), tz.y);
                uint32_t z;
                const uint32_t t1 = clk();
                asm volatile("atom.relaxed.gpu.global.exch.b32 %0, [%1], %2;" : "=r"(z) : "l"(zp), "r"(tz.w) : "memory");
                sts32(sb + R_MISC + M_SINK, z);
                sts32(pa, min(best, clk() - t1));
            }
        }
        continue;
      repair:
        {
            if (atomicAdd((unsigned*)(smem + R_MISC + M_PASS), 1) > (1u << 28)) TRAP(1000);
#pragma unroll 1
            for (int i = 0; i < 2; i++) {
                const uint2 tb = tab2(ma + fresh(i * 512 + ((s - 1) & 3) * 2048) + R_T1 + 256);
                const uint32_t md = ma + ((ma ^ (tb.y >> 31)) & 256) + R_MEM + i * 2048;
                const char* const ga = mkptr(tb.x, tb.y);
                cp16(md, ga); cp16(md + 256, ga + 1024); cp16(md + 4096, ga + 2048); cp16(md + 4352, ga + 3072);
                cp16(md + 8192, ga + 2560); cp16(md + 8448, ga + 3584);
            }
            asm volatile("cp.async.wait_all;" ::: "memory");
            __syncwarp();
            const uint32_t la = tab1(lp + fresh(wg * 512) + R_T4 + 128);
            LOAD_TRANSIENT(la)
            goto redo;
        }
    }
    if (wg == 1) PT(18);
    if (wg == 1 && q == 3) PUBLISH(NSEG - 1)
}

DEVI void attn_loop(const uint32_t (&wo)[3][8][4], const CUtensorMap* xmap, const CUtensorMap* amap, unsigned char* smem, const uint32_t sb, const uint32_t c, const int q,
                    const uint32_t lane0) {
    const uint32_t bar = sb + R_BAR;
    const bool c2 = c == 2;
    const uint32_t l16 = pin(sb + lane0 * 16);
{
        const uint4 t = lds128(l16 + q * 512 + R_T0);
        sts128(l16 + q * 512 + R_T6, t.x, t.y, t.z, t.w);
        sts128(l16 + q * 512 + R_T6 + 2048, t.x, t.y + (q < 3 ? 8 : 0), t.z, t.w + 8);
    }
#define UA(x) (l16 + fresh(x))
#define DUMP_QK()                                                                                                             \
    {                                                                                                                         \
        const uint32_t e64 = lds32(sb + R_MISC + M_EPOCH) * 64, so = sb + (s & 1) * PAR + R_K, nq = c2 ? 2048 : 3072;         \
        const uint32_t area = __shfl_sync(0xffffffffu, s & ((uint32_t)lds32(sb + R_MISC + M_DONE) == e64 + s - QR ? QR - 1 : 63), 0); \
        sts32(sb + R_MISC + M_RING, e64 + area);                                                                              \
        unsigned char* const dst = g_qkv + (size_t)(area * 32 + blockIdx.x / 3) * 30720 + c * 7680;                           \
        bulk_s2g_warp(dst, so - nq, nq + 1024);                                                                               \
        bulk_s2g_warp(dst + nq + 1536, so + 1536, 1024);                                                                      \
        if (!c2) bulk_s2g_warp(dst + 6144, so + 3072, 1024);                                                                  \
        bulk_commit_warp();                                                                                                   \
    }
#pragma unroll 1
    for (int s = 0; s < NSEG - 1; s++) {
        const uint32_t par = (s & 1) * PAR;
        uint32_t junk = 0;
        const uint4 ta = lds128(UA(q * 512 + (s & 1) * 2048) + R_T6);
        bar_sync(NB_TOK, 384);
#define SCORES()                                                                                                   \
    float x[2][3][4];                                                                                              \
    _Pragma("unroll") for (int t = 0; t < 3; t++) {                                                                \
        _Pragma("unroll") for (int j = 0; j < 4; j++) x[0][t][j] = x[1][t][j] = 0.f;                               \
        mma16(x[0][t], qf[t][0], qf[t][1], qf[t][2], qf[t][3], kf[t][0], kf[t][1]);                                \
        mma16(x[1][t], qf[t][0], qf[t][1], qf[t][2], qf[t][3], kf[t][2], kf[t][3]);                                \
    }                                                                                                              \
    if (G1T == 0) { PIN(); bar_arrive(NB_G1, 256); PIN(); }                                                        \
    float y[4];                                                                                                    \
    _Pragma("unroll") for (int j = 0; j < 4; j++)                                                                  \
        y[j] = ((x[j >> 1][0][j & 1] + x[j >> 1][0][2 + (j & 1)]) + (x[j >> 1][1][j & 1] + x[j >> 1][1][2 + (j & 1)])) + (x[j >> 1][2][j & 1] + x[j >> 1][2][2 + (j & 1)]);
        if (q < 2) {
            uint32_t qf[3][4], kf[3][4];
#pragma unroll
            for (int t = 0; t < 3; t++) ldsm4t(kf[t], UA(q * 512 + par) + R_K + t * 1536);
            bar_sync(NB_K, 384);
#pragma unroll
            for (int t = 0; t < 3; t++) ldsm4t(qf[t], l16 + R_QM + t * 512);
            SCORES()
            const uint32_t u0 = pack2(y[0], y[1]), u1 = pack2(y[2], y[3]);
            sta32(ta.x, u0, ta.y); sta32(ta.z, u0, ta.w);
            sta32(ta.x + 128, u1, ta.y); sta32(ta.z + 128, u1, ta.w);
            stsm2(UA(q * 256) + R_SC, u0, u1);
            if (G1T == 1) bar_arrive(NB_G1, 256);
        } else if (q == 2) {
            if (s > 0 && s + 2 < NSEG) {
                const int xi = s - 1 - 3 * (((s - 1) * 43) >> 7);
                mbar_wait(bar + BME, s & 1);
                spin_until(clk() + XD);
                asm volatile("{.reg .pred p; elect.sync _|p, 0xffffffff;\n"
                             "@p mbarrier.arrive.expect_tx.shared::cta.b64 _, [%2], 36864;\n"
                             "@p cp.async.bulk.tensor.3d.shared::cluster.global.mbarrier::complete_tx::bytes.multicast::cluster [%0], [%1, {%3, %4, %5}], [%2], %6;}"
                             :: "r"(sb + xi * 36864 + c * 12288), "l"(xmap), "r"(bar + BX0 + xi * 8), "r"(0), "r"((s + 2) * 32), "r"(c * 3), "h"((uint16_t)7) : "memory");
            }
            uint32_t qf[3][4], kf[3][4];
            bar_sync(NB_K, 384);
#pragma unroll
            for (int t = 0; t < 3; t++) { ldsm4t(qf[t], l16 + R_QM + t * 512); ldsm4t(kf[t], UA(q * 512 + par) + R_K + t * 1536); }
            SCORES()
            const uint32_t u0 = pack2(y[0] + y[2], y[1] + y[3]);
            sta32(ta.x, u0, ta.y);
            sta32(ta.z, u0, ta.w);
            EV(4);
            stsm2(l16 + R_SC + 1792, u0, u0);
            if (G1T == 1) bar_arrive(NB_G1, 256);
        } else {
            {
                const uint32_t vt = R_V + par + c * 2048, p0 = mapa(sb, c2 ? 0 : c + 1), p1 = mapa(sb, c == 0 ? 2 : c - 1);
                fence_smem_async();
                bulk_s2c_warp(p0 + vt, sb + vt, c2 ? 4096 : 2048, p0 + R_BAR + BSC + (s & 1) * 8);
                bulk_s2c_warp(p1 + vt, sb + vt, c2 ? 4096 : 2048, p1 + R_BAR + BSC + (s & 1) * 8);
            }
            DUMP_QK()
            {
                const int s3 = ((s + 1) * 43) >> 7;
                mbar_wait(bar + BX0 + (s + 1 - 3 * s3) * 8, s3 & 1);
                if (G1T < 2) bar_arrive(NB_G1, 256);
            }
            const uint32_t tag = (lds32(sb + R_MISC + M_EPOCH) * 64 + s + 1) << 22;
            sts32(sb + R_MISC + M_REF + 4, clock_offset());
            bar_sync(NB_K, 384);
            const uint32_t off = lds32(sb + R_MISC + M_REF + 4);
            const uint32_t t = off == 0x9e3779b9u ? 0u : clk();
            sts64(sb + R_MISC + M_REF, t, t + off);
            stg_rlx((uint32_t*)mkptr(ta.z + acc_slot(s), ta.y), ((t + off) & 0x3fffffu) | tag);
        }
#undef SCORES
        bar_sync(NB_W1, 256);
        uint32_t vf[4][4];
        const uint32_t vo = par + q * 2048;
        float o0[4], o1[4], sum;
        {
            uint32_t aw[5], bw[5], cw[5];
            ldsm4(aw, l16 + R_SC); aw[4] = tab1(l16 + R_SC + 1792);
            if (G1T == 2) { bar_arrive(NB_G1, 256); PIN(); }
            sts32(sb + R_MISC + M_SINK, or3(aw[0], aw[4], junk));
            mbar_wait(bar + BSC + (s & 1) * 8, (s >> 1) & 1);
            ldsm4(bw, l16 + R_SC + 512); ldsm4(cw, l16 + R_SC + 1024);
            { const uint2 t = tab2(l16 + R_SC + 1536); bw[4] = t.x; cw[4] = t.y; }
            junk = clk();
            ldsm4(vf[0], UA(vo) + R_V); ldsm4(vf[2], UA(vo) + R_V + 1024);
            PIN();
            EV(5);
            float x[10];
#pragma unroll
            for (int i = 0; i < 5; i++) { x[2 * i] = (bflo(aw[i]) + bflo(bw[i])) + bflo(cw[i]); x[2 * i + 1] = (bfhi(aw[i]) + bfhi(bw[i])) + bfhi(cw[i]); }
            float mx = fmaxf(fmaxf(fmaxf(fmaxf(x[0], x[1]), fmaxf(x[2], x[3])), fmaxf(fmaxf(x[4], x[5]), fmaxf(x[6], x[7]))), fmaxf(x[8], x[9]));
            const float m1 = __shfl_xor_sync(0xffffffffu, mx, 1), m2 = __shfl_xor_sync(0xffffffffu, mx, 2), m3 = __shfl_xor_sync(0xffffffffu, mx, 3);
            uint32_t vm[4];
            PIN();
            ldsm4(vf[1], UA(vo) + R_V + 512); ldsm4(vf[3], UA(vo) + R_V + 1536); ldsm4(vm, UA(q * 512 + par) + R_VM);
            bar_arrive(NB_E0, 256);
            PIN();
            mx = fmaxf(fmaxf(mx, m1), fmaxf(m2, m3));
            float e[10];
#pragma unroll
            for (int j = 0; j < 4; j++) o0[j] = o1[j] = 0.f;
#pragma unroll
            for (int i = 0; i < 10; i++) x[i] -= mx;
#pragma unroll
            for (int i = 0; i < 7; i++) { if (i == 4) PIN(); e[i] = ex2v(x[i]); }
            const uint32_t p0 = pack2(e[0], e[1]), p1 = pack2(e[2], e[3]);
            mma16(o0, vf[0][0], vf[0][1], vf[0][2], vf[0][3], p0, p1);
            mma16(o1, vf[2][0], vf[2][1], vf[2][2], vf[2][3], p0, p1);
#pragma unroll
            for (int i = 7; i < 10; i++) { if (i == 8) PIN(); e[i] = ex2v(x[i]); }
            PIN();
            const uint32_t p2 = pack2(e[4], e[5]), p3 = pack2(e[6], e[7]), p4 = pack2(e[8], e[9]);
            mma16(o0, vf[1][0], vf[1][1], vf[1][2], vf[1][3], p2, p3);
            mma16(o1, vf[3][0], vf[3][1], vf[3][2], vf[3][3], p2, p3);
            mma8(o0, vm[0], vm[1], p4);
            mma8(o1, vm[2], vm[3], p4);
            sum = (((e[0] + e[1]) + (e[2] + e[3])) + ((e[4] + e[5]) + (e[6] + e[7]))) + (e[8] + e[9]);
        }
        asm volatile("stmatrix.sync.aligned.m8n8.x1.shared.b16 [%0], {%1};" :: "r"(l16 + R_Z), "r"(__float_as_uint(sum)) : "memory");
        const uint32_t ls = (fresh(l16) & 48) * 2 + sb;
        const float4 s0 = lds128f(ls + R_Z), s1 = lds128f(ls + R_Z + 16);
        stsm4(UA(q * 512) + R_O8, pack2(o0[0], o0[1]), pack2(o0[2], o0[3]), pack2(o1[0], o1[1]), pack2(o1[2], o1[3]));
        EV(6);
        bar_sync(NB_W2, 128);
        uint32_t of[4][4];
        ldsm4t(of[0], l16 + R_O8);
        PIN();
#pragma unroll
        for (int i = 1; i < 4; i++) ldsm4t(of[i], l16 + R_O8 + i * 512);
        PIN();
        const float f0 = rcp_fast((s0.x + s0.y) + (s0.z + s0.w)), f1 = rcp_fast((s1.x + s1.y) + (s1.z + s1.w));
        float acc[3][2][4];
        uint2 tb;
#pragma unroll
        for (int m = 0; m < 3; m++)
#pragma unroll
            for (int j = 0; j < 4; j++) acc[m][0][j] = acc[m][1][j] = 0.f;
#pragma unroll
        for (int i = 0; i < 24; i++) {
            const int kk = i / 3, m = i % 3;
            if (i % 3 == 0 && i) PIN();
            if (i == 12) tb = tab2(UA(q * 512 + (s & 3) * 2048) + R_T1);
            if (i == GOE) { if (i % 3) PIN(); bar_arrive(NB_GO, 384); PIN(); }
            mma16(acc[m][kk & 1], wo[m][kk][0], wo[m][kk][1], wo[m][kk][2], wo[m][kk][3], of[kk >> 1][(kk & 1) * 2], of[kk >> 1][(kk & 1) * 2 + 1]);
        }
        PIN();
        if (GOE == 24) { bar_arrive(NB_GO, 384); PIN(); }
        char* const gw = mkptr(tb.x, tb.y);
        uint32_t wa[3], wb[3];
#pragma unroll
        for (int m = 0; m < 3; m++) {
            wa[m] = pack2(fmaf(acc[m][1][0], f0, acc[m][0][0] * f0), fmaf(acc[m][1][2], f0, acc[m][0][2] * f0));
            wb[m] = pack2(fmaf(acc[m][1][1], f1, acc[m][0][1] * f1), fmaf(acc[m][1][3], f1, acc[m][0][3] * f1));
        }
        red_b8(gw, wa[0], wa[1], wa[2], 0x3f80u); red_b8(gw + 1024, wb[0], wb[1], wb[2], 0x3f80u);
        if (GOE > 24) bar_arrive(NB_GO, 384);
        sts32(sb + R_MISC + M_SINK, junk);
        const uint32_t t0 = clk();
        if (EVX(0)) EVV(7, t0);
        if (q < 2) {
          if (!ONE || c == 0) {
            uint2 tg = lds64(sb + R_MISC + M_TGT + q * 8);
            for (int n = 0; tg.y != s + 1; tg = lds64(sb + R_MISC + M_TGT + q * 8)) if (++n > (1 << 26)) TRAP(1003);
            fine_until(t0 + max((int)(tg.x - t0), DMIN) + (c ? DL : 0));
#pragma unroll
            for (uint32_t j = ONE ? 0 : c; j < (ONE ? 3 : c + 1); j++)
            asm volatile("{.reg .pred p; elect.sync _|p, 0xffffffff;\n"
                         "@p cp.async.bulk.tensor.5d.shared::cluster.global.mbarrier::complete_tx::bytes.multicast::cluster [%0], [%1, {%3, %4, %4, %4, %5}], [%2], %6;}"
                         :: "r"(sb + R_MEM + j * 4096 + q * 2048), "l"(amap + q), "r"(bar + (DL && j ? BML : BME)), "r"((s & 1) * 64), "r"(0), "r"((s & 2) * 64 + (j ? 6 + 2 * j : 0)), "h"((uint16_t)7) : "memory");
            EV(8);
          }
        } else if (q == 2) {
            if (l16 == sb) {
                cp16(sb + R_MISC + M_DONE, &g_oflag[max(s + 1 - QR, 0)][blockIdx.x / 3][0]);
                mbar_expect(bar + BME, DL ? 4096 : 12288);
                if (DL) mbar_expect(bar + BML, 8192);
                mbar_expect(bar + BSC + 8 - (s & 1) * 8, (c2 ? 1024 : 1536) * (s < NSEG - 2 ? 5 : 1) + (s < NSEG - 2 ? 1280 : 0));
            }
        } else {
            asm volatile("cp.async.bulk.wait_group 0;" ::: "memory");
            bar_arrive(NB_D, 64);
        }
    }
    bar_sync(NB_TOK, 384);
    if (q == 3) {
        const int s = NSEG - 1;
        fence_smem_async();
        DUMP_QK()
    }
    bar_arrive(NB_K, 384);
    bar_arrive(NB_W1, 256);
    if (q == 3) {
        asm volatile("cp.async.bulk.wait_group 0;" ::: "memory");
        bar_arrive(NB_D, 64);
    }
    mbar_wait(bar + BSC + 8, 1);
}

struct Maps { CUtensorMap x, acc[2], w16[3], w32[3], wo; };
DEVI void tma2d(uint32_t dst, const CUtensorMap* m, uint32_t bar, int x, int y) {
    asm volatile("{.reg .pred p; elect.sync _|p, 0xffffffff;\n"
                 "@p cp.async.bulk.tensor.2d.shared::cluster.global.mbarrier::complete_tx::bytes [%0], [%1, {%3, %4}], [%2];}"
                 :: "r"(dst), "l"(m), "r"(bar), "r"(x), "r"(y) : "memory");
}

__global__ void __launch_bounds__(384, 1)
rk_kernel(const __grid_constant__ Maps maps, const __nv_bfloat16* __restrict__ xraw, const __nv_bfloat16* __restrict__ mem0) {
    extern __shared__ __align__(1024) unsigned char smem[];
    const uint32_t sb = smem_u32(smem);
    const int tid = threadIdx.x;
    const int warp = __shfl_sync(0xffffffffu, tid >> 5, 0), q = warp & 3;
    const int h = blockIdx.x / 3;
    const uint32_t c = blockIdx.x - 3 * h;
    const uint32_t bar = sb + R_BAR;
    GT(0, 0);
    if (tid >= 64 && tid < 74) asm volatile("prefetch.tensormap [%0];" :: "l"(&maps.x + (tid - 64)) : "memory");
    if (tid < 18) { mbar_init(bar + BW + tid * 8, 1); mbar_expect(bar + BW + tid * 8, tid >= 10 ? 6144 : (tid % 5 == 4 ? 8192 : 16384)); }
    if (tid == 32) {
        for (int i = 0; i < 3; i++) { mbar_init(bar + BX0 + i * 8, 1); mbar_expect(bar + BX0 + i * 8, 36864); }
        mbar_init(bar + BSC, 1); mbar_init(bar + BSC + 8, 1); mbar_init(bar + BME, 1); mbar_init(bar + BML, 1); mbar_arrive(bar + BME); mbar_arrive(bar + BML);
        mbar_expect(bar + BSC, c == 2 ? 6400 : 8960);
        asm volatile("fence.mbarrier_init.release.cluster;" ::: "memory");
    }
    if (warp < 2) fence_smem_async();
    __syncthreads();
    asm volatile("griddepcontrol.launch_dependents;");

    if (warp < 8) {
        const int wg = warp >> 2, p = q ^ (2 * wg);
        const uint32_t bw = bar + BW + wg * 40, st = sb + R_STAGE + wg * 65536;
        const int f2 = h * 128 + (c == 2 ? 96 : c * 64), f1 = h * 128 + 32 + c * 16, fv = h * 128 + c * 32;
        const bool single = c != 2 && p >= 2;
        if (wg == 0) PT(1);
#pragma unroll 1
        for (int i = 0; i < 4; i++) {
            const uint32_t dst = st + i * 16384 + q * 4096;
            const int row = wg * 288 + 32 + i * 64;
            if (q < 3 || c == 2) tma2d(dst, maps.w32 + min(q, 2), bw + i * 8, q < 2 ? f2 : fv + (q - 2) * 32, row);
            else {
#pragma unroll 1
                for (int j = 0; j < 4; j++) tma2d(dst + j * 1024, maps.w16 + (j < 2), bw + i * 8, f1, row + (j & 1) * 32);
            }
        }
        tma2d(sb + R_RES + wg * 8192 + q * 1024, maps.w16 + (c == 2 ? p >> 1 : p == 2), bw + 32, single ? f1 : f2 + (p & 1) * 16, wg * 288);
        tma2d(sb + R_RES + wg * 8192 + q * 1024 + 4096, maps.w16 + (c == 2 || p >= 2 ? 2 : 1), bw + 32, c == 2 ? fv + p * 16 : (p >= 2 ? fv : f2) + (p & 1) * 16, wg * 288);
        if (wg == 0) PT(0);
        asm volatile("setmaxnreg.inc.sync.aligned.u32 %0;" :: "n"(RP));
        const uint32_t lane = pin(tid & 31);
        uint32_t w[2][18][4];
        const uint32_t row = ((lane >> 4) << 3) + (lane & 7), ln = row * 32 + ((((lane >> 3) ^ (lane >> 2)) & 1) << 4);
        const uint32_t la = sb + R_RES + wg * 8192 + q * 1024 + ln;
        {
            const uint32_t lw = row * 64 + ((((p & 1) * 2 + ((lane >> 3) & 1)) ^ ((lane >> 1) & 3)) << 4);
            const uint32_t a0 = st + (single ? 12288 + (p & 1) * 2048 + ln : (c == 2 ? p >> 1 : 0) * 4096 + lw), s0 = single ? 512 : 1024;
            const uint32_t a1 = st + ((c == 2 ? 2 : 1) + (p >> 1)) * 4096 + lw;
#pragma unroll
            for (int i = 0; i < 4; i++) {
                mbar_wait(bw + i * 8, 0);
                if (wg == 0 && (i & 1)) PT(2 + i / 2);
#pragma unroll
                for (int j = 0; j < 4; j++) { ldsm4t(w[0][2 + i * 4 + j], a0 + j * s0 + i * 16384); ldsm4t(w[1][2 + i * 4 + j], a1 + j * 1024 + i * 16384); }
            }
            mbar_wait(bw + 32, 0);
            if (wg == 0) PT(4);
#pragma unroll
            for (int j = 0; j < 4; j++) ldsm4t(w[j >> 1][j & 1], la + (j >> 1) * 4096 + (j & 1) * 512);
        }
        bar_sync(0, 384);
        cluster_arrive_rlx();
        GT(0, 1);
        if (c == 2) sts128(sb + (q == 3 ? R_QM + 1024 : R_K + 3072 + q * 512 + wg * PAR) + lane * 16, 0, 0, 0, 0);
        cluster_wait();
        proj_loop(w, smem, sb, c, wg, q, lane, la);
    } else {
        asm volatile("setmaxnreg.dec.sync.aligned.u32 %0;" :: "n"(504 - 2 * RP));
        const uint32_t jw = (c + 3 - q % 3) % 3, bw = bar + BW + 80 + q * 16;
        const int wx = (q >> 1) * 288 + jw * 96 + (q & 1) * 48;
        const uint32_t lane0 = pin(tid & 31);
        const uint32_t lane = lane0, n = blockIdx.x;
        volatile uint32_t* const misc = (volatile uint32_t*)(smem + R_MISC);
        uint32_t z;
        asm volatile("atom.relaxed.gpu.global.exch.b32 %0, [%1], %2;" : "=r"(z) : "l"((char*)g_acc + acc_slot(q) + acc_line(n >> 4, (n >> 2) & 3, n & 3) + lane * 4), "r"((lane & 3) == 3 ? EMPTY : 0) : "memory");
        const unsigned epoch = g_epoch[36 + n] + 1;
        {
            uint32_t m0[3][6];
#pragma unroll
            for (int i = 0; i < 18; i++) m0[i / 6][i % 6] = __ldg((const uint32_t*)mem0 + (lane >> 2) * 288 + (q * 18 + i) * 4 + (lane & 3));
            if (q < 3)
                asm volatile("{.reg .pred p; elect.sync _|p, 0xffffffff;\n"
                             "@p cp.async.bulk.tensor.3d.shared::cluster.global.mbarrier::complete_tx::bytes [%0], [%1, {%3, %3, %4}], [%2];}"
                             :: "r"(sb + R_X0 + q * 12288), "l"(&maps.x), "r"(bar + BX0), "r"(0), "r"(q * 3) : "memory");
            tma2d(sb + R_WO + q * 6144, &maps.wo, bw, wx, h * 128);
            asm volatile("{.reg .pred p; elect.sync _|p, 0xffffffff; @p cp.async.bulk.prefetch.tensor.2d.L2.global [%0, {%1, %2}];}" :: "l"(&maps.wo), "r"(wx), "r"(h * 128 + 64) : "memory");
            PT(5);
            const uint32_t a = sb + R_MEM + (q & 1) * 6144 + (q >> 1) * 1024 + lane * 16;
#pragma unroll
            for (int i = 0; i < 6; i++) sts128(a + (i >> 1) * 2048 + (i & 1) * 512, m0[i >> 1][(i & 1) * 2], m0[i >> 1][(i & 1) * 2 + 1], m0[i >> 1][4 + (i & 1)], z & (lane >> 5));
        }
        bar_sync(NB_W2, 128);
        if (tid == 256) {
            stg_rlx(&g_pub[n], epoch);
            g_epoch[36 + n] = epoch;
             misc[M_PASS / 4] = 0; misc[M_TGT / 4 + 1] = 0; misc[M_TGT / 4 + 3] = 0; misc[M_PROBE / 4] = misc[M_PROBE / 4 + 1] = 0xffffffffu;
            misc[M_EPOCH / 4] = epoch; misc[M_DONE / 4] = 0xffffffffu;
        }
        __syncwarp();
        PT(6);
        {
            const uint32_t l16 = sb + lane * 16, gl = (uint32_t)(uint64_t)(void*)g_acc, gh = (uint32_t)((uint64_t)(void*)g_acc >> 32);
            const uint32_t p0 = mapa(sb, c == 2 ? 0 : c + 1), p1 = mapa(sb, c == 0 ? 2 : c - 1), so = R_SC + lane * 4;
            if (q < 3) sts128(l16 + R_T0 + q * 512, p0 + so + (q == 2 ? 1536 : 512 + q * 256), p0 + R_BAR + BSC, p1 + so + (q == 2 ? 1664 : 1024 + q * 256), p1 + R_BAR + BSC);
            else {
                sts128(l16 + R_T0 + q * 512, gl + acc_line(n >> 4, (n >> 2) & 3, n & 3) + lane * 4, gh, gl + acc_stamp(lane & 1, n), (lane & 3) == 3 ? EMPTY : 0);
                stsm2(l16 + R_T2, gl + acc_stamp(0, lane), gh);
            }
            for (int i = 0; i < 4; i++)
                stsm4(l16 + R_T1 + i * 2048 + q * 512, gl + acc_slot(i) + acc_line(2 * jw, q, (lane >> 4) * 2 + ((lane >> 1) & 1)) + ((lane & 1) * 4 + ((lane >> 2) & 3)) * 16, gh,
                       gl + acc_slot(i) + acc_line(0, q, lane >> 3) + (lane & 7) * 16, gh);
            __syncwarp();
        }
        uint32_t wo[3][8][4];
#pragma unroll
        for (int hf = 0; hf < 2; hf++) {
            const uint32_t g = lane >> 2, a = sb + R_WO + q * 6144 + (lane & 3) * 192 + (g & 3) * 4;
            mbar_wait(bw + hf * 8, 0);
#pragma unroll
            for (int m = 0; m < 3; m++)
#pragma unroll
                for (int kk = 0; kk < 8; kk++) {
                    const uint32_t ch = (m < 2 ? (g >> 2) * 2 + m : 4 + (g >> 2)) * 16;
                    const uint32_t x = lds32(a + ch + kk * 768), y = lds32(a + ch + kk * 768 + 96);
                    wo[m][hf * 4 + (kk >> 1)][(kk & 1) * 2] = __byte_perm(x, y, 0x5410);
                    wo[m][hf * 4 + (kk >> 1)][(kk & 1) * 2 + 1] = __byte_perm(x, y, 0x7632);
                }
            if (hf == 0) {
                fence_smem_async();
                __syncwarp();
                tma2d(sb + R_WO + q * 6144, &maps.wo, bw + 8, wx, h * 128 + 64);
                PT(7);
                if (q == 3) {
                    int it = 0;
                    while (!__all_sync(0xffffffffu, ldg_rlx(&g_pub[lane]) == epoch && ldg_rlx(&g_pub[32 + lane]) == epoch && ldg_rlx(&g_pub[64 + lane]) == epoch))
                        if (++it > (1 << 22)) TRAP(2000 + __LINE__);
                }
            }
        }
        PT(8);
        bar_sync(0, 384);
        bar_arrive(NB_G1, 256);
        bar_arrive(NB_E0, 256);
        bar_arrive(NB_GO, 384);
        cluster_arrive_rlx(); cluster_wait();
        PT(9);
        if (q >= 2 && lane == 0) {
            fence_smem_async();
            x_tma(sb + (q - 1) * 36864 + c * 12288, &maps.x, bar + BX0 + (q - 1) * 8, (q - 1) * 32, c * 3);
        }
        if (q == 1 && lane == 0) asm volatile("cp.async.bulk.prefetch.L2.global [%0], 24576;" :: "l"((const char*)xraw + n * 24576) : "memory");
        __syncwarp();
        PT(10);
        attn_loop(wo, &maps.x, maps.acc, smem, sb, c, q, lane0);
    }
    cluster_arrive_rlx(); cluster_wait();
    GT(0, 2);
}

constexpr int H_USTR = 32 * 144 + 16;
constexpr int H_U = 0;
constexpr int H_Z = H_U + 16 * H_USTR;
constexpr int H_W = 74752;
constexpr int H_WSTR = (2048 + 64) * 4;
constexpr int H_PAR = H_W + 8 * H_WSTR;
constexpr int H_KD = H_PAR + 8 * 2048;
constexpr int H_S4END = H_KD + 8 * 648 * 4;
constexpr int NST = 6;
constexpr int H_RING = H_W;
constexpr int H_QKV = 180224;
constexpr int H_AO = H_QKV + 30720;
constexpr int H_BAR = H_AO + 8192;
constexpr int H_SMEM = H_BAR + 512;
static_assert(H_Z + 256 <= H_W && H_S4END <= H_QKV && H_RING + NST * 16384 <= H_QKV && H_SMEM <= 232448 && H_RING % 1024 == 0, "smem");
enum { HB_FULL = 0  , HB_EMPTY = 64  , HB_QF = 256, HB_VF = 264, HB_QE = 272, HB_VE = 280, HB_OF = 288, HB_OE = 296 };
enum { HN_U = 1, HN_Y = 2, HN_P = 3  , HN_G = 5   };

DEVI int slot_channel(int i) { return ((i >> 1) & 3) * 4 + (i >> 3) * 2 + (i & 1); }
#define LOAD_U(W)                                                                                                                      \
    _Pragma("unroll 1") for (int i0 = 0; i0 < 32; i0 += 4) {                                                                            \
        uint2 v[4][2];                                                                                                                  \
        _Pragma("unroll") for (int i = 0; i < 8; i++)                                                                                   \
            v[i >> 1][i & 1] = __ldg((const uint2*)(u + (size_t)(((W) * 32 + i0) * 16 + i * 8 + g) * DM + d0 + tq * 4));                \
        _Pragma("unroll") for (int i = 0; i < 4; i++) {                                                                                 \
            const int t0 = ((W) * 32 + i0 + i) * 16;                                                                                    \
            asm volatile("stmatrix.sync.aligned.m8n8.x4.trans.shared.b16 [%0], {%1,%2,%3,%4};"                                          \
                         :: "r"(sb + H_U + (lane & 15) * H_USTR + (t0 >> 6) * 144 + (t0 & 63) * 2 + (lane >> 4) * 16),                  \
                            "r"(v[i][0].x), "r"(v[i][0].y), "r"(v[i][1].x), "r"(v[i][1].y) : "memory");                                 \
        }                                                                                                                               \
    }
DEVI uint64_t desc_plain(uint32_t saddr, uint32_t lbo, uint32_t sbo) { return ((uint64_t)(sbo >> 4) << 32) | ((uint64_t)(lbo >> 4) << 16) | (uint64_t)((saddr & 0x3FFFF) >> 4); }
template <int ACC> DEVI void wgmma48_tt(float* d, uint64_t adesc, uint64_t bdesc) {
    asm volatile("wgmma.mma_async.sync.aligned.m64n48k16.f32.bf16.bf16 "
                 "{%0,%1,%2,%3,%4,%5,%6,%7,%8,%9,%10,%11,%12,%13,%14,%15,%16,%17,%18,%19,%20,%21,%22,%23}, %24, %25, %26, 1, 1, 1, 1;"
                 : "+f"(d[0]), "+f"(d[1]), "+f"(d[2]), "+f"(d[3]), "+f"(d[4]), "+f"(d[5]), "+f"(d[6]), "+f"(d[7]),
                   "+f"(d[8]), "+f"(d[9]), "+f"(d[10]), "+f"(d[11]), "+f"(d[12]), "+f"(d[13]), "+f"(d[14]), "+f"(d[15]),
                   "+f"(d[16]), "+f"(d[17]), "+f"(d[18]), "+f"(d[19]), "+f"(d[20]), "+f"(d[21]), "+f"(d[22]), "+f"(d[23])
                 : "l"(adesc), "l"(bdesc), "n"(ACC));
}
template <int ACC> DEVI void wgmma64(float* d, const uint32_t* a, uint64_t desc) {
    asm volatile("wgmma.mma_async.sync.aligned.m64n64k16.f32.bf16.bf16 "
                 "{%0,%1,%2,%3,%4,%5,%6,%7,%8,%9,%10,%11,%12,%13,%14,%15,%16,%17,%18,%19,%20,%21,%22,%23,%24,%25,%26,%27,%28,%29,%30,%31}, {%32,%33,%34,%35}, %36, %37, 1, 1, 0;"
                 : "+f"(d[0]), "+f"(d[1]), "+f"(d[2]), "+f"(d[3]), "+f"(d[4]), "+f"(d[5]), "+f"(d[6]), "+f"(d[7]),
                   "+f"(d[8]), "+f"(d[9]), "+f"(d[10]), "+f"(d[11]), "+f"(d[12]), "+f"(d[13]), "+f"(d[14]), "+f"(d[15]),
                   "+f"(d[16]), "+f"(d[17]), "+f"(d[18]), "+f"(d[19]), "+f"(d[20]), "+f"(d[21]), "+f"(d[22]), "+f"(d[23]),
                   "+f"(d[24]), "+f"(d[25]), "+f"(d[26]), "+f"(d[27]), "+f"(d[28]), "+f"(d[29]), "+f"(d[30]), "+f"(d[31])
                 : "r"(a[0]), "r"(a[1]), "r"(a[2]), "r"(a[3]), "l"(desc), "n"(ACC));
}
DEVI uint2 ldg_rlx2(const void* p) { uint2 v; asm volatile("ld.relaxed.gpu.global.v2.u32 {%0,%1}, [%2];" : "=r"(v.x), "=r"(v.y) : "l"(p) : "memory"); return v; }
DEVI unsigned ldg_acq(const unsigned* p) { unsigned v; asm volatile("ld.acquire.gpu.global.u32 %0, [%1];" : "=r"(v) : "l"(p) : "memory"); return v; }
DEVI void csq(float& x, float& y) { const float a = fmaf(x, x, -y * y), b = 2.f * x * y; x = a; y = b; }
DEVI uint32_t tf(float x) { return __float_as_uint(x); }
constexpr float TFC = 1.f + 6.77e-4f;
DEVI void cexp_turns(float l2mag, float turns, float& x, float& y) {
    const float m = ex2(l2mag), a = (turns - rintf(turns)) * 6.283185307179586f;
    x = m * __cosf(a); y = m * __sinf(a);
}

__global__ void __launch_bounds__(512, 1)
hk_kernel(const __nv_bfloat16* __restrict__ Wo, const __nv_bfloat16* __restrict__ u,
          const __nv_bfloat16* __restrict__ logA, const __nv_bfloat16* __restrict__ Aim, const __nv_bfloat16* __restrict__ Cre,
          const __nv_bfloat16* __restrict__ Cim, const __nv_bfloat16* __restrict__ logdt, const __nv_bfloat16* __restrict__ Dsk,
          __nv_bfloat16* __restrict__ out) {
    extern __shared__ __align__(1024) unsigned char smem[];
    const uint32_t sb = smem_u32(smem);
    const int tid = threadIdx.x, lane = tid & 31, warp = __shfl_sync(0xffffffffu, tid >> 5, 0), g = lane >> 2, tq = lane & 3;
    const int cta = blockIdx.x;
    const bool shared = cta < 32;
    const uint32_t bar = sb + H_BAR;
    const int d0 = cta * 16;
    const uint32_t tstart = clk();
    if (tid == 0) {
        for (int i = 0; i < NST; i++) { mbar_init(bar + HB_FULL + i * 8, 1); mbar_init(bar + HB_EMPTY + i * 8, shared ? 8 : 4); }
        mbar_init(bar + HB_QF, 1); mbar_init(bar + HB_VF, 1); mbar_init(bar + HB_QE, 4); mbar_init(bar + HB_VE, 4); mbar_init(bar + HB_OF, 4); mbar_init(bar + HB_OE, 1);
        asm volatile("fence.proxy.async.shared::cta;" ::: "memory");
    }
    const unsigned epoch = g_epoch[cta] + 1;
    __syncthreads();
    if (tid == 0) g_epoch[cta] = epoch;
    if (warp < 8) {
        asm volatile("setmaxnreg.inc.sync.aligned.u32 176;");
        HEV(0); GT(96, 0);
        const int pr = warp & 3, wb = warp >> 2;
        float4* const par = (float4*)(smem + H_PAR + warp * 2048);
        float* const kd = (float*)(smem + H_KD + warp * 648 * 4);
        uint32_t* const wz = (uint32_t*)(smem + H_W + warp * H_WSTR);
        wz[lane] = 0; wz[32 + lane] = 0;
        if (lane < 16) {
            const __nv_bfloat16* const pp = (lane & 3) == 0 ? logA : (lane & 3) == 1 ? Aim : (lane & 3) == 2 ? Cre : Cim;
            asm volatile("prefetch.global.L2 [%0];" :: "l"(pp + (d0 + warp * 2) * 128 + (lane >> 2) * 64));
        }
        HEV(1);
        if (!(HM & 1)) bar_sync(HN_U + wb * 8, 256);
#pragma unroll 1
        for (int it = 0; it < ((HM & 1) ? 2 + wb : 0); it++) {
            const int ch = (it ? 2 * it - wb : 0) * 4 + pr, d = d0 + slot_channel(ch);
            const float dt = bf2f(__float2bfloat16(expf(bf2f(logdt[d]))));
            const uint32_t dsk = ((const uint16_t*)Dsk)[d];
#pragma unroll
            for (int n = lane; n < 128; n += 32) {
                const float ar = -bf2f(__float2bfloat16(expf(bf2f(logA[d * 128 + n])))) * dt, ai = bf2f(Aim[d * 128 + n]) * dt;
                par[n] = make_float4(ar * 1.4426950408889634f, ai * 0.15915494309189535f, 2.f * TFC * (bf2f(Cre[d * 128 + n]) * dt), 2.f * TFC * (bf2f(Cim[d * 128 + n]) * dt));
            }
            __syncwarp();
            {
                float kacc[5][4], klast = 0.f;
#pragma unroll
                for (int i = 0; i < 5; i++) kacc[i][0] = kacc[i][1] = kacc[i][2] = kacc[i][3] = 0.f;
                const float fa = (float)g, fb = (float)(g + 8);
                const int k0 = it ? 0 : wb * 4, k1 = it ? 8 : k0 + 4;
                float4 pn[4];
#pragma unroll
                for (int i = 0; i < 4; i++) pn[i] = par[16 * k0 + 4 * i + tq];
#pragma unroll 1
                for (int k4 = k0; k4 < k1; k4++) {
#pragma unroll
                    for (int ks = 0; ks < 4; ks++) {
                        const float4 p = pn[ks];
                        pn[ks] = par[(16 * k4 + 4 * ks + 16 + tq) & 127];
                        float ax, ay, bx, by;
                        cexp_turns(p.x * fa, p.y * fa, ax, ay);
                        cexp_turns(p.x * fb, p.y * fb, bx, by);
                        uint32_t F[4][4];
#pragma unroll
                        for (int r = 0; r < 4; r++) {
                            F[r][0] = tf(ax); F[r][1] = tf(bx); F[r][2] = tf(ay); F[r][3] = tf(by);
                            csq(ax, ay); csq(bx, by);
                        }
                        mma_tf32(kacc[0], F[0][0], F[0][1], F[0][2], F[0][3], tf(fmaf(p.z, ax, -p.w * ay)), tf(fmaf(-p.z, ay, -p.w * ax)));
#pragma unroll
                        for (int r = 0; r < 4; r++) {
                            mma_tf32(kacc[r + 1], F[r][0], F[r][1], F[r][2], F[r][3], tf(fmaf(p.z, bx, -p.w * by)), tf(fmaf(-p.z, by, -p.w * bx)));
                            csq(bx, by);
                        }
                        klast = fmaf(p.z, bx, fmaf(-p.w, by, klast));
                    }
                }
                klast += __shfl_xor_sync(0xffffffffu, klast, 1);
                klast += __shfl_xor_sync(0xffffffffu, klast, 2);
                klast *= 1.f / TFC;
                float* const kp = kd + 32 * tq + g;
                if (it == 0 && wb == 0) {
                    bar_sync(HN_G + pr, 64);
#pragma unroll
                    for (int i = 0; i < 5; i++) { kacc[i][0] += kp[i * 128]; kacc[i][1] += kp[i * 128 + 16]; kacc[i][2] += kp[i * 128 + 8]; kacc[i][3] += kp[i * 128 + 24]; }
                    klast += kd[640];
                    __syncwarp();
                }
                const int ko = it == 0 && wb ? -4 * 648 : 0;
#pragma unroll
                for (int i = 0; i < 5; i++) { kp[ko + i * 128] = kacc[i][0]; kp[ko + i * 128 + 16] = kacc[i][1]; kp[ko + i * 128 + 8] = kacc[i][2]; kp[ko + i * 128 + 24] = kacc[i][3]; }
                if (lane == 0) kd[ko + 640] = klast;
                if (ko) { bar_arrive(HN_G + pr, 64); continue; }
                __syncwarp();
            }
#pragma unroll
            for (int h = 0; h < 2; h++) {
                const int i = lane + 32 * h;
                const uint32_t wa = sb + H_W + warp * H_WSTR + 256;
                const float4 v = *(const float4*)(kd + 4 * i);
                sts128(wa + i * 16, pack2(v.x, i ? kd[4 * i - 1] : 0.f), pack2(v.y, v.x), pack2(v.z, v.y), pack2(v.w, v.z));
#pragma unroll
                for (int r = 1; r < 4; r++) {
                    const float2 ab = *(const float2*)(kd + 128 + r * 128 + 2 * i);
                    const float c = kd[130 + r * 128 + 2 * i];
                    const uint32_t ba = pack2(ab.y, ab.x), cb = pack2(c, ab.y);
                    const uint32_t aa = __byte_perm(ba, 0, 0x3232), bb = __byte_perm(ba, 0, 0x1010), cc = __byte_perm(cb, 0, 0x1010);
                    const uint32_t p = wa + (512 << r) + i * (8 << r);
                    if (r == 1) sts128(p, i ? aa : pack2(ab.x, kd[255]), aa, ba, cb);
                    if (r == 2) { sts128(p, aa, aa, aa, ba); sts128(p + 16, bb, bb, cb, cc); }
                    if (r == 3) { sts128(p, aa, aa, aa, aa); sts128(p + 16, aa, ba, bb, bb); sts128(p + 32, bb, bb, bb, bb); sts128(p + 48, cb, cc, cc, cc); }
                }
            }
            __syncwarp();
            if (it == wb) bar_sync(HN_U + wb * 8, 256);
            if (it == 0) HEV(2);
            float acc[4][4][4];
            const uint32_t ub = sb + H_U + ch * H_USTR + (lane >> 3) * 16, zb = sb + H_Z + (lane >> 3) * 16;
            uint32_t bn[2][2][4];
            {
                const uint32_t dg = g == 2 * tq ? dsk : (g == 2 * tq + 1 ? dsk << 16 : 0u);
#pragma unroll
                for (int G = 0; G < 4; G++) {
                    ldsm4(bn[0][0], ub + (8 * G + (lane & 7)) * 144); ldsm4(bn[0][1], ub + (8 * G + (lane & 7)) * 144 + 64);
#pragma unroll
                    for (int i = 0; i < 4; i++) {
                        acc[G][i][0] = acc[G][i][1] = acc[G][i][2] = acc[G][i][3] = 0.f;
                        mma16(acc[G][i], dg, 0, 0, dg, bn[0][i >> 1][(i & 1) * 2], bn[0][i >> 1][(i & 1) * 2 + 1]);
                    }
                }
            }
            const volatile uint32_t* wp = wz + 64 - 56 + g - 2 * tq;
            uint32_t A[8][4];
#pragma unroll
            for (int m = 0; m < 7; m++) { A[m][0] = wp[16 * m + 8]; A[m][3] = wp[16 * m + 8]; A[m][1] = wp[16 * m + 16]; A[m][2] = wp[16 * m]; }
#define CONV_STEP(G0, E)                                                                                                 \
    {                                                                                                                    \
        uint32_t b[3][2][4];                                                                                             \
        _Pragma("unroll") for (int G = 2; G >= (G0); G--) {                                                              \
            const int cidx = 8 * G + (lane & 7) - s - (E);                                                               \
            const uint32_t ba = (G > (G0) || cidx >= 0) ? ub + cidx * 144 : zb;                                          \
            ldsm4(b[G][0], ba); ldsm4(b[G][1], ba + 64);                                                                 \
        }                                                                                                                \
        {                                                                                                                \
            const int cidx = 23 + (lane & 7) - s - (E);                                                                  \
            const uint32_t ba = ((G0) < 2 || cidx >= 0) ? ub + cidx * 144 : zb;                                          \
            ldsm4(bn[1 - (E)][0], ba); ldsm4(bn[1 - (E)][1], ba + 64);                                                   \
        }                                                                                                                \
        const volatile uint32_t* const wn = wp + 64 * min(s + (E) + 1, 31);                                              \
        _Pragma("unroll") for (int ph = 0; ph < 2; ph++) {                                                               \
            _Pragma("unroll") for (int G = 3; G >= (G0); G--)                                                            \
                _Pragma("unroll") for (int j = 3; j >= 0; j--)                                                           \
                    _Pragma("unroll") for (int i = 0; i < 4; i++) {                                                      \
                        if ((i - j + 3 >= 3) != ph) continue;                                                            \
                        const uint32_t* const a = A[(i - j + 3 + 4 * (E)) & 7];                                          \
                        const uint32_t* const bq = G == 3 ? bn[E][j >> 1] : b[G][j >> 1];                                \
                        mma16(acc[G][i], a[0], a[1], a[2], a[3], bq[(j & 1) * 2], bq[(j & 1) * 2 + 1]);                  \
                    }                                                                                                    \
            if (ph == 0) {                                                                                               \
                _Pragma("unroll") for (int m = 3; m < 7; m++) {                                                          \
                    uint32_t* const a = A[(m + 4 + 4 * (E)) & 7];                                                        \
                    a[0] = wn[16 * m + 8]; a[1] = wn[16 * m + 16];                                                       \
                    if (DUPL) { a[2] = wn[16 * m]; a[3] = wn[16 * m + 8]; } else { a[2] = A[(m + 3 + 4 * (E)) & 7][1]; a[3] = a[0]; } \
                }                                                                                                        \
            }                                                                                                            \
        }                                                                                                                \
    }
#define CONV_RANGE(G0) _Pragma("unroll 1") for (int s = 8 * (G0); s < 8 * (G0) + 8; s += 2) { CONV_STEP(G0, 0) CONV_STEP(G0, 1) }
            CONV_RANGE(0) CONV_RANGE(1) CONV_RANGE(2) CONV_RANGE(3)
#undef CONV_RANGE
#undef CONV_STEP
            __syncwarp();
            if (it == 0) HEV(3);
#pragma unroll
            for (int G = 0; G < 4; G++)
#pragma unroll
                for (int i = 0; i < 4; i += 2)
                    asm volatile("stmatrix.sync.aligned.m8n8.x4.trans.shared.b16 [%0], {%1,%2,%3,%4};"
                                 :: "r"(ub + (8 * G + (lane & 7)) * 144 + i * 32), "r"(pack2(acc[G][i][0], acc[G][i][1])), "r"(pack2(acc[G][i][2], acc[G][i][3])),
                                    "r"(pack2(acc[G][i + 1][0], acc[G][i + 1][1])), "r"(pack2(acc[G][i + 1][2], acc[G][i + 1][3])) : "memory");
        }
        HEV(4); GT(96, 1);
        const int wg = warp >> 2, q = warp & 3, t = tid & 127;
        const int nt = shared ? (cta & 3) * 2 + wg : 8, kg = shared ? cta >> 2 : (cta - 32) * 2 + wg;
        fence_smem_async();
        bar_arrive(HN_Y, 320);
        uint32_t w[32][4];
        {
            const uint32_t* src = (const uint32_t*)(Wo + (size_t)(kg * 512 + tq * 8) * DM + nt * 64 + q * 16) + g;
#pragma unroll
            for (int i = 0; i < 64; i++) {
                const int row = (i >> 2) * 32 + (i & 3) * 2;
                const uint32_t x = __ldg(src + row * (DM / 2)), y = __ldg(src + (row + 1) * (DM / 2));
                w[i >> 1][(i & 1) * 2] = __byte_perm(x, y, 0x5410);
                w[i >> 1][(i & 1) * 2 + 1] = __byte_perm(x, y, 0x7632);
            }
        }
        HEV(5);
        if (wg == 1) bar_arrive(HN_P, 256);
        uint32_t* const px = &g_part[0][nt][0][0][t];
        uint32_t* const dst = (uint32_t*)(out + (size_t)((kg >> 1) * 8 + 2 * tq + (kg & 1)) * OUTW + nt * 64 + q * 16) + g;
#pragma unroll 1
        for (int s = 0; s < ((HM & 4) ? NSEG + LAG : 0); s++) {
            const int f = s - LAG;
            const uint32_t* const src = px + (f & 7) * (9 * 8192) + kg * 1024;
            uint32_t v[8];
#pragma unroll
            for (int i = 0; i < 8; i++) v[i] = ldg_rlx(src + i * 128);
            float d[16];
            if (s < NSEG) {
                const int n = shared ? 2 * s : 4 * s + 2 * wg, r = n / NST, st = n - r * NST;
                const uint32_t dl = desc_lo(sb + H_RING + st * 16384);
                if (wg == 0) HS(0);
                mbar_wait(bar + HB_FULL + st * 8, r & 1);
                bar_sync(HN_P + wg, 256);
                if (wg == 0) HS(1);
                wg_fence();
                wgmma32<0>(d, w[0], desc_of(dl));
#pragma unroll
                for (int i = 1; i < 16; i++) wgmma32<1>(d, w[i], desc_of(dl + (i >> 2) * 256 + (i & 3) * 2));
                wg_commit();
                mbar_wait(bar + HB_FULL + st * 8 + 8, r & 1);
                wg_fence();
#pragma unroll
                for (int i = 16; i < PPT; i++) wgmma32<1>(d, w[i], desc_of(dl + (i >> 2) * 256 + (i & 3) * 2));
                bar_arrive(HN_P + (wg ^ 1), 256);
#pragma unroll
                for (int i = PPT; i < 32; i++) wgmma32<1>(d, w[i], desc_of(dl + (i >> 2) * 256 + (i & 3) * 2));
                wg_commit();
                asm volatile("wgmma.wait_group.sync.aligned 1;" ::: "memory");
                mbar_arrive_warp(bar + HB_EMPTY + st * 8);
                wg_wait0();
                mbar_arrive_warp(bar + HB_EMPTY + st * 8 + 8);
                if (wg == 0) HS(2);
                const uint32_t ph = ((s >> 3) + 1) & 1, rnd = ph ? 0u : 0x10000u;
                uint32_t* const p = px + (s & 7) * (9 * 8192) + kg * 128;
#pragma unroll
                for (int r = 0; r < 8; r++) {
                    const uint32_t lo = __float_as_uint(d[4 * (r >> 1) + (r & 1)]) + rnd, hi = __float_as_uint(d[4 * (r >> 1) + 2 + (r & 1)]) + 0x8000u;
                    stg_rlx(p + r * 1024, (__byte_perm(lo, hi, 0x7632) & 0xfffffffeu) | ph);
                }
                if (wg == 0) HS(3);
            }
            if (s >= LAG) {
                const uint32_t ph = ((f >> 3) + 1) & 1;
                for (int it = 0; __any_sync(0xffffffffu, (or3(diff2(v[0], v[1], ph), diff2(v[2], v[3], ph), diff2(v[4], v[5], ph)) | diff2(v[6], v[7], ph)) & 1);) {
#pragma unroll
                    for (int i = 0; i < 8; i++) v[i] = ldg_rlx(src + i * 128);
                    if (++it > (1 << 22)) TRAP(2000 + __LINE__);
                }
            }
            if (s >= LAG)
                dst[(size_t)f * 32 * (OUTW / 2)] = pack2(((bflo(v[0]) + bflo(v[1])) + (bflo(v[2]) + bflo(v[3]))) + ((bflo(v[4]) + bflo(v[5])) + (bflo(v[6]) + bflo(v[7]))),
                                                         ((bfhi(v[0]) + bfhi(v[1])) + (bfhi(v[2]) + bfhi(v[3]))) + ((bfhi(v[4]) + bfhi(v[5])) + (bfhi(v[6]) + bfhi(v[7]))));
            if (wg == 0) HS(4);
        }
        if ((HM & 4) && wg == 0) bar_sync(HN_P, 256);
    } else if (warp < 12) {
        asm volatile("setmaxnreg.dec.sync.aligned.u32 48;");
        if (tid - 256 < 64) ((uint32_t*)(smem + H_Z))[tid - 256] = 0;
        spin_until(tstart + UDLY);
        LOAD_U(warp - 8)
        bar_arrive(HN_U, 256);
        bar_arrive(HN_U + 8, 256);
        const int hd = cta, h0 = shared ? cta & 28 : (cta - 32) * 8, nst = shared ? 2 : 4;
        if (warp == 8) {
            bar_sync(HN_Y, 320);
            int ready = 0;
#pragma unroll 1
            for (int s = 0; s < ((HM & 4) ? NSEG : 0); s++) {
                for (int it = 0; ready <= s;) {
                    const unsigned want = epoch * 64 + s + (lane >> 3);
                    unsigned v = want;
                    if (s + (lane >> 3) < NSEG) v = ldg_acq(&g_oflag[s + (lane >> 3)][h0 + (lane & (2 * nst - 1))][0]);
                    const uint32_t miss = ~__ballot_sync(0xffffffffu, v == want);
                    ready = s + (miss ? (__ffs(miss) - 1) >> 3 : 4);
                    if (++it > (1 << 24)) TRAP(2000 + __LINE__);
                }
                asm volatile("fence.proxy.async.global;" ::: "memory");
#pragma unroll 1
                for (int i = 0; i < nst; i++) {
                    const int n = nst * s + i, r = n / NST, st = n - r * NST;
                    if (r > 0) mbar_wait(bar + HB_EMPTY + st * 8, (r - 1) & 1);
                    if (lane == 0) {
                        mbar_expect(bar + HB_FULL + st * 8, 16384);
                        bulk_g2s(sb + H_RING + st * 16384, (const char*)g_o + (size_t)(s * 64 + h0 * 2 + i * 4) * 4096, 16384, bar + HB_FULL + st * 8);
                    }
                    __syncwarp();
                }
                HS(7);
            }
        } else if (warp == 9) {
#pragma unroll 1
            for (int s = 0; s < ((HM & 2) && shared ? NSEG : 0); s++) {
                const int c = lane % 3;
                unsigned v;
                for (int it = 0; v = ldg_acq(&g_qflag[s][hd][c * 8]), !__all_sync(0xffffffffu, (v ^ (epoch * 64)) < 64);)
                    if (++it > (1 << 24)) TRAP(2000 + __LINE__);
                HS(5);
                asm volatile("fence.proxy.async.global;" ::: "memory");
                const uint32_t off = lane < 3 ? c * 7680 : lane < 6 ? 20480 + c * 2048 : 28672 + c * 512;
                const unsigned char* const src = g_qkv + (size_t)((v & 63) * 32 + hd) * 30720 + off;
                if (s > 0) mbar_wait(bar + HB_QE, (s - 1) & 1);
                if (lane == 0) mbar_expect(bar + HB_QF, 20480);
                if (lane < 3) bulk_g2s(sb + H_QKV + off, src, c == 2 ? 5120 : 7680, bar + HB_QF);
                __syncwarp();
                if (s > 0) mbar_wait(bar + HB_VE, (s - 1) & 1);
                if (lane == 0) mbar_expect(bar + HB_VF, 10240);
                if (lane >= 3 && lane < 9) bulk_g2s(sb + H_QKV + off, src, (lane < 6 ? 2048 : 512) << (c >> 1), bar + HB_VF);
                __syncwarp();
            }
        } else if (warp == 10) {
#pragma unroll 1
            for (int s = 0; s < ((HM & 2) && shared ? NSEG : 0); s++) {
                mbar_wait(bar + HB_OF, s & 1);
                if (lane == 0) {
                    bulk_s2g((char*)g_o + (size_t)(s * 64 + hd * 2) * 4096, sb + H_AO, 8192);
                    asm volatile("cp.async.bulk.commit_group;" ::: "memory");
                    asm volatile("cp.async.bulk.wait_group.read 0;" ::: "memory");
                    mbar_arrive(bar + HB_OE);
                    asm volatile("cp.async.bulk.wait_group 0;" ::: "memory");
                    stg_rlx(&g_oflag[s][hd][0], epoch * 64 + s);
                }
                __syncwarp();
                HS(6);
            }
        } else {
            bar_sync(HN_Y, 320);
#pragma unroll 1
            for (int i = 0; i < 128; i++) {
                const uint32_t t0 = clk();
                uint32_t v[4];
                ldsm4t(v, sb + H_U + (lane & 15) * H_USTR + (i >> 2) * 144 + (i & 3) * 32 + (lane >> 4) * 16);
                uint2* const p = (uint2*)(out + (size_t)(i * 16 + g) * OUTW + DM + d0 + tq * 4);
                p[0] = make_uint2(v[0], v[1]);
                p[8 * (OUTW / 4)] = make_uint2(v[2], v[3]);
                spin_until(t0 + YDLY);
            }
            asm volatile("griddepcontrol.wait;" ::: "memory");
        }
    } else {
        asm volatile("setmaxnreg.dec.sync.aligned.u32 112;");
        const uint32_t qk = sb + H_QKV;
        const int dg = 8 * (warp & 3) + g - 2 * tq;
        const uint32_t oa = pin(sb + H_AO + (8 * (warp & 3) + g) * 128);
#pragma unroll 1
        for (int s = 0; s < ((HM & 2) && shared ? NSEG : 0); s++) {
            float x[24];
            mbar_wait(bar + HB_QF, s & 1);
            wg_fence();
#pragma unroll
            for (int i = 0; i < 8; i++) {
                constexpr int QO[8] = {0, 1024, 2048, 7680, 8704, 9728, 15360, 16384}, KO[8] = {3072, 4608, 6144, 10752, 12288, 13824, 17408, 18944};
                if (i == 0) wgmma48_tt<0>(x, desc_plain(qk + QO[i], 128, 128), desc_plain(qk + KO[i], 128, 256));
                else wgmma48_tt<1>(x, desc_plain(qk + QO[i], 128, 128), desc_plain(qk + KO[i], 128, 256));
            }
            wg_commit();
            wg_wait0();
            mbar_arrive_warp(bar + HB_QE);
            x[16] += x[20]; x[17] += x[21];
            float m = fmaxf(x[16], x[17]);
#pragma unroll
            for (int b = 0; b < 4; b++) {
                if (8 * b > dg) x[4 * b] = NEG;
                if (8 * b + 1 > dg) x[4 * b + 1] = NEG;
                m = fmaxf(m, fmaxf(x[4 * b], x[4 * b + 1]));
            }
            m = fmaxf(m, __shfl_xor_sync(0xffffffffu, m, 1));
            m = fmaxf(m, __shfl_xor_sync(0xffffffffu, m, 2));
            float l = 0.f;
            uint32_t pa[3][4];
#pragma unroll
            for (int b = 0; b < 5; b++) {
                const float e0 = ex2(x[4 * b] - m), e1 = ex2(x[4 * b + 1] - m);
                l += e0 + e1;
                pa[b >> 1][(b & 1) * 2] = pack2(e0, e1);
                pa[b >> 1][(b & 1) * 2 + 1] = 0;
            }
            pa[2][2] = pa[2][3] = 0;
            l += __shfl_xor_sync(0xffffffffu, l, 1);
            l = rcp_fast(l + __shfl_xor_sync(0xffffffffu, l, 2));
            uint32_t ow[2][8];
            mbar_wait(bar + HB_VF, s & 1);
#pragma unroll
            for (int hf = 0; hf < 2; hf++) {
                float o[32];
                wg_fence();
                wgmma64<0>(o, pa[0], desc_plain(qk + 20480 + hf * 128, 256, 1024));
                wgmma64<1>(o, pa[1], desc_plain(qk + 20480 + 512 + hf * 128, 256, 1024));
                wgmma64<1>(o, pa[2], desc_plain(qk + 28672 + hf * 128, 0, 256));
                wg_commit();
                if (hf == 0 && s > 0) mbar_wait(bar + HB_OE, (s - 1) & 1);
                wg_wait0();
#pragma unroll
                for (int i = 0; i < 8; i++) ow[hf][i] = pack2(o[4 * i] * l, o[4 * i + 1] * l);
            }
            mbar_arrive_warp(bar + HB_VE);
#pragma unroll
            for (int grp = 0; grp < 4; grp++)
                sts128(oa + (grp >> 1) * 4096 + ((((grp & 1) * 4 + tq) ^ g) << 4), ow[0][2 * grp], ow[1][2 * grp], ow[0][2 * grp + 1], ow[1][2 * grp + 1]);
            fence_smem_async();
            mbar_arrive_warp(bar + HB_OF);
        }
    }
}

typedef CUresult (*EncodeFn)(CUtensorMap*, CUtensorMapDataType, cuuint32_t, void*, const cuuint64_t*, const cuuint64_t*, const cuuint32_t*,
                             const cuuint32_t*, CUtensorMapInterleave, CUtensorMapSwizzle, CUtensorMapL2promotion, CUtensorMapFloatOOBfill);

static void make_map(EncodeFn enc, CUtensorMap* m, void* base, int width, int boxchunks) {
    cuuint64_t dims[3] = {64, 2048, (cuuint64_t)(width / 64)};
    cuuint64_t strides[2] = {(cuuint64_t)width * 2, 128};
    cuuint32_t box[3] = {64, 32, (cuuint32_t)boxchunks};
    cuuint32_t es[3] = {1, 1, 1};
    enc(m, CU_TENSOR_MAP_DATA_TYPE_BFLOAT16, 3, base, dims, strides, box, es, CU_TENSOR_MAP_INTERLEAVE_NONE, CU_TENSOR_MAP_SWIZZLE_128B,
        CU_TENSOR_MAP_L2_PROMOTION_L2_256B, CU_TENSOR_MAP_FLOAT_OOB_FILL_NONE);
}

extern "C" void kernel_launch(void* const* d_in, const int* in_sizes, int n_in, void* d_out, int out_size) {
    typedef const __nv_bfloat16* P;
    static EncodeFn enc = nullptr;
    if (!enc) {
        void* fn = nullptr;
        cudaDriverEntryPointQueryResult st;
        cudaGetDriverEntryPoint("cuTensorMapEncodeTiled", &fn, cudaEnableDefault, &st);
        enc = (EncodeFn)fn;
        cudaFuncSetAttribute(rk_kernel, cudaFuncAttributeMaxDynamicSharedMemorySize, R_SMEM);
        cudaFuncSetAttribute(hk_kernel, cudaFuncAttributeMaxDynamicSharedMemorySize, H_SMEM);
    }
    Maps maps;
    make_map(enc, &maps.x, d_in[0], DM, 3);
    {
        void* acc = nullptr;
        cudaGetSymbolAddress(&acc, g_acc);
        for (int m = 0; m < 2; m++) {
            cuuint64_t dims[5] = {128, 2, 2, 2, 144};
            cuuint64_t strides[4] = {(cuuint64_t)(m ? 4096 : 12288), 1024, 16384, 256};
            cuuint32_t box[5] = {64, 2, 2, 2, 2}, es[5] = {1, 1, 1, 1, 1};
            enc(&maps.acc[m], CU_TENSOR_MAP_DATA_TYPE_BFLOAT16, 5, (char*)acc + m * 4096, dims, strides, box, es, CU_TENSOR_MAP_INTERLEAVE_NONE,
                CU_TENSOR_MAP_SWIZZLE_NONE, CU_TENSOR_MAP_L2_PROMOTION_NONE, CU_TENSOR_MAP_FLOAT_OOB_FILL_NONE);
        }
    }

    for (int m = 0; m < 7; m++) {
        cuuint64_t dims[2] = {(cuuint64_t)(m < 6 ? HD : DM), (cuuint64_t)(m < 6 ? DM : HD)}, strides[1] = {dims[0] * 2};
        cuuint32_t box[2] = {16u * (m / 3 + 1), m < 3 ? 32u : 64u}, es[2] = {1, 1};
        enc(m < 3 ? &maps.w16[m] : m < 6 ? &maps.w32[m - 3] : &maps.wo, CU_TENSOR_MAP_DATA_TYPE_BFLOAT16, 2, d_in[m < 6 ? 2 + m % 3 : 5], dims, strides, box, es,
            CU_TENSOR_MAP_INTERLEAVE_NONE, m < 3 ? CU_TENSOR_MAP_SWIZZLE_32B : m < 6 ? CU_TENSOR_MAP_SWIZZLE_64B : CU_TENSOR_MAP_SWIZZLE_NONE,
            (CUtensorMapL2promotion)WPF, CU_TENSOR_MAP_FLOAT_OOB_FILL_NONE);
    }

    cudaLaunchConfig_t cfg = {};
    cudaLaunchAttribute at[1];
    cfg.gridDim = dim3(96); cfg.blockDim = dim3(384); cfg.dynamicSmemBytes = R_SMEM; cfg.stream = cudaStreamPerThread;
    at[0].id = cudaLaunchAttributeClusterDimension; at[0].val.clusterDim.x = 3; at[0].val.clusterDim.y = 1; at[0].val.clusterDim.z = 1;
    cfg.attrs = at; cfg.numAttrs = 1;
    cudaLaunchKernelEx(&cfg, rk_kernel, maps, (P)d_in[0], (P)d_in[1]);

    cfg.gridDim = dim3(36); cfg.blockDim = dim3(512); cfg.dynamicSmemBytes = H_SMEM;
    at[0].id = cudaLaunchAttributeProgrammaticStreamSerialization; at[0].val.programmaticStreamSerializationAllowed = 1;
    cudaLaunchKernelEx(&cfg, hk_kernel, (P)d_in[5], (P)d_in[7], (P)d_in[8], (P)d_in[9], (P)d_in[10], (P)d_in[11], (P)d_in[12], (P)d_in[13],
                       (__nv_bfloat16*)d_out);
}
```

```cpp
#include <cuda_runtime.h>
#include <cuda_bf16.h>
#include <cuda_fp16.h>
#include <cuda.h>
#include <stdint.h>

#define DEVI __device__ __forceinline__

#define NEG __int_as_float(0xff800000)
constexpr int DM = 576, NSEG = 64, HD = 4096, OUTW = 1152;

#define HM 7
#define QW 4000
#define NPROBE 4
#define CT 1600
#define FE 85
#define DL 0
#define DMIN 150
#define DMAX 4000
#define BACKOFF 200
#define LW 3
#define TIE 0
#define C2ADJ 80
#define DST 120
#define VFE 0
#define EW 0
#define LB 12
#define NTR 3
#define RP 176
#define NW2 3
#define KT 4
#define DDUMP 200
#define DPUSH 300
#define GOE 21
#define LDM 2
#define XD 50
#define G1T 0
#define F0T 14
#define F1T 16
#define SUMV 0
#define UDLY 0
#define YDLY 300
#define PPT 32
#define LAG 3
#define QR 4
#define DUPL 1
#define WPF 3
#define XPF 0
#define SSP 10
#define TR0 0
#define KB 0
#define NCH 4
#define NS 4
#define N0 3
#define P2 9
#define VW 0
#define VD 0
#define VT 1
#define PE 1
#define DUMPX 0
#define NPOLL 3
#define DSTI 150
#define ONE 1
#define OB 1
#define TR1 2
#define MW 2
#define WD 600
#define WB 4
#define PDLY 0
#define PB 0
#define N1 8

__device__ __align__(1024) __nv_bfloat16 g_o[2048 * HD];
__device__ __align__(65536) uint32_t g_acc[16384];
__device__ __align__(128) unsigned g_pub[96];
__device__ __align__(128) uint32_t g_part[8][9][8][8][128];
__device__ __align__(1024) unsigned char g_qkv[(size_t)NSEG * 32 * 30720];
__device__ __align__(128) unsigned g_qflag[NSEG][32][32];
__device__ __align__(128) unsigned g_oflag[NSEG][32][8];
__device__ unsigned g_epoch[36 + 96];
#define EV(i)
#define EVV(i, v)
#define EVX(i) 0
#define EVADD(i, v)
#define HS(i)
#define PT(i)
#define HEV(i)
#define GT(b, i)

#define TRAP(code) __trap()
#define LOC(v)
DEVI uint32_t smem_u32(const void* p) { return (uint32_t)__cvta_generic_to_shared(p); }
DEVI uint32_t clk() { uint64_t t; asm volatile("mov.u64 %0, %%clock64;" : "=l"(t) :: "memory"); return (uint32_t)t; }
DEVI uint32_t gtime() { uint64_t t; asm volatile("mov.u64 %0, %%globaltimer;" : "=l"(t) :: "memory"); return (uint32_t)t; }
DEVI void spin_until(uint32_t t) { while ((int)(clk() - t) < 0) {} }
DEVI void jit() {}
DEVI uint32_t mapa(uint32_t a, uint32_t r) { uint32_t o; asm("mapa.shared::cluster.u32 %0, %1, %2;" : "=r"(o) : "r"(a), "r"(r)); return o; }
DEVI void mbar_init(uint32_t b, uint32_t n) { asm volatile("mbarrier.init.shared::cta.b64 [%0], %1;" :: "r"(b), "r"(n) : "memory"); }
DEVI void mbar_expect(uint32_t b, uint32_t bytes) { asm volatile("mbarrier.arrive.expect_tx.shared::cta.b64 _, [%0], %1;" :: "r"(b), "r"(bytes) : "memory"); }
DEVI void mbar_arrive(uint32_t b) { asm volatile("mbarrier.arrive.shared::cta.b64 _, [%0];" :: "r"(b) : "memory"); }
DEVI bool mbar_try(uint32_t b, uint32_t parity) {
    uint32_t ok;
    asm volatile("{.reg .pred p; mbarrier.try_wait.parity.shared::cta.b64 p, [%1], %2; selp.u32 %0, 1, 0, p;}" : "=r"(ok) : "r"(b), "r"(parity) : "memory");
    return ok;
}
DEVI void mbar_wait(uint32_t b, uint32_t parity) {
    LOC(0x100 | (b & 0xff) | (parity << 12));
    asm volatile("{.reg .pred p, q; .reg .u32 n; mov.u32 n, 0;\n W: mbarrier.try_wait.parity.shared::cta.b64 p, [%0], %1;\n"
                 "add.u32 n, n, 1; setp.lt.and.u32 q, n, 0x40000, !p; @q bra W;}" :: "r"(b), "r"(parity) : "memory");
    LOC(0x300 | (b & 0xff));
    jit();
}
DEVI void bar_sync(int id, int n) { jit(); LOC(0x200 | id); asm volatile("bar.sync %0, %1;" :: "r"(id), "r"(n) : "memory"); LOC(0x400 | id); jit(); }
DEVI void bar_arrive(int id, int n) { jit(); asm volatile("bar.arrive %0, %1;" :: "r"(id), "r"(n) : "memory"); jit(); }
DEVI void cluster_sync() { asm volatile("barrier.cluster.arrive.release.aligned; barrier.cluster.wait.acquire.aligned;" ::: "memory"); }
DEVI void cluster_arrive_rlx() { asm volatile("barrier.cluster.arrive.relaxed.aligned;" ::: "memory"); }
DEVI void cluster_wait() { asm volatile("barrier.cluster.wait.aligned;" ::: "memory"); }
DEVI void fence_async() { asm volatile("fence.proxy.async;" ::: "memory"); }
DEVI void cp16(uint32_t dst, const void* src) { asm volatile("cp.async.cg.shared.global [%0], [%1], 16;" :: "r"(dst), "l"(src) : "memory"); }
DEVI void cp_commit() { asm volatile("cp.async.commit_group;" ::: "memory"); }
template <int N> DEVI void cp_wait() { asm volatile("cp.async.wait_group %0;" :: "n"(N) : "memory"); }
DEVI void ldsm4(uint32_t* r, uint32_t a) {
    asm volatile("ldmatrix.sync.aligned.m8n8.x4.shared.b16 {%0,%1,%2,%3}, [%4];" : "=r"(r[0]), "=r"(r[1]), "=r"(r[2]), "=r"(r[3]) : "r"(a) : "memory");
}
DEVI uint32_t tab1(uint32_t a) { uint32_t r; asm volatile("ldmatrix.sync.aligned.m8n8.x1.shared.b16 {%0}, [%1];" : "=r"(r) : "r"(a) : "memory"); return r; }
DEVI uint2 tab2(uint32_t a) { uint2 r; asm volatile("ldmatrix.sync.aligned.m8n8.x2.shared.b16 {%0,%1}, [%2];" : "=r"(r.x), "=r"(r.y) : "r"(a) : "memory"); return r; }
DEVI void ldsm4t(uint32_t* r, uint32_t a) {
    asm volatile("ldmatrix.sync.aligned.m8n8.x4.trans.shared.b16 {%0,%1,%2,%3}, [%4];" : "=r"(r[0]), "=r"(r[1]), "=r"(r[2]), "=r"(r[3]) : "r"(a) : "memory");
}
DEVI void mma16(float* d, uint32_t a0, uint32_t a1, uint32_t a2, uint32_t a3, uint32_t b0, uint32_t b1) {
    asm volatile("mma.sync.aligned.m16n8k16.row.col.f32.bf16.bf16.f32 {%0,%1,%2,%3}, {%4,%5,%6,%7}, {%8,%9}, {%0,%1,%2,%3};"
                 : "+f"(d[0]), "+f"(d[1]), "+f"(d[2]), "+f"(d[3]) : "r"(a0), "r"(a1), "r"(a2), "r"(a3), "r"(b0), "r"(b1));
}
DEVI void mma8(float* d, uint32_t a0, uint32_t a1, uint32_t b0) {
    asm volatile("mma.sync.aligned.m16n8k8.row.col.f32.bf16.bf16.f32 {%0,%1,%2,%3}, {%4,%5}, {%6}, {%0,%1,%2,%3};"
                 : "+f"(d[0]), "+f"(d[1]), "+f"(d[2]), "+f"(d[3]) : "r"(a0), "r"(a1), "r"(b0));
}
DEVI void mma_tf32(float* d, uint32_t a0, uint32_t a1, uint32_t a2, uint32_t a3, uint32_t b0, uint32_t b1) {
    asm volatile("mma.sync.aligned.m16n8k8.row.col.f32.tf32.tf32.f32 {%0,%1,%2,%3}, {%4,%5,%6,%7}, {%8,%9}, {%0,%1,%2,%3};"
                 : "+f"(d[0]), "+f"(d[1]), "+f"(d[2]), "+f"(d[3]) : "r"(a0), "r"(a1), "r"(a2), "r"(a3), "r"(b0), "r"(b1));
}
template <int ACC> DEVI void wgmma32(float* d, const uint32_t* a, uint64_t desc) {
    asm volatile("wgmma.mma_async.sync.aligned.m64n32k16.f32.bf16.bf16 "
                 "{%0,%1,%2,%3,%4,%5,%6,%7,%8,%9,%10,%11,%12,%13,%14,%15}, {%16,%17,%18,%19}, %20, %21, 1, 1, 0;"
                 : "+f"(d[0]), "+f"(d[1]), "+f"(d[2]), "+f"(d[3]), "+f"(d[4]), "+f"(d[5]), "+f"(d[6]), "+f"(d[7]),
                   "+f"(d[8]), "+f"(d[9]), "+f"(d[10]), "+f"(d[11]), "+f"(d[12]), "+f"(d[13]), "+f"(d[14]), "+f"(d[15])
                 : "r"(a[0]), "r"(a[1]), "r"(a[2]), "r"(a[3]), "l"(desc), "n"(ACC));
}
template <int ACC> DEVI void wgmma32_ss(float* d, uint64_t adesc, uint64_t desc) {
    asm volatile("wgmma.mma_async.sync.aligned.m64n32k16.f32.bf16.bf16 "
                 "{%0,%1,%2,%3,%4,%5,%6,%7,%8,%9,%10,%11,%12,%13,%14,%15}, %16, %17, %18, 1, 1, 1, 0;"
                 : "+f"(d[0]), "+f"(d[1]), "+f"(d[2]), "+f"(d[3]), "+f"(d[4]), "+f"(d[5]), "+f"(d[6]), "+f"(d[7]),
                   "+f"(d[8]), "+f"(d[9]), "+f"(d[10]), "+f"(d[11]), "+f"(d[12]), "+f"(d[13]), "+f"(d[14]), "+f"(d[15])
                 : "l"(adesc), "l"(desc), "n"(ACC));
}
DEVI void wg_fence() { asm volatile("wgmma.fence.sync.aligned;" ::: "memory"); }
DEVI void wg_commit() { asm volatile("wgmma.commit_group.sync.aligned;" ::: "memory"); }
DEVI void wg_wait0() { asm volatile("wgmma.wait_group.sync.aligned 0;" ::: "memory"); }
DEVI uint64_t desc_sw128(uint32_t saddr) { return ((uint64_t)1 << 62) | ((uint64_t)64 << 32) | ((uint64_t)1 << 16) | (uint64_t)((saddr & 0x3FFFF) >> 4); }
DEVI uint32_t desc_lo(uint32_t saddr) { return (1u << 16) | ((saddr & 0x3FFFF) >> 4); }
DEVI uint64_t desc_of(uint32_t lo) { uint64_t d; asm("mov.b64 %0, {%1, 0x40000040};" : "=l"(d) : "r"(lo)); return d; }
DEVI uint64_t desc_sw32(uint32_t lo) { uint64_t d; asm("mov.b64 %0, {%1, 0xc0000010};" : "=l"(d) : "r"(lo)); return d; }
DEVI uint32_t pack2(float lo, float hi) { uint32_t r; asm("cvt.rn.bf16x2.f32 %0, %1, %2;" : "=r"(r) : "f"(hi), "f"(lo)); return r; }
DEVI void sts32(uint32_t a, uint32_t v) { asm volatile("st.shared.u32 [%0], %1;" :: "r"(a), "r"(v) : "memory"); }
DEVI void sts64f(uint32_t a, float x, float y) { asm volatile("st.shared.v2.f32 [%0], {%1,%2};" :: "r"(a), "f"(x), "f"(y) : "memory"); }
DEVI void sts128f(uint32_t a, float x, float y, float z, float w) { asm volatile("st.shared.v4.f32 [%0], {%1,%2,%3,%4};" :: "r"(a), "f"(x), "f"(y), "f"(z), "f"(w) : "memory"); }
DEVI float2 lds64f(uint32_t a) { float2 v; asm volatile("ld.shared.v2.f32 {%0,%1}, [%2];" : "=f"(v.x), "=f"(v.y) : "r"(a) : "memory"); return v; }
DEVI float4 lds128f(uint32_t a) { float4 v; asm volatile("ld.shared.v4.f32 {%0,%1,%2,%3}, [%4];" : "=f"(v.x), "=f"(v.y), "=f"(v.z), "=f"(v.w) : "r"(a) : "memory"); return v; }
DEVI uint4 lds128(uint32_t a) { uint4 v; asm volatile("ld.shared.v4.u32 {%0,%1,%2,%3}, [%4];" : "=r"(v.x), "=r"(v.y), "=r"(v.z), "=r"(v.w) : "r"(a) : "memory"); return v; }
DEVI uint4 ldm128(uint32_t a) {
    uint4 v;
    asm volatile("ld.volatile.shared.v4.u32 {%0,%1,%2,%3}, [%4];" : "=r"(v.x), "=r"(v.y), "=r"(v.z), "=r"(v.w) : "r"(a) : "memory");
    return v;
}
DEVI void sta32(uint32_t a, uint32_t v, uint32_t bar) { asm volatile("st.async.weak.shared::cluster.mbarrier::complete_tx::bytes.b32 [%0], %1, [%2];" :: "r"(a), "r"(v), "r"(bar) : "memory"); }
DEVI void sta64f(uint32_t a, float x, float y, uint32_t bar) { asm volatile("st.async.weak.shared::cluster.mbarrier::complete_tx::bytes.v2.f32 [%0], {%1,%2}, [%3];" :: "r"(a), "f"(x), "f"(y), "r"(bar) : "memory"); }
DEVI void sta128f(uint32_t a, float x, float y, float z, float w, uint32_t bar) {
    asm volatile("st.async.weak.shared::cluster.mbarrier::complete_tx::bytes.v4.f32 [%0], {%1,%2,%3,%4}, [%5];" :: "r"(a), "f"(x), "f"(y), "f"(z), "f"(w), "r"(bar) : "memory");
}
DEVI void stg_rlx(uint32_t* p, uint32_t v) { asm volatile("st.relaxed.gpu.global.u32 [%0], %1;" :: "l"(p), "r"(v) : "memory"); }
DEVI void stg_release(unsigned* p, unsigned v) { asm volatile("st.release.gpu.global.u32 [%0], %1;" :: "l"(p), "r"(v) : "memory"); }
DEVI uint32_t ldg_rlx(const uint32_t* p) { uint32_t v; asm volatile("ld.relaxed.gpu.global.u32 %0, [%1];" : "=r"(v) : "l"(p) : "memory"); return v; }
DEVI void bulk_g2s(uint32_t dst, const void* src, uint32_t bytes, uint32_t bar) {
    asm volatile("cp.async.bulk.shared::cluster.global.mbarrier::complete_tx::bytes [%0], [%1], %2, [%3];" :: "r"(dst), "l"(src), "r"(bytes), "r"(bar) : "memory");
}
DEVI void bulk_s2c(uint32_t dst, uint32_t src, uint32_t bytes, uint32_t bar) {
    asm volatile("cp.async.bulk.shared::cluster.shared::cta.mbarrier::complete_tx::bytes [%0], [%1], %2, [%3];" :: "r"(dst), "r"(src), "r"(bytes), "r"(bar) : "memory");
}
DEVI float ex2(float x) { float y; asm("ex2.approx.ftz.f32 %0, %1;" : "=f"(y) : "f"(x)); return y; }
DEVI float ex2v(float x) { float y; asm volatile("ex2.approx.ftz.f32 %0, %1;" : "=f"(y) : "f"(x)); return y; }
DEVI float bf2f(__nv_bfloat16 v) { return __bfloat162float(v); }

DEVI uint32_t pin(uint32_t v) { return __shfl_sync(0xffffffffu, v, threadIdx.x & 31); }
template <typename T> DEVI T* pinp(T* p) { const uint64_t v = (uint64_t)p; return (T*)(((uint64_t)pin((uint32_t)(v >> 32)) << 32) | pin((uint32_t)v)); }
DEVI uint32_t fresh(uint32_t v) { uint32_t r; asm volatile("mov.u32 %0, %1;" : "=r"(r) : "r"(v)); return r; }
DEVI uint64_t fresh64(uint64_t v) { uint64_t r; asm volatile("mov.u64 %0, %1;" : "=l"(r) : "l"(v)); return r; }
DEVI uint32_t or3(uint32_t a, uint32_t b, uint32_t c) { uint32_t d; asm("lop3.b32 %0, %1, %2, %3, 0xfe;" : "=r"(d) : "r"(a), "r"(b), "r"(c)); return d; }
DEVI uint32_t orand(uint32_t a, uint32_t b, uint32_t c) { uint32_t d; asm("lop3.b32 %0, %1, %2, %3, 0xf8;" : "=r"(d) : "r"(a), "r"(b), "r"(c)); return d; }
DEVI uint32_t and3(uint32_t a, uint32_t b, uint32_t c) { uint32_t d; asm("lop3.b32 %0, %1, %2, %3, 0x80;" : "=r"(d) : "r"(a), "r"(b), "r"(c)); return d; }
DEVI uint32_t diff2(uint32_t a, uint32_t b, uint32_t p) { uint32_t d; asm("lop3.b32 %0, %1, %2, %3, 0x7e;" : "=r"(d) : "r"(a), "r"(b), "r"(p)); return d; }
DEVI int lds32(uint32_t a) { int v; asm volatile("ld.volatile.shared.s32 %0, [%1];" : "=r"(v) : "r"(a) : "memory"); return v; }
DEVI uint2 lds64(uint32_t a) { uint2 v; asm volatile("ld.shared.v2.u32 {%0,%1}, [%2];" : "=r"(v.x), "=r"(v.y) : "r"(a) : "memory"); return v; }
DEVI void sts64(uint32_t a, uint32_t x, uint32_t y) { asm volatile("st.shared.v2.u32 [%0], {%1,%2};" :: "r"(a), "r"(x), "r"(y) : "memory"); }
DEVI void sta64(uint32_t a, uint32_t x, uint32_t y, uint32_t bar) { asm volatile("st.async.weak.shared::cluster.mbarrier::complete_tx::bytes.v2.b32 [%0], {%1,%2}, [%3];" :: "r"(a), "r"(x), "r"(y), "r"(bar) : "memory"); }
DEVI float rcp_fast(float x) { float y; asm("rcp.approx.ftz.f32 %0, %1;" : "=f"(y) : "f"(x)); return y; }
DEVI uint4 ldg_rlx4(const void* p) { uint4 v; asm volatile("ld.relaxed.gpu.global.v4.u32 {%0,%1,%2,%3}, [%4];" : "=r"(v.x), "=r"(v.y), "=r"(v.z), "=r"(v.w) : "l"(p) : "memory"); return v; }
DEVI void sts128(uint32_t a, uint32_t x, uint32_t y, uint32_t z, uint32_t w) { asm volatile("st.shared.v4.u32 [%0], {%1,%2,%3,%4};" :: "r"(a), "r"(x), "r"(y), "r"(z), "r"(w) : "memory"); }
DEVI void stsm4(uint32_t a, uint32_t x, uint32_t y, uint32_t z, uint32_t w) { asm volatile("stmatrix.sync.aligned.m8n8.x4.shared.b16 [%0], {%1,%2,%3,%4};" :: "r"(a), "r"(x), "r"(y), "r"(z), "r"(w) : "memory"); }
DEVI void stsm2(uint32_t a, uint32_t x, uint32_t y) { asm volatile("stmatrix.sync.aligned.m8n8.x2.shared.b16 [%0], {%1,%2};" :: "r"(a), "r"(x), "r"(y) : "memory"); }
DEVI void fence_smem_async() { asm volatile("fence.proxy.async.shared::cta;" ::: "memory"); }
DEVI uint32_t packh2(float lo, float hi) { uint32_t r; asm("cvt.rn.f16x2.f32 %0, %1, %2;" : "=r"(r) : "f"(hi), "f"(lo)); return r; }
DEVI uint32_t h2_to_bf2(uint32_t w) {
    uint32_t r;
    asm("{.reg .f16 l, h; .reg .f32 a, b; mov.b32 {l, h}, %1; cvt.f32.f16 a, l; cvt.f32.f16 b, h; cvt.rn.bf16x2.f32 %0, b, a;}" : "=r"(r) : "r"(w));
    return r;
}
DEVI uint32_t amax2(uint32_t m, uint32_t w) { return __vmaxu2(m, w & 0x7fff7fffu); }
DEVI uint32_t amax_fold(uint32_t m) { return __reduce_max_sync(0xffffffffu, max(m & 0xffffu, m >> 16)); }
DEVI float bflo(uint32_t w) { return __uint_as_float(w << 16); }
DEVI float bfhi(uint32_t w) { return __uint_as_float(w & 0xffff0000u); }
DEVI void red_b8(void* p, uint32_t a, uint32_t b, uint32_t c, uint32_t d) {
    asm volatile("red.relaxed.gpu.global.add.noftz.v4.bf16x2 [%0], {%1,%2,%3,%4};" :: "l"(p), "r"(a), "r"(b), "r"(c), "r"(d) : "memory");
}
DEVI void red_h8_if(bool on, void* p, uint32_t a, uint32_t b, uint32_t c, uint32_t d) {
    asm volatile("{.reg .pred p; setp.ne.u32 p, %5, 0; @p red.relaxed.gpu.global.add.noftz.v4.bf16x2 [%0], {%1,%2,%3,%4};}" :: "l"(p), "r"(a), "r"(b), "r"(c), "r"(d), "r"((uint32_t)on) : "memory");
}
DEVI void mbar_arrive_warp(uint32_t b) { asm volatile("{.reg .pred p; elect.sync _|p, 0xffffffff; @p mbarrier.arrive.shared::cta.b64 _, [%0];}" :: "r"(b) : "memory"); }
DEVI void bulk_s2c_warp(uint32_t dst, uint32_t src, uint32_t bytes, uint32_t bar) {
    asm volatile("{.reg .pred p; elect.sync _|p, 0xffffffff; @p cp.async.bulk.shared::cluster.shared::cta.mbarrier::complete_tx::bytes [%0], [%1], %2, [%3];}" :: "r"(dst), "r"(src), "r"(bytes), "r"(bar) : "memory");
}
DEVI char* mkptr(uint32_t lo, uint32_t hi) { uint64_t p; asm("mov.b64 %0, {%1, %2};" : "=l"(p) : "r"(lo), "r"(hi)); return (char*)p; }
DEVI void bulk_s2g(void* dst, uint32_t src, uint32_t bytes) { asm volatile("cp.async.bulk.global.shared::cta.bulk_group [%0], [%1], %2;" :: "l"(dst), "r"(src), "r"(bytes) : "memory"); }
DEVI void x_tma(uint32_t dst, const CUtensorMap* m, uint32_t xb, int row, int chunk) {
    asm volatile("cp.async.bulk.tensor.3d.shared::cluster.global.mbarrier::complete_tx::bytes.multicast::cluster [%0], [%1, {%3, %4, %5}], [%2], %6;"
                 :: "r"(dst), "l"(m), "r"(xb), "r"(0), "r"(row), "r"(chunk), "h"((uint16_t)7) : "memory");
}
#define RUNG_(A, B, PA, PB) "mov.u64 " A ", %%clock64;\n cvt.u32.u64 l, " B ";\n sub.s32 l, l, %0;\n setp.ge.s32 " PB ", l, 0;\n @" PA " bra.uni DONE;\n"
DEVI void fine_until(uint32_t t) {
    asm volatile("{.reg .pred p0, p1; .reg .b64 t0, t1; .reg .b32 l;\n setp.ne.u32 p0, 0, 0;\n mov.u64 t1, %%clock64;\n LOOP:\n"
                 RUNG_("t0", "t1", "p0", "p1") RUNG_("t1", "t0", "p1", "p0") RUNG_("t0", "t1", "p0", "p1") RUNG_("t1", "t0", "p1", "p0")
                 RUNG_("t0", "t1", "p0", "p1") RUNG_("t1", "t0", "p1", "p0") RUNG_("t0", "t1", "p0", "p1") RUNG_("t1", "t0", "p1", "p0")
                 "bra.uni LOOP;\n DONE:\n}" :: "r"(t) : "memory");
}
DEVI uint32_t clock_offset() {
    const uint32_t g0 = gtime();
    uint32_t e = clk();
#pragma unroll
    for (int i = 0; i < 7; i++) { const uint32_t g = gtime(), t = clk(); e = g == g0 ? t : e; }
    return ((((g0 >> 5) + 1) * 3686u) >> 6) - e;
}
constexpr int R_X0 = 0;
constexpr int R_K = 110592 + 3072;
constexpr int R_V = R_K + 4608;
constexpr int R_VM = R_V + 8192;
constexpr int PAR = 17920;
constexpr int R_QM = R_VM + 2048 + PAR;
constexpr int R_SC = R_QM + 1536;
constexpr int R_O8 = R_SC + 2048;
constexpr int R_PX = R_O8 + 2048;
constexpr int R_PV = R_PX + 8192;
constexpr int R_Z = R_PV + 4096;
constexpr int R_END = R_Z + 512;
constexpr int R_STAGE = 36864;
constexpr int R_RES = R_STAGE + 8 * 16384;
constexpr int R_WO = R_RES + 16384;
constexpr int R_T4 = R_WO;
constexpr int R_T5 = R_T4 + 4096;
constexpr int R_T6 = R_T5 + 4096;
constexpr int R_DBG = R_T6 + 4096;
constexpr int R_T0 = R_WO + 24576;
constexpr int R_T1 = R_T0 + 2048;
constexpr int R_T2 = R_T1 + 8192;
constexpr int R_MEM = R_T2 + 256;
constexpr int R_BAR = R_MEM + 12288;
constexpr int R_MISC = R_BAR + 384;
constexpr int R_SMEM = R_MISC + 128;
static_assert(R_END <= R_RES && R_SMEM <= 232448, "smem");
enum { BX0 = 0  , BME = 32, BSC = 40  , BML = 56, BW = 64   };
enum { NB_F1 = 1, NB_D = 2, NB_K = 5, NB_G1 = 6, NB_E0 = 7, NB_GO = 8, NB_W1 = 9, NB_H1 = 10, NB_TOK = 11, NB_W2 = 12, NB_F0 = 13 };
enum { M_EPOCH = 0, M_SINK = 4,  M_PASS = 8, M_TGT = 16  , M_RING = 40, M_REF = 48  , M_PROBE = 56  , M_DONE = 64   };
constexpr uint32_t EMPTY = 0xc200u;
constexpr float QS = 0.08838834764831845f * 1.4426950408889634f;

DEVI uint32_t acc_slot(uint32_t s) { return (s & 1) * 128 + (s & 2) * 16384; }
DEVI uint32_t acc_blk(uint32_t m, uint32_t l) { return (((l >> 1) << 2) | ((l & 1) << 1) | ((l & 1) ^ m)) * 4096; }
DEVI uint32_t acc_line(uint32_t i, uint32_t q, uint32_t l) { return acc_blk(q & 1, l) + (q >> 1) * 256 + (i < 4 ? i * 1024 : i * 1024 - 1536); }
DEVI uint32_t acc_stamp(uint32_t m, uint32_t n) { return acc_blk(m, (n >> 3) & 3) + 512 + ((n >> 5) & 1) * 256 + (n >> 6) * 1024 + (n & 7) * 16; }

#define LOAD_TRANSIENT(LA) { _Pragma("unroll") for (int i_ = 0; i_ < NTR; i_++) ldsm4t(w[i_ & 1][i_ >> 1], (LA) + (i_ & 1) * 4096 + (i_ >> 1) * 512); }
#define PIN() asm volatile("{.reg .b64 t; .reg .b32 l, h; mov.u64 t, %%clock64; mov.b64 {l, h}, t; xor.b32 %0, %0, l;}" : "+r"(junk) :: "memory")
#define MMAW(D, T, K, B0, B1) mma16(D, w[T][K][0], w[T][K][1], w[T][K][2], w[T][K][3], B0, B1)

DEVI void bulk_s2g_warp(void* dst, uint32_t src, uint32_t bytes) {
    asm volatile("{.reg .pred p; elect.sync _|p, 0xffffffff; @p cp.async.bulk.global.shared::cta.bulk_group [%0], [%1], %2;}" :: "l"(dst), "r"(src), "r"(bytes) : "memory");
}
DEVI void bulk_commit_warp() { asm volatile("{.reg .pred p; elect.sync _|p, 0xffffffff; @p cp.async.bulk.commit_group;}" ::: "memory"); }
#define PUBLISH(S) { asm volatile("cp.async.bulk.wait_group 0;" ::: "memory"); bar_sync(NB_D, 64); stg_rlx(&g_qflag[S][blockIdx.x / 3][c * 8], lds32(sb + R_MISC + M_RING)); }

DEVI void proj_loop(uint32_t (&w)[2][18][4], unsigned char* smem, const uint32_t sb, const uint32_t c, const int wg, const int q, const uint32_t lane0,
                    const uint32_t la) {
    const uint32_t bar = sb + R_BAR;
    const int p = q ^ (2 * wg);
    const bool c2 = c == 2, both = !c2 && p < 2, aq = c2 ? p < 2 : p != 2;
    const uint32_t lp = pin(sb + lane0 * 16 + p * 1024), ma = pin(sb + lane0 * 16 + wg * 1024);
    {
        const uint32_t l16 = sb + lane0 * 16;
        const int ia = c2 ? p & 1 : min(p, 2), vt = c2 ? 4 + p : 2 * c + p - 2;
        const uint32_t dtok = l16 + (wg ? (aq ? R_K - ((c2 ? 2 : 3) - ia) * 1024 : R_K + ia * 1536) : (both ? R_K + p * 1536 : R_V + vt * 1024));
                const bool lo = lane0 < 16, mq = aq && lo, mv = !both && !lo;
        const uint32_t dmem = sb + (mq ? R_QM + ia * 512 + (lane0 & 8) * 32 + wg * 128 : (mv ? R_PV + p * 1024 : R_K + ia * 1536 + 1024) + wg * 256 + (lane0 & 8) * 16) + (lane0 & 7) * 16;
        stsm4(lp + R_T4 + wg * 512, dtok, la, dmem, dmem + (mq || mv ? 0 : PAR));
        const uint32_t p0 = mapa(sb, c2 ? 0 : c + 1), p1 = mapa(sb, c == 0 ? 2 : c - 1), d = R_VM + vt * 256 + lane0 * 4;
        sts128(lp + R_T5 + wg * 512, p0 + d + wg * PAR, p0 + R_BAR + BSC + wg * 8, p1 + d + wg * PAR, p1 + R_BAR + BSC + wg * 8);
        __syncwarp();
        mbar_wait(bar + BX0, 0);
    }
#pragma unroll 1
    for (int s = 0; s < NSEG; s++) {
        const int xi = s - 3 * ((s * 43) >> 7);
        {
            float d[16];
#define TOKEN(WG, T, AT, NB, ZERO)                                                                                          \
    {                                                                                                                       \
    const uint32_t xd = fresh(desc_lo(sb + xi * 36864)), ad = fresh((64u << 16) | (((sb + R_RES) & 0x3FFFF) >> 4));                     \
    wg_fence();                                                                                                             \
    _Pragma("unroll") for (int i = 0; i < 18; i++) {                                                                        \
        if (i == (AT)) bar_arrive(NB, 256);                                                                                 \
        const int j = i < SSP ? i + 2 : (i < SSP + 2 ? i - SSP : i), g = 18 * WG + j;                                              \
        const uint64_t bd = desc_of(xd + (g >> 2) * 256 + (g & 3) * 2);                                                     \
        if (2 * j + (T) < NTR) wgmma32_ss<1>(d, desc_sw32(ad + ((WG * 8192 + (T) * 4096 + j * 512) >> 4)), bd);                          \
        else if (i == 0 && ZERO) wgmma32<0>(d, w[T][j], bd);                                                                \
        else wgmma32<1>(d, w[T][j], bd);                                                                                    \
    }                                                                                                                       \
    wg_commit();                                                                                                            \
    if ((AT) == 18) bar_arrive(NB, 256);                                                                                    \
    }
#define HANDOVER(WG)                                                                                                        \
    {                                                                                                                       \
        const uint32_t xa = lp + R_PX + WG * 4096;                                                                          \
        sts128(xa, pack2(d[0], d[1]), pack2(d[2], d[3]), pack2(d[4], d[5]), pack2(d[6], d[7]));                             \
        sts128(xa + 512, pack2(d[8], d[9]), pack2(d[10], d[11]), pack2(d[12], d[13]), pack2(d[14], d[15]));                 \
    }
            if (wg == 0) {
                bar_sync(NB_G1, 256);
                TOKEN(0, 0, -1, 0, 1)
                const uint32_t la = tab1(lp + R_T4 + 128);
                if (!PE) wg_wait0();
                if (q == 1 && s > 0 && (!ONE || c == 0)) {
                    const uint2 tt = tab2(lp + R_T2 - 1024), rt = lds64(sb + R_MISC + M_PROBE);
                    const uint32_t tag = (lds32(sb + R_MISC + M_EPOCH) * 64 + s) << 22, side = rt.y < rt.x;
                    const uint32_t* const sp = (const uint32_t*)mkptr((tt.x ^ (side << 12)) + acc_slot(s - 1), tt.y);
                    uint32_t v0 = ldg_rlx(sp), v1 = ldg_rlx(sp + 64), v2 = ldg_rlx(sp + 256);
                    if (PE) wg_wait0();
                    bar_sync(NB_E0, 256);
                    HANDOVER(0)
                    bar_arrive(NB_GO, 384);
                    if (!TR0) LOAD_TRANSIENT(la)
                    const uint2 tr = lds64(sb + R_MISC + M_REF);
                    int n = 0;
                    while (__any_sync(0xffffffffu, (diff2(v0, v1, tag) | (v2 ^ tag)) >> 22)) {
                        v0 = ldg_rlx(sp); v1 = ldg_rlx(sp + 64); v2 = ldg_rlx(sp + 256);
                        if (++n > (1 << 22)) TRAP(1002);
                    }
                    const int m = __reduce_max_sync(0xffffffffu, max(max((int)((v0 - tr.y) << 10), (int)((v1 - tr.y) << 10)), (int)((v2 - tr.y) << 10))) >> 10;
                    const uint32_t tn = tr.x + min(m, DMAX) + (CT - 65), tf = tn - (s > 2 ? FE : 0);
                    sts128(sb + R_MISC + M_TGT, side ? tf : tn, s, side ? tn : tf, s);
                    EV(0);
                    if (EVX(0)) { EVV(11, m); EVV(10, tr.x); }
                } else {
                    if (PE) wg_wait0();
                    EV(3);
                    bar_sync(NB_E0, 256);
                    HANDOVER(0)
                    bar_arrive(NB_GO, 384);
                    if (!TR0) LOAD_TRANSIENT(la)
                }
                bar_sync(NB_F0, 256);
                TOKEN(0, 1, F1T, NB_F1, 1)
                const uint32_t dtok = tab1(lp + R_T4) + (s & 1) * PAR;
                bar_sync(NB_H1, 256);
                const uint4 oa = lds128(lp + R_PX + 4096);
                const uint4 ob = lds128(lp + R_PX + 4608);
                wg_wait0();
                const uint32_t u0 = pack2(d[0] + bflo(oa.x), d[1] + bfhi(oa.x)), u1 = pack2(d[2] + bflo(oa.y), d[3] + bfhi(oa.y));
                stsm4(dtok, u0, u1, pack2(d[4] + bflo(oa.z), d[5] + bfhi(oa.z)), pack2(d[6] + bflo(oa.w), d[7] + bfhi(oa.w)));
                stsm4(dtok + 512, pack2(d[8] + bflo(ob.x), d[9] + bfhi(ob.x)), pack2(d[10] + bflo(ob.y), d[11] + bfhi(ob.y)),
                      pack2(d[12] + bflo(ob.z), d[13] + bfhi(ob.z)), pack2(d[14] + bflo(ob.w), d[15] + bfhi(ob.w)));
                bar_arrive(NB_TOK, 384);
                if (TR0) LOAD_TRANSIENT(la)
                mbar_wait(bar + BME, s & 1);
            } else {
                const uint2 tw = tab2(lp + R_T4 + 512);
                bar_sync(NB_GO, 384);
                TOKEN(1, 1, F0T, NB_F0, 1)
                const uint4 oa = lds128(lp + R_PX), ob = lds128(lp + R_PX + 512);
                wg_wait0();
                HANDOVER(1)
                bar_arrive(NB_H1, 256);
                {
                    const uint32_t ox[8] = {oa.x, oa.y, oa.z, oa.w, ob.x, ob.y, ob.z, ob.w};
#pragma unroll
                    for (int j = 0; j < 8; j++) { d[2 * j] = bflo(ox[j]); d[2 * j + 1] = bfhi(ox[j]); }
                }
                if (!TR1) LOAD_TRANSIENT(tw.y)
                bar_sync(NB_F1, 256);
                TOKEN(1, 0, -1, 0, 0)
                if (TR1 == 1) LOAD_TRANSIENT(tw.y)
                if (q == 3 && s > 0) PUBLISH(s - 1)
                if (TR1 == 2) LOAD_TRANSIENT(tw.y)
                const float qs = aq ? QS : 1.f;
                const uint32_t dtok = tw.x + (s & 1) * PAR;
                if (MW == 1) mbar_wait(bar + BME, s & 1);
                uint32_t there = 0;
                if (MW == 2) asm volatile("{.reg .pred p; mbarrier.test_wait.parity.shared::cta.b64 p, [%1], %2; selp.u32 %0, 1, 0, p;}" : "=r"(there) : "r"(bar + BME), "r"(s & 1) : "memory");
                wg_wait0();
                EV(13);
#pragma unroll
                for (int hf = 0; hf < 2; hf++) {
                    const float* e = d + 8 * hf;
                    stsm4(dtok + hf * 512, pack2(e[0] * qs, e[1] * qs), pack2(e[2] * qs, e[3] * qs), pack2(e[4] * qs, e[5] * qs), pack2(e[6] * qs, e[7] * qs));
                }
                EV(12);
                bar_arrive(NB_TOK, 384);
                if (MW != 1 && !there) mbar_wait(bar + BME, s & 1);
            }
#undef TOKEN
#undef HANDOVER
        }
        uint4 b[12];
        float a[4][4];
      redo:
#pragma unroll
        for (int j = 0; j < 4; j++) a[0][j] = a[1][j] = a[2][j] = a[3][j] = 0.f;
#define LD(i) b[i] = ldm128(ma + R_MEM + ((i) >> 1) * 2048 + ((i) & 1) * 512);
#define BK0(k) ((k) % 3 == 2 ? b[(k) / 3 * 2].z : b[(k) / 3 * 2 + (k) % 3].x)
#define BK1(k) ((k) % 3 == 2 ? b[(k) / 3 * 2].w : b[(k) / 3 * 2 + (k) % 3].y)
#define KS(T, k) MMAW(a[2 * (T) + ((k) & 1)], T, k, BK0(k), BK1(k));
        uint32_t chk = 0, dmem;
        uint4 tv;
#pragma unroll
        for (int i = 0; i < 4; i++) LD(i)
#pragma unroll
        for (int k = 0; k < LW; k++) {
            if (k % 3 == 2) { chk = or3(chk, b[k / 3 * 2].w, b[k / 3 * 2 + 1].w); b[k / 3 * 2].w = b[k / 3 * 2 + 1].z | chk; }
            KS(0, k) KS(1, k)
        }
        if (DL) mbar_wait(bar + BML, s & 1);
#pragma unroll
        for (int i = 4; i < 12; i++) LD(i)
        tv = lds128(lp + fresh((s & 1) * 512) + R_T5); dmem = tab1(lp + fresh(wg * 512 + (s & 1) * 128) + R_T4 + 256);
#pragma unroll
        for (int k = LW; k < 18; k++) {
            if (k % 3 == 2) { chk = or3(chk, b[k / 3 * 2].w, b[k / 3 * 2 + 1].w); b[k / 3 * 2].w = b[k / 3 * 2 + 1].z | chk; }
            KS(0, k) KS(1, k)
        }
        float r[4];
        {
            const float s0 = aq ? QS : 1.f;
#pragma unroll
            for (int j = 0; j < 4; j++) { r[j] = a[3][j] + a[2][j]; a[0][j] = fmaf(a[1][j], s0, a[0][j] * s0); }
            stsm4(dmem, pack2(a[0][0], a[0][1]), pack2(a[0][2], a[0][3]), pack2(r[0], r[1]), pack2(r[2], r[3]));
            const uint32_t bad = __any_sync(0xffffffffu, chk);
            asm volatile("{.reg .pred p; setp.eq.u32 p, %0, 0; @p bar.sync %1, 384;}" :: "r"(bad), "n"((int)NB_K) : "memory");
            const uint2 o = tab2(lp + R_PV);
            if (!(bad | (wg ^ 1) | both)) {
                const uint32_t lo = pack2(r[0] + bflo(o.x), r[1] + bfhi(o.x)), hi = pack2(r[2] + bflo(o.y), r[3] + bfhi(o.y)), v2 = (tv.x & 0xffffffu) | (sb & 0xff000000u);
                sta32(tv.x, lo, tv.y); sta32(tv.z, lo, tv.w);
                sta32(tv.x + 128, hi, tv.y); sta32(tv.z + 128, hi, tv.w);
                sts32(v2, lo); sts32(v2 + 128, hi);
            }
            if (__builtin_expect(bad, 0)) goto repair;
        }
#undef LD
#undef KS
#undef BK0
#undef BK1
        if (wg == 0) { EV(1); continue; }
        EV(2);
        {
            if (q != 3) bar_arrive(NB_W1, 256);
            if (q == 3) {
                const uint32_t area = __shfl_sync(0xffffffffu, lds32(sb + R_MISC + M_RING), 0) & 63, so = sb + (s & 1) * PAR;
                unsigned char* const dst = g_qkv + (size_t)(area * 32 + blockIdx.x / 3) * 30720;
                unsigned char* const dk = dst + c * 7680 + (c2 ? 3072 : 4096);
                sts32(sb + R_MISC + M_SINK, clk());
                bar_sync(NB_W1, 256);
                fence_smem_async();
                bulk_s2g_warp(dst + 20480 + c * 2048, so + R_V + c * 2048, c2 ? 4096 : 2048);
                bulk_s2g_warp(dst + 28672 + c * 512, so + R_VM + c * 512, c2 ? 1024 : 512);
                bulk_s2g_warp(dk, so + R_K + 1024, 512);
                bulk_s2g_warp(dk + 1536, so + R_K + 2560, 512);
                if (!c2) bulk_s2g_warp(dk + 3072, so + R_K + 4096, 512);
                bulk_commit_warp();
            } else if (q == 2) {
                const uint4 tz = lds128(lp + R_T0 + 1536);
                const uint32_t pa = sb + R_MISC + M_PROBE + (((blockIdx.x >> 2) ^ s) & 1) * 4, best = lds32(pa);
                char* const zp = mkptr((tz.x ^ ((s & 1) << 12)) + acc_slot(s + 2), tz.y);
                uint32_t z;
                const uint32_t t1 = clk();
                asm volatile("atom.relaxed.gpu.global.exch.b32 %0, [%1], %2;" : "=r"(z) : "l"(zp), "r"(tz.w) : "memory");
                sts32(sb + R_MISC + M_SINK, z);
                sts32(pa, min(best, clk() - t1));
            }
        }
        continue;
      repair:
        {
            if (atomicAdd((unsigned*)(smem + R_MISC + M_PASS), 1) > (1u << 28)) TRAP(1000);
#pragma unroll 1
            for (int i = 0; i < 2; i++) {
                const uint2 tb = tab2(ma + fresh(i * 512 + ((s - 1) & 3) * 2048) + R_T1 + 256);
                const uint32_t md = ma + ((ma ^ (tb.y >> 31)) & 256) + R_MEM + i * 2048;
                const char* const ga = mkptr(tb.x, tb.y);
                cp16(md, ga); cp16(md + 256, ga + 1024); cp16(md + 4096, ga + 2048); cp16(md + 4352, ga + 3072);
                cp16(md + 8192, ga + 2560); cp16(md + 8448, ga + 3584);
            }
            asm volatile("cp.async.wait_all;" ::: "memory");
            __syncwarp();
            const uint32_t la = tab1(lp + fresh(wg * 512) + R_T4 + 128);
            LOAD_TRANSIENT(la)
            goto redo;
        }
    }
    if (wg == 1) PT(18);
    if (wg == 1 && q == 3) PUBLISH(NSEG - 1)
}

DEVI void attn_loop(const uint32_t (&wo)[3][8][4], const CUtensorMap* xmap, const CUtensorMap* amap, unsigned char* smem, const uint32_t sb, const uint32_t c, const int q,
                    const uint32_t lane0) {
    const uint32_t bar = sb + R_BAR;
    const bool c2 = c == 2;
    const uint32_t l16 = pin(sb + lane0 * 16);
{
        const uint4 t = lds128(l16 + q * 512 + R_T0);
        sts128(l16 + q * 512 + R_T6, t.x, t.y, t.z, t.w);
        sts128(l16 + q * 512 + R_T6 + 2048, t.x, t.y + (q < 3 ? 8 : 0), t.z, t.w + 8);
    }
#define UA(x) (l16 + fresh(x))
#define DUMP_QK()                                                                                                             \
    {                                                                                                                         \
        const uint32_t e64 = lds32(sb + R_MISC + M_EPOCH) * 64, so = sb + (s & 1) * PAR + R_K, nq = c2 ? 2048 : 3072;         \
        const uint32_t area = __shfl_sync(0xffffffffu, s & ((uint32_t)lds32(sb + R_MISC + M_DONE) == e64 + s - QR ? QR - 1 : 63), 0); \
        sts32(sb + R_MISC + M_RING, e64 + area);                                                                              \
        unsigned char* const dst = g_qkv + (size_t)(area * 32 + blockIdx.x / 3) * 30720 + c * 7680;                           \
        bulk_s2g_warp(dst, so - nq, nq + 1024);                                                                               \
        bulk_s2g_warp(dst + nq + 1536, so + 1536, 1024);                                                                      \
        if (!c2) bulk_s2g_warp(dst + 6144, so + 3072, 1024);                                                                  \
        bulk_commit_warp();                                                                                                   \
    }
#pragma unroll 1
    for (int s = 0; s < NSEG - 1; s++) {
        const uint32_t par = (s & 1) * PAR;
        uint32_t junk = 0;
        const uint4 ta = lds128(UA(q * 512 + (s & 1) * 2048) + R_T6);
        bar_sync(NB_TOK, 384);
#define SCORES()                                                                                                   \
    float x[2][3][4];                                                                                              \
    _Pragma("unroll") for (int t = 0; t < 3; t++) {                                                                \
        _Pragma("unroll") for (int j = 0; j < 4; j++) x[0][t][j] = x[1][t][j] = 0.f;                               \
        mma16(x[0][t], qf[t][0], qf[t][1], qf[t][2], qf[t][3], kf[t][0], kf[t][1]);                                \
        mma16(x[1][t], qf[t][0], qf[t][1], qf[t][2], qf[t][3], kf[t][2], kf[t][3]);                                \
    }                                                                                                              \
    if (G1T == 0) { PIN(); bar_arrive(NB_G1, 256); PIN(); }                                                        \
    float y[4];                                                                                                    \
    _Pragma("unroll") for (int j = 0; j < 4; j++)                                                                  \
        y[j] = ((x[j >> 1][0][j & 1] + x[j >> 1][0][2 + (j & 1)]) + (x[j >> 1][1][j & 1] + x[j >> 1][1][2 + (j & 1)])) + (x[j >> 1][2][j & 1] + x[j >> 1][2][2 + (j & 1)]);
        if (q < 2) {
            uint32_t qf[3][4], kf[3][4];
#pragma unroll
            for (int t = 0; t < 3; t++) ldsm4t(kf[t], UA(q * 512 + par) + R_K + t * 1536);
            bar_sync(NB_K, 384);
#pragma unroll
            for (int t = 0; t < 3; t++) ldsm4t(qf[t], l16 + R_QM + t * 512);
            SCORES()
            const uint32_t u0 = pack2(y[0], y[1]), u1 = pack2(y[2], y[3]);
            sta32(ta.x, u0, ta.y); sta32(ta.z, u0, ta.w);
            sta32(ta.x + 128, u1, ta.y); sta32(ta.z + 128, u1, ta.w);
            stsm2(UA(q * 256) + R_SC, u0, u1);
            if (G1T == 1) bar_arrive(NB_G1, 256);
        } else if (q == 2) {
            if (s > 0 && s + 2 < NSEG) {
                const int xi = s - 1 - 3 * (((s - 1) * 43) >> 7);
                mbar_wait(bar + BME, s & 1);
                spin_until(clk() + XD);
                asm volatile("{.reg .pred p; elect.sync _|p, 0xffffffff;\n"
                             "@p mbarrier.arrive.expect_tx.shared::cta.b64 _, [%2], 36864;\n"
                             "@p cp.async.bulk.tensor.3d.shared::cluster.global.mbarrier::complete_tx::bytes.multicast::cluster [%0], [%1, {%3, %4, %5}], [%2], %6;}"
                             :: "r"(sb + xi * 36864 + c * 12288), "l"(xmap), "r"(bar + BX0 + xi * 8), "r"(0), "r"((s + 2) * 32), "r"(c * 3), "h"((uint16_t)7) : "memory");
            }
            uint32_t qf[3][4], kf[3][4];
            bar_sync(NB_K, 384);
#pragma unroll
            for (int t = 0; t < 3; t++) { ldsm4t(qf[t], l16 + R_QM + t * 512); ldsm4t(kf[t], UA(q * 512 + par) + R_K + t * 1536); }
            SCORES()
            const uint32_t u0 = pack2(y[0] + y[2], y[1] + y[3]);
            sta32(ta.x, u0, ta.y);
            sta32(ta.z, u0, ta.w);
            EV(4);
            stsm2(l16 + R_SC + 1792, u0, u0);
            if (G1T == 1) bar_arrive(NB_G1, 256);
        } else {
            {
                const uint32_t vt = R_V + par + c * 2048, p0 = mapa(sb, c2 ? 0 : c + 1), p1 = mapa(sb, c == 0 ? 2 : c - 1);
                fence_smem_async();
                bulk_s2c_warp(p0 + vt, sb + vt, c2 ? 4096 : 2048, p0 + R_BAR + BSC + (s & 1) * 8);
                bulk_s2c_warp(p1 + vt, sb + vt, c2 ? 4096 : 2048, p1 + R_BAR + BSC + (s & 1) * 8);
            }
            DUMP_QK()
            {
                const int s3 = ((s + 1) * 43) >> 7;
                mbar_wait(bar + BX0 + (s + 1 - 3 * s3) * 8, s3 & 1);
                if (G1T < 2) bar_arrive(NB_G1, 256);
            }
            const uint32_t tag = (lds32(sb + R_MISC + M_EPOCH) * 64 + s + 1) << 22;
            sts32(sb + R_MISC + M_REF + 4, clock_offset());
            bar_sync(NB_K, 384);
            const uint32_t off = lds32(sb + R_MISC + M_REF + 4);
            const uint32_t t = off == 0x9e3779b9u ? 0u : clk();
            sts64(sb + R_MISC + M_REF, t, t + off);
            EVV(9, t);
            stg_rlx((uint32_t*)mkptr(ta.z + acc_slot(s), ta.y), ((t + off) & 0x3fffffu) | tag);
        }
#undef SCORES
        bar_sync(NB_W1, 256);
        uint32_t vf[4][4];
        const uint32_t vo = par + q * 2048;
        float o0[4], o1[4], sum;
        {
            uint32_t aw[5], bw[5], cw[5];
            ldsm4(aw, l16 + R_SC); aw[4] = tab1(l16 + R_SC + 1792);
            if (G1T == 2) { bar_arrive(NB_G1, 256); PIN(); }
            sts32(sb + R_MISC + M_SINK, or3(aw[0], aw[4], junk));
            mbar_wait(bar + BSC + (s & 1) * 8, (s >> 1) & 1);
            ldsm4(bw, l16 + R_SC + 512); ldsm4(cw, l16 + R_SC + 1024);
            { const uint2 t = tab2(l16 + R_SC + 1536); bw[4] = t.x; cw[4] = t.y; }
            junk = clk();
            ldsm4(vf[0], UA(vo) + R_V); ldsm4(vf[2], UA(vo) + R_V + 1024);
            PIN();
            EV(5);
            float x[10];
#pragma unroll
            for (int i = 0; i < 5; i++) { x[2 * i] = (bflo(aw[i]) + bflo(bw[i])) + bflo(cw[i]); x[2 * i + 1] = (bfhi(aw[i]) + bfhi(bw[i])) + bfhi(cw[i]); }
            float mx = fmaxf(fmaxf(fmaxf(fmaxf(x[0], x[1]), fmaxf(x[2], x[3])), fmaxf(fmaxf(x[4], x[5]), fmaxf(x[6], x[7]))), fmaxf(x[8], x[9]));
            const float m1 = __shfl_xor_sync(0xffffffffu, mx, 1), m2 = __shfl_xor_sync(0xffffffffu, mx, 2), m3 = __shfl_xor_sync(0xffffffffu, mx, 3);
            uint32_t vm[4];
            PIN();
            ldsm4(vf[1], UA(vo) + R_V + 512); ldsm4(vf[3], UA(vo) + R_V + 1536); ldsm4(vm, UA(q * 512 + par) + R_VM);
            bar_arrive(NB_E0, 256);
            PIN();
            mx = fmaxf(fmaxf(mx, m1), fmaxf(m2, m3));
            float e[10];
#pragma unroll
            for (int j = 0; j < 4; j++) o0[j] = o1[j] = 0.f;
#pragma unroll
            for (int i = 0; i < 10; i++) x[i] -= mx;
#pragma unroll
            for (int i = 0; i < 7; i++) { if (i == 4) PIN(); e[i] = ex2v(x[i]); }
            const uint32_t p0 = pack2(e[0], e[1]), p1 = pack2(e[2], e[3]);
            mma16(o0, vf[0][0], vf[0][1], vf[0][2], vf[0][3], p0, p1);
            mma16(o1, vf[2][0], vf[2][1], vf[2][2], vf[2][3], p0, p1);
#pragma unroll
            for (int i = 7; i < 10; i++) { if (i == 8) PIN(); e[i] = ex2v(x[i]); }
            PIN();
            const uint32_t p2 = pack2(e[4], e[5]), p3 = pack2(e[6], e[7]), p4 = pack2(e[8], e[9]);
            mma16(o0, vf[1][0], vf[1][1], vf[1][2], vf[1][3], p2, p3);
            mma16(o1, vf[3][0], vf[3][1], vf[3][2], vf[3][3], p2, p3);
            mma8(o0, vm[0], vm[1], p4);
            mma8(o1, vm[2], vm[3], p4);
            sum = (((e[0] + e[1]) + (e[2] + e[3])) + ((e[4] + e[5]) + (e[6] + e[7]))) + (e[8] + e[9]);
        }
        asm volatile("stmatrix.sync.aligned.m8n8.x1.shared.b16 [%0], {%1};" :: "r"(l16 + R_Z), "r"(__float_as_uint(sum)) : "memory");
        const uint32_t ls = (fresh(l16) & 48) * 2 + sb;
        const float4 s0 = lds128f(ls + R_Z), s1 = lds128f(ls + R_Z + 16);
        stsm4(UA(q * 512) + R_O8, pack2(o0[0], o0[1]), pack2(o0[2], o0[3]), pack2(o1[0], o1[1]), pack2(o1[2], o1[3]));
        EV(6);
        bar_sync(NB_W2, 128);
        uint32_t of[4][4];
        ldsm4t(of[0], l16 + R_O8);
        PIN();
#pragma unroll
        for (int i = 1; i < 4; i++) ldsm4t(of[i], l16 + R_O8 + i * 512);
        PIN();
        const float f0 = rcp_fast((s0.x + s0.y) + (s0.z + s0.w)), f1 = rcp_fast((s1.x + s1.y) + (s1.z + s1.w));
        float acc[3][2][4];
        uint2 tb;
#pragma unroll
        for (int m = 0; m < 3; m++)
#pragma unroll
            for (int j = 0; j < 4; j++) acc[m][0][j] = acc[m][1][j] = 0.f;
#pragma unroll
        for (int i = 0; i < 24; i++) {
            const int kk = i / 3, m = i % 3;
            if (i % 3 == 0 && i) PIN();
            if (i == 12) tb = tab2(UA(q * 512 + (s & 3) * 2048) + R_T1);
            if (i == GOE) { if (i % 3) PIN(); bar_arrive(NB_GO, 384); PIN(); }
            mma16(acc[m][kk & 1], wo[m][kk][0], wo[m][kk][1], wo[m][kk][2], wo[m][kk][3], of[kk >> 1][(kk & 1) * 2], of[kk >> 1][(kk & 1) * 2 + 1]);
        }
        PIN();
        if (GOE == 24) { bar_arrive(NB_GO, 384); PIN(); }
        char* const gw = mkptr(tb.x, tb.y);
        uint32_t wa[3], wb[3];
#pragma unroll
        for (int m = 0; m < 3; m++) {
            wa[m] = pack2(fmaf(acc[m][1][0], f0, acc[m][0][0] * f0), fmaf(acc[m][1][2], f0, acc[m][0][2] * f0));
            wb[m] = pack2(fmaf(acc[m][1][1], f1, acc[m][0][1] * f1), fmaf(acc[m][1][3], f1, acc[m][0][3] * f1));
        }
        red_b8(gw, wa[0], wa[1], wa[2], 0x3f80u); red_b8(gw + 1024, wb[0], wb[1], wb[2], 0x3f80u);
        if (GOE > 24) bar_arrive(NB_GO, 384);
        sts32(sb + R_MISC + M_SINK, junk);
        const uint32_t t0 = clk();
        if (EVX(0)) EVV(7, t0);
        if (q < 2) {
          if (!ONE || c == 0) {
            uint2 tg = lds64(sb + R_MISC + M_TGT + q * 8);
            for (int n = 0; tg.y != s + 1; tg = lds64(sb + R_MISC + M_TGT + q * 8)) if (++n > (1 << 26)) TRAP(1003);
            fine_until(t0 + max((int)(tg.x - t0), DMIN) + (c ? DL : 0));
#pragma unroll
            for (uint32_t j = ONE ? 0 : c; j < (ONE ? 3 : c + 1); j++)
            asm volatile("{.reg .pred p; elect.sync _|p, 0xffffffff;\n"
                         "@p cp.async.bulk.tensor.5d.shared::cluster.global.mbarrier::complete_tx::bytes.multicast::cluster [%0], [%1, {%3, %4, %4, %4, %5}], [%2], %6;}"
                         :: "r"(sb + R_MEM + j * 4096 + q * 2048), "l"(amap + q), "r"(bar + (DL && j ? BML : BME)), "r"((s & 1) * 64), "r"(0), "r"((s & 2) * 64 + (j ? 6 + 2 * j : 0)), "h"((uint16_t)7) : "memory");
            EV(8);
          }
        } else if (q == 2) {
            if (l16 == sb) {
                cp16(sb + R_MISC + M_DONE, &g_oflag[max(s + 1 - QR, 0)][blockIdx.x / 3][0]);
                mbar_expect(bar + BME, DL ? 4096 : 12288);
                if (DL) mbar_expect(bar + BML, 8192);
                mbar_expect(bar + BSC + 8 - (s & 1) * 8, (c2 ? 1024 : 1536) * (s < NSEG - 2 ? 5 : 1) + (s < NSEG - 2 ? 1280 : 0));
            }
        } else {
            asm volatile("cp.async.bulk.wait_group 0;" ::: "memory");
            bar_arrive(NB_D, 64);
        }
    }
    bar_sync(NB_TOK, 384);
    if (q == 3) {
        const int s = NSEG - 1;
        fence_smem_async();
        DUMP_QK()
    }
    bar_arrive(NB_K, 384);
    bar_arrive(NB_W1, 256);
    if (q == 3) {
        asm volatile("cp.async.bulk.wait_group 0;" ::: "memory");
        bar_arrive(NB_D, 64);
    }
    mbar_wait(bar + BSC + 8, 1);
}

struct Maps { CUtensorMap x, acc[2], w16[3], w32[3], wo; };
DEVI void tma2d(uint32_t dst, const CUtensorMap* m, uint32_t bar, int x, int y) {
    asm volatile("{.reg .pred p; elect.sync _|p, 0xffffffff;\n"
                 "@p cp.async.bulk.tensor.2d.shared::cluster.global.mbarrier::complete_tx::bytes [%0], [%1, {%3, %4}], [%2];}"
                 :: "r"(dst), "l"(m), "r"(bar), "r"(x), "r"(y) : "memory");
}

__global__ void __launch_bounds__(384, 1)
rk_kernel(const __grid_constant__ Maps maps, const __nv_bfloat16* __restrict__ xraw, const __nv_bfloat16* __restrict__ mem0) {
    extern __shared__ __align__(1024) unsigned char smem[];
    const uint32_t sb = smem_u32(smem);
    const int tid = threadIdx.x;
    const int warp = __shfl_sync(0xffffffffu, tid >> 5, 0), q = warp & 3;
    const int h = blockIdx.x / 3;
    const uint32_t c = blockIdx.x - 3 * h;
    const uint32_t bar = sb + R_BAR;
    GT(0, 0);
    if (tid >= 64 && tid < 74) asm volatile("prefetch.tensormap [%0];" :: "l"(&maps.x + (tid - 64)) : "memory");
    if (tid < 18) { mbar_init(bar + BW + tid * 8, 1); mbar_expect(bar + BW + tid * 8, tid >= 10 ? 6144 : (tid % 5 == 4 ? 8192 : 16384)); }
    if (tid == 32) {
        for (int i = 0; i < 3; i++) { mbar_init(bar + BX0 + i * 8, 1); mbar_expect(bar + BX0 + i * 8, 36864); }
        mbar_init(bar + BSC, 1); mbar_init(bar + BSC + 8, 1); mbar_init(bar + BME, 1); mbar_init(bar + BML, 1); mbar_arrive(bar + BME); mbar_arrive(bar + BML);
        mbar_expect(bar + BSC, c == 2 ? 6400 : 8960);
        asm volatile("fence.mbarrier_init.release.cluster;" ::: "memory");
    }
    if (warp < 2) fence_smem_async();
    __syncthreads();
    asm volatile("griddepcontrol.launch_dependents;");

    if (warp < 8) {
        const int wg = warp >> 2, p = q ^ (2 * wg);
        const uint32_t bw = bar + BW + wg * 40, st = sb + R_STAGE + wg * 65536;
        const int f2 = h * 128 + (c == 2 ? 96 : c * 64), f1 = h * 128 + 32 + c * 16, fv = h * 128 + c * 32;
        const bool single = c != 2 && p >= 2;
        if (wg == 0) PT(1);
#pragma unroll 1
        for (int i = 0; i < 4; i++) {
            const uint32_t dst = st + i * 16384 + q * 4096;
            const int row = wg * 288 + 32 + i * 64;
            if (q < 3 || c == 2) tma2d(dst, maps.w32 + min(q, 2), bw + i * 8, q < 2 ? f2 : fv + (q - 2) * 32, row);
            else {
#pragma unroll 1
                for (int j = 0; j < 4; j++) tma2d(dst + j * 1024, maps.w16 + (j < 2), bw + i * 8, f1, row + (j & 1) * 32);
            }
        }
        tma2d(sb + R_RES + wg * 8192 + q * 1024, maps.w16 + (c == 2 ? p >> 1 : p == 2), bw + 32, single ? f1 : f2 + (p & 1) * 16, wg * 288);
        tma2d(sb + R_RES + wg * 8192 + q * 1024 + 4096, maps.w16 + (c == 2 || p >= 2 ? 2 : 1), bw + 32, c == 2 ? fv + p * 16 : (p >= 2 ? fv : f2) + (p & 1) * 16, wg * 288);
        if (wg == 0) PT(0);
        asm volatile("setmaxnreg.inc.sync.aligned.u32 %0;" :: "n"(RP));
        const uint32_t lane = pin(tid & 31);
        uint32_t w[2][18][4];
        const uint32_t row = ((lane >> 4) << 3) + (lane & 7), ln = row * 32 + ((((lane >> 3) ^ (lane >> 2)) & 1) << 4);
        const uint32_t la = sb + R_RES + wg * 8192 + q * 1024 + ln;
        {
            const uint32_t lw = row * 64 + ((((p & 1) * 2 + ((lane >> 3) & 1)) ^ ((lane >> 1) & 3)) << 4);
            const uint32_t a0 = st + (single ? 12288 + (p & 1) * 2048 + ln : (c == 2 ? p >> 1 : 0) * 4096 + lw), s0 = single ? 512 : 1024;
            const uint32_t a1 = st + ((c == 2 ? 2 : 1) + (p >> 1)) * 4096 + lw;
#pragma unroll
            for (int i = 0; i < 4; i++) {
                mbar_wait(bw + i * 8, 0);
                if (wg == 0 && (i & 1)) PT(2 + i / 2);
#pragma unroll
                for (int j = 0; j < 4; j++) { ldsm4t(w[0][2 + i * 4 + j], a0 + j * s0 + i * 16384); ldsm4t(w[1][2 + i * 4 + j], a1 + j * 1024 + i * 16384); }
            }
            mbar_wait(bw + 32, 0);
            if (wg == 0) PT(4);
#pragma unroll
            for (int j = 0; j < 4; j++) ldsm4t(w[j >> 1][j & 1], la + (j >> 1) * 4096 + (j & 1) * 512);
        }
        bar_sync(0, 384);
        cluster_arrive_rlx();
        GT(0, 1);
        if (c == 2) sts128(sb + (q == 3 ? R_QM + 1024 : R_K + 3072 + q * 512 + wg * PAR) + lane * 16, 0, 0, 0, 0);
        cluster_wait();
        proj_loop(w, smem, sb, c, wg, q, lane, la);
    } else {
        asm volatile("setmaxnreg.dec.sync.aligned.u32 %0;" :: "n"(504 - 2 * RP));
        const uint32_t jw = (c + 3 - q % 3) % 3, bw = bar + BW + 80 + q * 16;
        const int wx = (q >> 1) * 288 + jw * 96 + (q & 1) * 48;
        const uint32_t lane0 = pin(tid & 31);
        const uint32_t lane = lane0, n = blockIdx.x;
        volatile uint32_t* const misc = (volatile uint32_t*)(smem + R_MISC);
        uint32_t z;
        asm volatile("atom.relaxed.gpu.global.exch.b32 %0, [%1], %2;" : "=r"(z) : "l"((char*)g_acc + acc_slot(q) + acc_line(n >> 4, (n >> 2) & 3, n & 3) + lane * 4), "r"((lane & 3) == 3 ? EMPTY : 0) : "memory");
        const unsigned epoch = g_epoch[36 + n] + 1;
        {
            uint32_t m0[3][6];
#pragma unroll
            for (int i = 0; i < 18; i++) m0[i / 6][i % 6] = __ldg((const uint32_t*)mem0 + (lane >> 2) * 288 + (q * 18 + i) * 4 + (lane & 3));
            if (q < 3)
                asm volatile("{.reg .pred p; elect.sync _|p, 0xffffffff;\n"
                             "@p cp.async.bulk.tensor.3d.shared::cluster.global.mbarrier::complete_tx::bytes [%0], [%1, {%3, %3, %4}], [%2];}"
                             :: "r"(sb + R_X0 + q * 12288), "l"(&maps.x), "r"(bar + BX0), "r"(0), "r"(q * 3) : "memory");
            tma2d(sb + R_WO + q * 6144, &maps.wo, bw, wx, h * 128);
            asm volatile("{.reg .pred p; elect.sync _|p, 0xffffffff; @p cp.async.bulk.prefetch.tensor.2d.L2.global [%0, {%1, %2}];}" :: "l"(&maps.wo), "r"(wx), "r"(h * 128 + 64) : "memory");
            PT(5);
            const uint32_t a = sb + R_MEM + (q & 1) * 6144 + (q >> 1) * 1024 + lane * 16;
#pragma unroll
            for (int i = 0; i < 6; i++) sts128(a + (i >> 1) * 2048 + (i & 1) * 512, m0[i >> 1][(i & 1) * 2], m0[i >> 1][(i & 1) * 2 + 1], m0[i >> 1][4 + (i & 1)], z & (lane >> 5));
        }
        bar_sync(NB_W2, 128);
        if (tid == 256) {
            stg_rlx(&g_pub[n], epoch);
            g_epoch[36 + n] = epoch;
             misc[M_PASS / 4] = 0; misc[M_TGT / 4 + 1] = 0; misc[M_TGT / 4 + 3] = 0; misc[M_PROBE / 4] = misc[M_PROBE / 4 + 1] = 0xffffffffu;
            misc[M_EPOCH / 4] = epoch; misc[M_DONE / 4] = 0xffffffffu;
        }
        __syncwarp();
        PT(6);
        {
            const uint32_t l16 = sb + lane * 16, gl = (uint32_t)(uint64_t)(void*)g_acc, gh = (uint32_t)((uint64_t)(void*)g_acc >> 32);
            const uint32_t p0 = mapa(sb, c == 2 ? 0 : c + 1), p1 = mapa(sb, c == 0 ? 2 : c - 1), so = R_SC + lane * 4;
            if (q < 3) sts128(l16 + R_T0 + q * 512, p0 + so + (q == 2 ? 1536 : 512 + q * 256), p0 + R_BAR + BSC, p1 + so + (q == 2 ? 1664 : 1024 + q * 256), p1 + R_BAR + BSC);
            else {
                sts128(l16 + R_T0 + q * 512, gl + acc_line(n >> 4, (n >> 2) & 3, n & 3) + lane * 4, gh, gl + acc_stamp(lane & 1, n), (lane & 3) == 3 ? EMPTY : 0);
                stsm2(l16 + R_T2, gl + acc_stamp(0, lane), gh);
            }
            for (int i = 0; i < 4; i++)
                stsm4(l16 + R_T1 + i * 2048 + q * 512, gl + acc_slot(i) + acc_line(2 * jw, q, (lane >> 4) * 2 + ((lane >> 1) & 1)) + ((lane & 1) * 4 + ((lane >> 2) & 3)) * 16, gh,
                       gl + acc_slot(i) + acc_line(0, q, lane >> 3) + (lane & 7) * 16, gh);
            __syncwarp();
        }
        uint32_t wo[3][8][4];
#pragma unroll
        for (int hf = 0; hf < 2; hf++) {
            const uint32_t g = lane >> 2, a = sb + R_WO + q * 6144 + (lane & 3) * 192 + (g & 3) * 4;
            mbar_wait(bw + hf * 8, 0);
#pragma unroll
            for (int m = 0; m < 3; m++)
#pragma unroll
                for (int kk = 0; kk < 8; kk++) {
                    const uint32_t ch = (m < 2 ? (g >> 2) * 2 + m : 4 + (g >> 2)) * 16;
                    const uint32_t x = lds32(a + ch + kk * 768), y = lds32(a + ch + kk * 768 + 96);
                    wo[m][hf * 4 + (kk >> 1)][(kk & 1) * 2] = __byte_perm(x, y, 0x5410);
                    wo[m][hf * 4 + (kk >> 1)][(kk & 1) * 2 + 1] = __byte_perm(x, y, 0x7632);
                }
            if (hf == 0) {
                fence_smem_async();
                __syncwarp();
                tma2d(sb + R_WO + q * 6144, &maps.wo, bw + 8, wx, h * 128 + 64);
                PT(7);
                if (q == 3) {
                    int it = 0;
                    while (!__all_sync(0xffffffffu, ldg_rlx(&g_pub[lane]) == epoch && ldg_rlx(&g_pub[32 + lane]) == epoch && ldg_rlx(&g_pub[64 + lane]) == epoch))
                        if (++it > (1 << 22)) TRAP(2000 + __LINE__);
                }
            }
        }
        PT(8);
        bar_sync(0, 384);
        bar_arrive(NB_G1, 256);
        bar_arrive(NB_E0, 256);
        bar_arrive(NB_GO, 384);
        cluster_arrive_rlx(); cluster_wait();
        PT(9);
        if (q >= 2 && lane == 0) {
            fence_smem_async();
            x_tma(sb + (q - 1) * 36864 + c * 12288, &maps.x, bar + BX0 + (q - 1) * 8, (q - 1) * 32, c * 3);
        }
        if (q == 1 && lane == 0) asm volatile("cp.async.bulk.prefetch.L2.global [%0], 24576;" :: "l"((const char*)xraw + n * 24576) : "memory");
        __syncwarp();
        PT(10);
        attn_loop(wo, &maps.x, maps.acc, smem, sb, c, q, lane0);
    }
    cluster_arrive_rlx(); cluster_wait();
    GT(0, 2);
}

constexpr int H_USTR = 32 * 144 + 16;
constexpr int H_U = 0;
constexpr int H_Z = H_U + 16 * H_USTR;
constexpr int H_W = 74752;
constexpr int H_WSTR = (2048 + 64) * 4;
constexpr int H_PAR = H_W + 8 * H_WSTR;
constexpr int H_KD = H_PAR + 8 * 2048;
constexpr int H_S4END = H_KD + 8 * 648 * 4;
constexpr int NST = 6;
constexpr int H_RING = H_W;
constexpr int H_QKV = 180224;
constexpr int H_AO = H_QKV + 30720;
constexpr int H_BAR = H_AO + 8192;
constexpr int H_SMEM = H_BAR + 512;
static_assert(H_Z + 256 <= H_W && H_S4END <= H_QKV && H_RING + NST * 16384 <= H_QKV && H_SMEM <= 232448 && H_RING % 1024 == 0, "smem");
enum { HB_FULL = 0  , HB_EMPTY = 64  , HB_QF = 256, HB_VF = 264, HB_QE = 272, HB_VE = 280, HB_OF = 288, HB_OE = 296 };
enum { HN_U = 1, HN_Y = 2, HN_P = 3  , HN_G = 5   };

DEVI int slot_channel(int i) { return ((i >> 1) & 3) * 4 + (i >> 3) * 2 + (i & 1); }
#define LOAD_U(W)                                                                                                                      \
    _Pragma("unroll 1") for (int i0 = 0; i0 < 32; i0 += 4) {                                                                            \
        uint2 v[4][2];                                                                                                                  \
        _Pragma("unroll") for (int i = 0; i < 8; i++)                                                                                   \
            v[i >> 1][i & 1] = __ldg((const uint2*)(u + (size_t)(((W) * 32 + i0) * 16 + i * 8 + g) * DM + d0 + tq * 4));                \
        _Pragma("unroll") for (int i = 0; i < 4; i++) {                                                                                 \
            const int t0 = ((W) * 32 + i0 + i) * 16;                                                                                    \
            asm volatile("stmatrix.sync.aligned.m8n8.x4.trans.shared.b16 [%0], {%1,%2,%3,%4};"                                          \
                         :: "r"(sb + H_U + (lane & 15) * H_USTR + (t0 >> 6) * 144 + (t0 & 63) * 2 + (lane >> 4) * 16),                  \
                            "r"(v[i][0].x), "r"(v[i][0].y), "r"(v[i][1].x), "r"(v[i][1].y) : "memory");                                 \
        }                                                                                                                               \
    }
DEVI uint64_t desc_plain(uint32_t saddr, uint32_t lbo, uint32_t sbo) { return ((uint64_t)(sbo >> 4) << 32) | ((uint64_t)(lbo >> 4) << 16) | (uint64_t)((saddr & 0x3FFFF) >> 4); }
template <int ACC> DEVI void wgmma48_tt(float* d, uint64_t adesc, uint64_t bdesc) {
    asm volatile("wgmma.mma_async.sync.aligned.m64n48k16.f32.bf16.bf16 "
                 "{%0,%1,%2,%3,%4,%5,%6,%7,%8,%9,%10,%11,%12,%13,%14,%15,%16,%17,%18,%19,%20,%21,%22,%23}, %24, %25, %26, 1, 1, 1, 1;"
                 : "+f"(d[0]), "+f"(d[1]), "+f"(d[2]), "+f"(d[3]), "+f"(d[4]), "+f"(d[5]), "+f"(d[6]), "+f"(d[7]),
                   "+f"(d[8]), "+f"(d[9]), "+f"(d[10]), "+f"(d[11]), "+f"(d[12]), "+f"(d[13]), "+f"(d[14]), "+f"(d[15]),
                   "+f"(d[16]), "+f"(d[17]), "+f"(d[18]), "+f"(d[19]), "+f"(d[20]), "+f"(d[21]), "+f"(d[22]), "+f"(d[23])
                 : "l"(adesc), "l"(bdesc), "n"(ACC));
}
template <int ACC> DEVI void wgmma64(float* d, const uint32_t* a, uint64_t desc) {
    asm volatile("wgmma.mma_async.sync.aligned.m64n64k16.f32.bf16.bf16 "
                 "{%0,%1,%2,%3,%4,%5,%6,%7,%8,%9,%10,%11,%12,%13,%14,%15,%16,%17,%18,%19,%20,%21,%22,%23,%24,%25,%26,%27,%28,%29,%30,%31}, {%32,%33,%34,%35}, %36, %37, 1, 1, 0;"
                 : "+f"(d[0]), "+f"(d[1]), "+f"(d[2]), "+f"(d[3]), "+f"(d[4]), "+f"(d[5]), "+f"(d[6]), "+f"(d[7]),
                   "+f"(d[8]), "+f"(d[9]), "+f"(d[10]), "+f"(d[11]), "+f"(d[12]), "+f"(d[13]), "+f"(d[14]), "+f"(d[15]),
                   "+f"(d[16]), "+f"(d[17]), "+f"(d[18]), "+f"(d[19]), "+f"(d[20]), "+f"(d[21]), "+f"(d[22]), "+f"(d[23]),
                   "+f"(d[24]), "+f"(d[25]), "+f"(d[26]), "+f"(d[27]), "+f"(d[28]), "+f"(d[29]), "+f"(d[30]), "+f"(d[31])
                 : "r"(a[0]), "r"(a[1]), "r"(a[2]), "r"(a[3]), "l"(desc), "n"(ACC));
}
DEVI uint2 ldg_rlx2(const void* p) { uint2 v; asm volatile("ld.relaxed.gpu.global.v2.u32 {%0,%1}, [%2];" : "=r"(v.x), "=r"(v.y) : "l"(p) : "memory"); return v; }
DEVI unsigned ldg_acq(const unsigned* p) { unsigned v; asm volatile("ld.acquire.gpu.global.u32 %0, [%1];" : "=r"(v) : "l"(p) : "memory"); return v; }
DEVI void csq(float& x, float& y) { const float a = fmaf(x, x, -y * y), b = 2.f * x * y; x = a; y = b; }
DEVI uint32_t tf(float x) { return __float_as_uint(x); }
constexpr float TFC = 1.f + 6.77e-4f;
DEVI void cexp_turns(float l2mag, float turns, float& x, float& y) {
    const float m = ex2(l2mag), a = (turns - rintf(turns)) * 6.283185307179586f;
    x = m * __cosf(a); y = m * __sinf(a);
}

__global__ void __launch_bounds__(512, 1)
hk_kernel(const __nv_bfloat16* __restrict__ Wo, const __nv_bfloat16* __restrict__ u,
          const __nv_bfloat16* __restrict__ logA, const __nv_bfloat16* __restrict__ Aim, const __nv_bfloat16* __restrict__ Cre,
          const __nv_bfloat16* __restrict__ Cim, const __nv_bfloat16* __restrict__ logdt, const __nv_bfloat16* __restrict__ Dsk,
          __nv_bfloat16* __restrict__ out) {
    extern __shared__ __align__(1024) unsigned char smem[];
    const uint32_t sb = smem_u32(smem);
    const int tid = threadIdx.x, lane = tid & 31, warp = __shfl_sync(0xffffffffu, tid >> 5, 0), g = lane >> 2, tq = lane & 3;
    const int cta = blockIdx.x;
    const bool shared = cta < 32;
    const uint32_t bar = sb + H_BAR;
    const int d0 = cta * 16;
    const uint32_t tstart = clk();
    if (tid == 0) {
        for (int i = 0; i < NST; i++) { mbar_init(bar + HB_FULL + i * 8, 1); mbar_init(bar + HB_EMPTY + i * 8, shared ? 8 : 4); }
        mbar_init(bar + HB_QF, 1); mbar_init(bar + HB_VF, 1); mbar_init(bar + HB_QE, 4); mbar_init(bar + HB_VE, 4); mbar_init(bar + HB_OF, 4); mbar_init(bar + HB_OE, 1);
        asm volatile("fence.proxy.async.shared::cta;" ::: "memory");
    }
    const unsigned epoch = g_epoch[cta] + 1;
    __syncthreads();
    if (tid == 0) g_epoch[cta] = epoch;
    if (warp < 8) {
        asm volatile("setmaxnreg.inc.sync.aligned.u32 176;");
        HEV(0); GT(96, 0);
        const int pr = warp & 3, wb = warp >> 2;
        float4* const par = (float4*)(smem + H_PAR + warp * 2048);
        float* const kd = (float*)(smem + H_KD + warp * 648 * 4);
        uint32_t* const wz = (uint32_t*)(smem + H_W + warp * H_WSTR);
        wz[lane] = 0; wz[32 + lane] = 0;
        spin_until(tstart + PDLY);
        if (lane < 16) {
            const __nv_bfloat16* const pp = (lane & 3) == 0 ? logA : (lane & 3) == 1 ? Aim : (lane & 3) == 2 ? Cre : Cim;
            asm volatile("prefetch.global.L2 [%0];" :: "l"(pp + (d0 + warp * 2) * 128 + (lane >> 2) * 64));
        }
        HEV(1);
        if (!(HM & 1)) bar_sync(HN_U + wb * 8, 256);
#pragma unroll 1
        for (int it = 0; it < ((HM & 1) ? 2 + wb : 0); it++) {
            const int ch = (it ? 2 * it - wb : 0) * 4 + pr, d = d0 + slot_channel(ch);
            const float dt = bf2f(__float2bfloat16(expf(bf2f(logdt[d]))));
            const uint32_t dsk = ((const uint16_t*)Dsk)[d];
#pragma unroll
            for (int n = lane; n < 128; n += 32) {
                const float ar = -bf2f(__float2bfloat16(expf(bf2f(logA[d * 128 + n])))) * dt, ai = bf2f(Aim[d * 128 + n]) * dt;
                par[n] = make_float4(ar * 1.4426950408889634f, ai * 0.15915494309189535f, 2.f * TFC * (bf2f(Cre[d * 128 + n]) * dt), 2.f * TFC * (bf2f(Cim[d * 128 + n]) * dt));
            }
            __syncwarp();
            {
                float kacc[5][4], klast = 0.f;
#pragma unroll
                for (int i = 0; i < 5; i++) kacc[i][0] = kacc[i][1] = kacc[i][2] = kacc[i][3] = 0.f;
                const float fa = (float)g, fb = (float)(g + 8);
                const int k0 = it ? 0 : wb * 4, k1 = it ? 8 : k0 + 4;
                float4 pn[4];
#pragma unroll
                for (int i = 0; i < 4; i++) pn[i] = par[16 * k0 + 4 * i + tq];
#pragma unroll 1
                for (int k4 = k0; k4 < k1; k4++) {
#pragma unroll
                    for (int ks = 0; ks < 4; ks++) {
                        const float4 p = pn[ks];
                        pn[ks] = par[(16 * k4 + 4 * ks + 16 + tq) & 127];
                        float ax, ay, bx, by;
                        cexp_turns(p.x * fa, p.y * fa, ax, ay);
                        cexp_turns(p.x * fb, p.y * fb, bx, by);
                        uint32_t F[4][4];
#pragma unroll
                        for (int r = 0; r < 4; r++) {
                            F[r][0] = tf(ax); F[r][1] = tf(bx); F[r][2] = tf(ay); F[r][3] = tf(by);
                            csq(ax, ay); csq(bx, by);
                        }
                        mma_tf32(kacc[0], F[0][0], F[0][1], F[0][2], F[0][3], tf(fmaf(p.z, ax, -p.w * ay)), tf(fmaf(-p.z, ay, -p.w * ax)));
#pragma unroll
                        for (int r = 0; r < 4; r++) {
                            mma_tf32(kacc[r + 1], F[r][0], F[r][1], F[r][2], F[r][3], tf(fmaf(p.z, bx, -p.w * by)), tf(fmaf(-p.z, by, -p.w * bx)));
                            csq(bx, by);
                        }
                        klast = fmaf(p.z, bx, fmaf(-p.w, by, klast));
                    }
                }
                klast += __shfl_xor_sync(0xffffffffu, klast, 1);
                klast += __shfl_xor_sync(0xffffffffu, klast, 2);
                klast *= 1.f / TFC;
                float* const kp = kd + 32 * tq + g;
                if (it == 0 && wb == 0) {
                    bar_sync(HN_G + pr, 64);
#pragma unroll
                    for (int i = 0; i < 5; i++) { kacc[i][0] += kp[i * 128]; kacc[i][1] += kp[i * 128 + 16]; kacc[i][2] += kp[i * 128 + 8]; kacc[i][3] += kp[i * 128 + 24]; }
                    klast += kd[640];
                    __syncwarp();
                }
                const int ko = it == 0 && wb ? -4 * 648 : 0;
#pragma unroll
                for (int i = 0; i < 5; i++) { kp[ko + i * 128] = kacc[i][0]; kp[ko + i * 128 + 16] = kacc[i][1]; kp[ko + i * 128 + 8] = kacc[i][2]; kp[ko + i * 128 + 24] = kacc[i][3]; }
                if (lane == 0) kd[ko + 640] = klast;
                if (ko) { bar_arrive(HN_G + pr, 64); continue; }
                __syncwarp();
            }
#pragma unroll
            for (int h = 0; h < 2; h++) {
                const int i = lane + 32 * h;
                const uint32_t wa = sb + H_W + warp * H_WSTR + 256;
                const float4 v = *(const float4*)(kd + 4 * i);
                sts128(wa + i * 16, pack2(v.x, i ? kd[4 * i - 1] : 0.f), pack2(v.y, v.x), pack2(v.z, v.y), pack2(v.w, v.z));
#pragma unroll
                for (int r = 1; r < 4; r++) {
                    const float2 ab = *(const float2*)(kd + 128 + r * 128 + 2 * i);
                    const float c = kd[130 + r * 128 + 2 * i];
                    const uint32_t ba = pack2(ab.y, ab.x), cb = pack2(c, ab.y);
                    const uint32_t aa = __byte_perm(ba, 0, 0x3232), bb = __byte_perm(ba, 0, 0x1010), cc = __byte_perm(cb, 0, 0x1010);
                    const uint32_t p = wa + (512 << r) + i * (8 << r);
                    if (r == 1) sts128(p, i ? aa : pack2(ab.x, kd[255]), aa, ba, cb);
                    if (r == 2) { sts128(p, aa, aa, aa, ba); sts128(p + 16, bb, bb, cb, cc); }
                    if (r == 3) { sts128(p, aa, aa, aa, aa); sts128(p + 16, aa, ba, bb, bb); sts128(p + 32, bb, bb, bb, bb); sts128(p + 48, cb, cc, cc, cc); }
                }
            }
            __syncwarp();
            if (it == wb) bar_sync(HN_U + wb * 8, 256);
            if (it == 0) HEV(2);
            float acc[4][4][4];
            const uint32_t ub = sb + H_U + ch * H_USTR + (lane >> 3) * 16, zb = sb + H_Z + (lane >> 3) * 16;
            uint32_t bn[2][2][4];
            {
                const uint32_t dg = g == 2 * tq ? dsk : (g == 2 * tq + 1 ? dsk << 16 : 0u);
#pragma unroll
                for (int G = 0; G < 4; G++) {
                    ldsm4(bn[0][0], ub + (8 * G + (lane & 7)) * 144); ldsm4(bn[0][1], ub + (8 * G + (lane & 7)) * 144 + 64);
#pragma unroll
                    for (int i = 0; i < 4; i++) {
                        acc[G][i][0] = acc[G][i][1] = acc[G][i][2] = acc[G][i][3] = 0.f;
                        mma16(acc[G][i], dg, 0, 0, dg, bn[0][i >> 1][(i & 1) * 2], bn[0][i >> 1][(i & 1) * 2 + 1]);
                    }
                }
            }
            const volatile uint32_t* wp = wz + 64 - 56 + g - 2 * tq;
            uint32_t A[8][4];
#pragma unroll
            for (int m = 0; m < 7; m++) { A[m][0] = wp[16 * m + 8]; A[m][3] = wp[16 * m + 8]; A[m][1] = wp[16 * m + 16]; A[m][2] = wp[16 * m]; }
#define CONV_STEP(G0, E)                                                                                                 \
    {                                                                                                                    \
        uint32_t b[3][2][4];                                                                                             \
        _Pragma("unroll") for (int G = 2; G >= (G0); G--) {                                                              \
            const int cidx = 8 * G + (lane & 7) - s - (E);                                                               \
            const uint32_t ba = (G > (G0) || cidx >= 0) ? ub + cidx * 144 : zb;                                          \
            ldsm4(b[G][0], ba); ldsm4(b[G][1], ba + 64);                                                                 \
        }                                                                                                                \
        {                                                                                                                \
            const int cidx = 23 + (lane & 7) - s - (E);                                                                  \
            const uint32_t ba = ((G0) < 2 || cidx >= 0) ? ub + cidx * 144 : zb;                                          \
            ldsm4(bn[1 - (E)][0], ba); ldsm4(bn[1 - (E)][1], ba + 64);                                                   \
        }                                                                                                                \
        const volatile uint32_t* const wn = wp + 64 * min(s + (E) + 1, 31);                                              \
        _Pragma("unroll") for (int ph = 0; ph < 2; ph++) {                                                               \
            _Pragma("unroll") for (int G = 3; G >= (G0); G--)                                                            \
                _Pragma("unroll") for (int j = 3; j >= 0; j--)                                                           \
                    _Pragma("unroll") for (int i = 0; i < 4; i++) {                                                      \
                        if ((i - j + 3 >= 3) != ph) continue;                                                            \
                        const uint32_t* const a = A[(i - j + 3 + 4 * (E)) & 7];                                          \
                        const uint32_t* const bq = G == 3 ? bn[E][j >> 1] : b[G][j >> 1];                                \
                        mma16(acc[G][i], a[0], a[1], a[2], a[3], bq[(j & 1) * 2], bq[(j & 1) * 2 + 1]);                  \
                    }                                                                                                    \
            if (ph == 0) {                                                                                               \
                _Pragma("unroll") for (int m = 3; m < 7; m++) {                                                          \
                    uint32_t* const a = A[(m + 4 + 4 * (E)) & 7];                                                        \
                    a[0] = wn[16 * m + 8]; a[1] = wn[16 * m + 16];                                                       \
                    if (DUPL) { a[2] = wn[16 * m]; a[3] = wn[16 * m + 8]; } else { a[2] = A[(m + 3 + 4 * (E)) & 7][1]; a[3] = a[0]; } \
                }                                                                                                        \
            }                                                                                                            \
        }                                                                                                                \
    }
#define CONV_RANGE(G0) _Pragma("unroll 1") for (int s = 8 * (G0); s < 8 * (G0) + 8; s += 2) { CONV_STEP(G0, 0) CONV_STEP(G0, 1) }
            CONV_RANGE(0) CONV_RANGE(1) CONV_RANGE(2) CONV_RANGE(3)
#undef CONV_RANGE
#undef CONV_STEP
            __syncwarp();
            if (it == 0) HEV(3);
#pragma unroll
            for (int G = 0; G < 4; G++)
#pragma unroll
                for (int i = 0; i < 4; i += 2)
                    asm volatile("stmatrix.sync.aligned.m8n8.x4.trans.shared.b16 [%0], {%1,%2,%3,%4};"
                                 :: "r"(ub + (8 * G + (lane & 7)) * 144 + i * 32), "r"(pack2(acc[G][i][0], acc[G][i][1])), "r"(pack2(acc[G][i][2], acc[G][i][3])),
                                    "r"(pack2(acc[G][i + 1][0], acc[G][i + 1][1])), "r"(pack2(acc[G][i + 1][2], acc[G][i + 1][3])) : "memory");
        }
        HEV(4); GT(96, 1);
        const int wg = warp >> 2, q = warp & 3, t = tid & 127;
        const int nt = shared ? (cta & 3) * 2 + wg : 8, kg = shared ? cta >> 2 : (cta - 32) * 2 + wg;
        fence_smem_async();
        bar_arrive(HN_Y, 320);
        uint32_t w[32][4];
        {
            const uint32_t* src = (const uint32_t*)(Wo + (size_t)(kg * 512 + tq * 8) * DM + nt * 64 + q * 16) + g;
            const uint32_t t0 = clk() + q * (WD / 4);
#pragma unroll
            for (int i = 0; i < 64; i++) {
                if (WD && i % WB == 0) spin_until(t0 + i / WB * WD);
                const int row = (i >> 2) * 32 + (i & 3) * 2;
                const uint32_t x = (HM & 32) ? lds32(sb + H_Z + i * 4) : __ldg(src + row * (DM / 2)), y = (HM & 32) ? lds32(sb + H_Z + i * 4) : __ldg(src + (row + 1) * (DM / 2));
                w[i >> 1][(i & 1) * 2] = __byte_perm(x, y, 0x5410);
                w[i >> 1][(i & 1) * 2 + 1] = __byte_perm(x, y, 0x7632);
            }
        }
        HEV(5);
        if (wg == 1) bar_arrive(HN_P, 256);
        uint32_t* const px = &g_part[0][nt][0][0][t];
        uint32_t* const dst = (uint32_t*)(out + (size_t)((kg >> 1) * 8 + 2 * tq + (kg & 1)) * OUTW + nt * 64 + q * 16) + g;
#pragma unroll 1
        for (int s = 0; s < ((HM & 4) ? NSEG + LAG : 0); s++) {
            const int f = s - LAG;
            const uint32_t* const src = px + (f & 7) * (9 * 8192) + kg * 1024;
            uint32_t v[8];
#pragma unroll
            for (int i = 0; i < 8; i++) v[i] = (s >= LAG && !(HM & 64)) ? ldg_rlx(src + i * 128) : 0;
            float d[16];
            if (s < NSEG) {
                const int n = shared ? 2 * s : 4 * s + 2 * wg, r = n / NST, st = n - r * NST;
                const uint32_t dl = desc_lo(sb + H_RING + st * 16384);
                if (wg == 0) HS(0);
                mbar_wait(bar + HB_FULL + st * 8, r & 1);
                bar_sync(HN_P + wg, 256);
                if (wg == 0) HS(1);
                wg_fence();
                wgmma32<0>(d, w[0], desc_of(dl));
#pragma unroll
                for (int i = 1; i < 16; i++) wgmma32<1>(d, w[i], desc_of(dl + (i >> 2) * 256 + (i & 3) * 2));
                wg_commit();
                mbar_wait(bar + HB_FULL + st * 8 + 8, r & 1);
                wg_fence();
#pragma unroll
                for (int i = 16; i < PPT; i++) wgmma32<1>(d, w[i], desc_of(dl + (i >> 2) * 256 + (i & 3) * 2));
                bar_arrive(HN_P + (wg ^ 1), 256);
#pragma unroll
                for (int i = PPT; i < 32; i++) wgmma32<1>(d, w[i], desc_of(dl + (i >> 2) * 256 + (i & 3) * 2));
                wg_commit();
                asm volatile("wgmma.wait_group.sync.aligned 1;" ::: "memory");
                mbar_arrive_warp(bar + HB_EMPTY + st * 8);
                wg_wait0();
                mbar_arrive_warp(bar + HB_EMPTY + st * 8 + 8);
                if (wg == 0) HS(2);
                const uint32_t ph = ((s >> 3) + 1) & 1, rnd = ph ? 0u : 0x10000u;
                uint32_t* const p = px + (s & 7) * (9 * 8192) + kg * 128;
#pragma unroll
                for (int r = 0; r < 8; r++) {
                    const uint32_t lo = __float_as_uint(d[4 * (r >> 1) + (r & 1)]) + rnd, hi = __float_as_uint(d[4 * (r >> 1) + 2 + (r & 1)]) + 0x8000u;
                    if (!(HM & 128) || lo == 0x12345) stg_rlx(p + r * 1024, (__byte_perm(lo, hi, 0x7632) & 0xfffffffeu) | ph);
                }
                if (wg == 0) HS(3);
            }
            if (s >= LAG && !(HM & 64)) {
                const uint32_t ph = ((f >> 3) + 1) & 1;
                for (int it = 0; __any_sync(0xffffffffu, (or3(diff2(v[0], v[1], ph), diff2(v[2], v[3], ph), diff2(v[4], v[5], ph)) | diff2(v[6], v[7], ph)) & 1);) {
                    if (PB && it) spin_until(clk() + PB);
#pragma unroll
                    for (int i = 0; i < 8; i++) v[i] = ldg_rlx(src + i * 128);
                    if (++it > (1 << 22)) TRAP(2000 + __LINE__);
                }
            }
            if (s >= LAG && !(HM & 16))
                dst[(size_t)f * 32 * (OUTW / 2)] = pack2(((bflo(v[0]) + bflo(v[1])) + (bflo(v[2]) + bflo(v[3]))) + ((bflo(v[4]) + bflo(v[5])) + (bflo(v[6]) + bflo(v[7]))),
                                                         ((bfhi(v[0]) + bfhi(v[1])) + (bfhi(v[2]) + bfhi(v[3]))) + ((bfhi(v[4]) + bfhi(v[5])) + (bfhi(v[6]) + bfhi(v[7]))));
            if (wg == 0) HS(4);
        }
        if ((HM & 4) && wg == 0) bar_sync(HN_P, 256);
    } else if (warp < 12) {
        asm volatile("setmaxnreg.dec.sync.aligned.u32 48;");
        if (tid - 256 < 64) ((uint32_t*)(smem + H_Z))[tid - 256] = 0;
        spin_until(tstart + UDLY);
        LOAD_U(warp - 8)
        bar_arrive(HN_U, 256);
        bar_arrive(HN_U + 8, 256);
        const int hd = cta, h0 = shared ? cta & 28 : (cta - 32) * 8, nst = shared ? 2 : 4;
        if (warp == 8) {
            bar_sync(HN_Y, 320);
            int ready = 0;
#pragma unroll 1
            for (int s = 0; s < ((HM & 4) ? NSEG : 0); s++) {
                for (int it = 0; ready <= s;) {
                    const unsigned want = epoch * 64 + s + (lane >> 3);
                    unsigned v = want;
                    if (s + (lane >> 3) < NSEG) v = ldg_acq(&g_oflag[s + (lane >> 3)][h0 + (lane & (2 * nst - 1))][0]);
                    const uint32_t miss = ~__ballot_sync(0xffffffffu, v == want);
                    ready = s + (miss ? (__ffs(miss) - 1) >> 3 : 4);
                    if (++it > (1 << 24)) TRAP(2000 + __LINE__);
                }
                asm volatile("fence.proxy.async.global;" ::: "memory");
#pragma unroll 1
                for (int i = 0; i < nst; i++) {
                    const int n = nst * s + i, r = n / NST, st = n - r * NST;
                    if (r > 0) mbar_wait(bar + HB_EMPTY + st * 8, (r - 1) & 1);
                    if (lane == 0) {
                        mbar_expect(bar + HB_FULL + st * 8, (HM & 256) ? 0 : 16384);
                        if (!(HM & 256)) bulk_g2s(sb + H_RING + st * 16384, (const char*)g_o + (size_t)(s * 64 + h0 * 2 + i * 4) * 4096, 16384, bar + HB_FULL + st * 8);
                    }
                    __syncwarp();
                }
                HS(7);
            }
        } else if (warp == 9) {
#pragma unroll 1
            for (int s = 0; s < ((HM & 2) && shared ? NSEG : 0); s++) {
                const int c = lane % 3;
                unsigned v;
                for (int it = 0; v = ldg_acq(&g_qflag[s][hd][c * 8]), !__all_sync(0xffffffffu, (v ^ (epoch * 64)) < 64);)
                    if (++it > (1 << 24)) TRAP(2000 + __LINE__);
                HS(5);
                asm volatile("fence.proxy.async.global;" ::: "memory");
                const uint32_t off = lane < 3 ? c * 7680 : lane < 6 ? 20480 + c * 2048 : 28672 + c * 512;
                const unsigned char* const src = g_qkv + (size_t)((v & 63) * 32 + hd) * 30720 + off;
                if (s > 0) mbar_wait(bar + HB_QE, (s - 1) & 1);
                if (lane == 0) mbar_expect(bar + HB_QF, 20480);
                if (lane < 3) bulk_g2s(sb + H_QKV + off, src, c == 2 ? 5120 : 7680, bar + HB_QF);
                __syncwarp();
                if (s > 0) mbar_wait(bar + HB_VE, (s - 1) & 1);
                if (lane == 0) mbar_expect(bar + HB_VF, 10240);
                if (lane >= 3 && lane < 9) bulk_g2s(sb + H_QKV + off, src, (lane < 6 ? 2048 : 512) << (c >> 1), bar + HB_VF);
                __syncwarp();
            }
        } else if (warp == 10) {
#pragma unroll 1
            for (int s = 0; s < ((HM & 2) && shared ? NSEG : 0); s++) {
                mbar_wait(bar + HB_OF, s & 1);
                if (lane == 0) {
                    bulk_s2g((char*)g_o + (size_t)(s * 64 + hd * 2) * 4096, sb + H_AO, 8192);
                    asm volatile("cp.async.bulk.commit_group;" ::: "memory");
                    asm volatile("cp.async.bulk.wait_group.read 0;" ::: "memory");
                    mbar_arrive(bar + HB_OE);
                    asm volatile("cp.async.bulk.wait_group 0;" ::: "memory");
                    stg_rlx(&g_oflag[s][hd][0], epoch * 64 + s);
                }
                __syncwarp();
                HS(6);
            }
        } else {
            bar_sync(HN_Y, 320);
#pragma unroll 1
            for (int i = 0; i < ((HM & 8) ? 0 : 128); i++) {
                const uint32_t t0 = clk();
                uint32_t v[4];
                ldsm4t(v, sb + H_U + (lane & 15) * H_USTR + (i >> 2) * 144 + (i & 3) * 32 + (lane >> 4) * 16);
                uint2* const p = (uint2*)(out + (size_t)(i * 16 + g) * OUTW + DM + d0 + tq * 4);
                p[0] = make_uint2(v[0], v[1]);
                p[8 * (OUTW / 4)] = make_uint2(v[2], v[3]);
                spin_until(t0 + YDLY);
            }
            asm volatile("griddepcontrol.wait;" ::: "memory");
        }
    } else {
        asm volatile("setmaxnreg.dec.sync.aligned.u32 112;");
        const uint32_t qk = sb + H_QKV;
        const int dg = 8 * (warp & 3) + g - 2 * tq;
        const uint32_t oa = pin(sb + H_AO + (8 * (warp & 3) + g) * 128);
#pragma unroll 1
        for (int s = 0; s < ((HM & 2) && shared ? NSEG : 0); s++) {
            float x[24];
            mbar_wait(bar + HB_QF, s & 1);
            wg_fence();
#pragma unroll
            for (int i = 0; i < 8; i++) {
                constexpr int QO[8] = {0, 1024, 2048, 7680, 8704, 9728, 15360, 16384}, KO[8] = {3072, 4608, 6144, 10752, 12288, 13824, 17408, 18944};
                if (i == 0) wgmma48_tt<0>(x, desc_plain(qk + QO[i], 128, 128), desc_plain(qk + KO[i], 128, 256));
                else wgmma48_tt<1>(x, desc_plain(qk + QO[i], 128, 128), desc_plain(qk + KO[i], 128, 256));
            }
            wg_commit();
            wg_wait0();
            mbar_arrive_warp(bar + HB_QE);
            x[16] += x[20]; x[17] += x[21];
            float m = fmaxf(x[16], x[17]);
#pragma unroll
            for (int b = 0; b < 4; b++) {
                if (8 * b > dg) x[4 * b] = NEG;
                if (8 * b + 1 > dg) x[4 * b + 1] = NEG;
                m = fmaxf(m, fmaxf(x[4 * b], x[4 * b + 1]));
            }
            m = fmaxf(m, __shfl_xor_sync(0xffffffffu, m, 1));
            m = fmaxf(m, __shfl_xor_sync(0xffffffffu, m, 2));
            float l = 0.f;
            uint32_t pa[3][4];
#pragma unroll
            for (int b = 0; b < 5; b++) {
                const float e0 = ex2(x[4 * b] - m), e1 = ex2(x[4 * b + 1] - m);
                l += e0 + e1;
                pa[b >> 1][(b & 1) * 2] = pack2(e0, e1);
                pa[b >> 1][(b & 1) * 2 + 1] = 0;
            }
            pa[2][2] = pa[2][3] = 0;
            l += __shfl_xor_sync(0xffffffffu, l, 1);
            l = rcp_fast(l + __shfl_xor_sync(0xffffffffu, l, 2));
            uint32_t ow[2][8];
            mbar_wait(bar + HB_VF, s & 1);
#pragma unroll
            for (int hf = 0; hf < 2; hf++) {
                float o[32];
                wg_fence();
                wgmma64<0>(o, pa[0], desc_plain(qk + 20480 + hf * 128, 256, 1024));
                wgmma64<1>(o, pa[1], desc_plain(qk + 20480 + 512 + hf * 128, 256, 1024));
                wgmma64<1>(o, pa[2], desc_plain(qk + 28672 + hf * 128, 0, 256));
                wg_commit();
                if (hf == 0 && s > 0) mbar_wait(bar + HB_OE, (s - 1) & 1);
                wg_wait0();
#pragma unroll
                for (int i = 0; i < 8; i++) ow[hf][i] = pack2(o[4 * i] * l, o[4 * i + 1] * l);
            }
            mbar_arrive_warp(bar + HB_VE);
#pragma unroll
            for (int grp = 0; grp < 4; grp++)
                sts128(oa + (grp >> 1) * 4096 + ((((grp & 1) * 4 + tq) ^ g) << 4), ow[0][2 * grp], ow[1][2 * grp], ow[0][2 * grp + 1], ow[1][2 * grp + 1]);
            fence_smem_async();
            mbar_arrive_warp(bar + HB_OF);
        }
    }
}

typedef CUresult (*EncodeFn)(CUtensorMap*, CUtensorMapDataType, cuuint32_t, void*, const cuuint64_t*, const cuuint64_t*, const cuuint32_t*,
                             const cuuint32_t*, CUtensorMapInterleave, CUtensorMapSwizzle, CUtensorMapL2promotion, CUtensorMapFloatOOBfill);

static void make_map(EncodeFn enc, CUtensorMap* m, void* base, int width, int boxchunks) {
    cuuint64_t dims[3] = {64, 2048, (cuuint64_t)(width / 64)};
    cuuint64_t strides[2] = {(cuuint64_t)width * 2, 128};
    cuuint32_t box[3] = {64, 32, (cuuint32_t)boxchunks};
    cuuint32_t es[3] = {1, 1, 1};
    enc(m, CU_TENSOR_MAP_DATA_TYPE_BFLOAT16, 3, base, dims, strides, box, es, CU_TENSOR_MAP_INTERLEAVE_NONE, CU_TENSOR_MAP_SWIZZLE_128B,
        CU_TENSOR_MAP_L2_PROMOTION_L2_256B, CU_TENSOR_MAP_FLOAT_OOB_FILL_NONE);
}

extern "C" void kernel_launch(void* const* d_in, const int* in_sizes, int n_in, void* d_out, int out_size) {
    typedef const __nv_bfloat16* P;
    static EncodeFn enc = nullptr;
    if (!enc) {
        void* fn = nullptr;
        cudaDriverEntryPointQueryResult st;
        cudaGetDriverEntryPoint("cuTensorMapEncodeTiled", &fn, cudaEnableDefault, &st);
        enc = (EncodeFn)fn;
        cudaFuncSetAttribute(rk_kernel, cudaFuncAttributeMaxDynamicSharedMemorySize, R_SMEM);
        cudaFuncSetAttribute(hk_kernel, cudaFuncAttributeMaxDynamicSharedMemorySize, H_SMEM);
    }
    Maps maps;
    make_map(enc, &maps.x, d_in[0], DM, 3);
    {
        void* acc = nullptr;
        cudaGetSymbolAddress(&acc, g_acc);
        for (int m = 0; m < 2; m++) {
            cuuint64_t dims[5] = {128, 2, 2, 2, 144};
            cuuint64_t strides[4] = {(cuuint64_t)(m ? 4096 : 12288), 1024, 16384, 256};
            cuuint32_t box[5] = {64, 2, 2, 2, 2}, es[5] = {1, 1, 1, 1, 1};
            enc(&maps.acc[m], CU_TENSOR_MAP_DATA_TYPE_BFLOAT16, 5, (char*)acc + m * 4096, dims, strides, box, es, CU_TENSOR_MAP_INTERLEAVE_NONE,
                CU_TENSOR_MAP_SWIZZLE_NONE, CU_TENSOR_MAP_L2_PROMOTION_NONE, CU_TENSOR_MAP_FLOAT_OOB_FILL_NONE);
        }
    }

    for (int m = 0; m < 7; m++) {
        cuuint64_t dims[2] = {(cuuint64_t)(m < 6 ? HD : DM), (cuuint64_t)(m < 6 ? DM : HD)}, strides[1] = {dims[0] * 2};
        cuuint32_t box[2] = {16u * (m / 3 + 1), m < 3 ? 32u : 64u}, es[2] = {1, 1};
        enc(m < 3 ? &maps.w16[m] : m < 6 ? &maps.w32[m - 3] : &maps.wo, CU_TENSOR_MAP_DATA_TYPE_BFLOAT16, 2, d_in[m < 6 ? 2 + m % 3 : 5], dims, strides, box, es,
            CU_TENSOR_MAP_INTERLEAVE_NONE, m < 3 ? CU_TENSOR_MAP_SWIZZLE_32B : m < 6 ? CU_TENSOR_MAP_SWIZZLE_64B : CU_TENSOR_MAP_SWIZZLE_NONE,
            (CUtensorMapL2promotion)WPF, CU_TENSOR_MAP_FLOAT_OOB_FILL_NONE);
    }

    cudaLaunchConfig_t cfg = {};
    cudaLaunchAttribute at[1];
    cfg.gridDim = dim3(96); cfg.blockDim = dim3(384); cfg.dynamicSmemBytes = R_SMEM; cfg.stream = cudaStreamPerThread;
    at[0].id = cudaLaunchAttributeClusterDimension; at[0].val.clusterDim.x = 3; at[0].val.clusterDim.y = 1; at[0].val.clusterDim.z = 1;
    cfg.attrs = at; cfg.numAttrs = 1;
    cudaLaunchKernelEx(&cfg, rk_kernel, maps, (P)d_in[0], (P)d_in[1]);

    cfg.gridDim = dim3(36); cfg.blockDim = dim3(512); cfg.dynamicSmemBytes = H_SMEM;
    at[0].id = cudaLaunchAttributeProgrammaticStreamSerialization; at[0].val.programmaticStreamSerializationAllowed = 1;
    cudaLaunchKernelEx(&cfg, hk_kernel, (P)d_in[5], (P)d_in[7], (P)d_in[8], (P)d_in[9], (P)d_in[10], (P)d_in[11], (P)d_in[12], (P)d_in[13],
                       (__nv_bfloat16*)d_out);
}
```

```cpp
#include <cuda_runtime.h>
#include <cuda_bf16.h>
#include <cuda_fp16.h>
#include <cuda.h>
#include <stdint.h>

#define DEVI __device__ __forceinline__

#define NEG __int_as_float(0xff800000)
constexpr int DM = 576, NSEG = 64, HD = 4096, OUTW = 1152;

#define HM 7
#define QW 4000
#define NPROBE 4
#define CT 1600
#define FE 85
#define DL 0
#define DMIN 150
#define DMAX 4000
#define BACKOFF 200
#define LW 3
#define TIE 0
#define C2ADJ 80
#define DST 120
#define VFE 0
#define EW 0
#define LB 12
#define NTR 3
#define RP 176
#define NW2 3
#define KT 4
#define DDUMP 200
#define DPUSH 300
#define GOE 21
#define LDM 2
#define XD 50
#define G1T 0
#define F0T 14
#define F1T 16
#define SUMV 0
#define UDLY 0
#define YDLY 300
#define PPT 32
#define LAG 3
#define QR 4
#define DUPL 1
#define WPF 3
#define XPF 0
#define SSP 10
#define TR0 0
#define KB 0
#define NCH 4
#define NS 4
#define N0 3
#define P2 9
#define VW 0
#define VD 0
#define VT 1
#define PE 1
#define DUMPX 0
#define NPOLL 3
#define DSTI 150
#define ONE 1
#define OB 1
#define TR1 2
#define MW 2
#define WD 600
#define WB 4
#define PDLY 0
#define PB 0
#define WOS 8000
#define XPA 5
#define N1 8

__device__ __align__(1024) __nv_bfloat16 g_o[2048 * HD];
__device__ __align__(65536) uint32_t g_acc[16384];
__device__ __align__(128) unsigned g_pub[96];
__device__ __align__(128) uint32_t g_part[8][9][8][8][128];
__device__ __align__(1024) unsigned char g_qkv[(size_t)NSEG * 32 * 30720];
__device__ __align__(128) unsigned g_qflag[NSEG][32][32];
__device__ __align__(128) unsigned g_oflag[NSEG][32][8];
__device__ unsigned g_epoch[36 + 96];
#define EV(i)
#define EVV(i, v)
#define EVX(i) 0
#define EVADD(i, v)
#define HS(i)
#define PT(i)
#define HEV(i)
#define GT(b, i)

#define TRAP(code) __trap()
#define LOC(v)
DEVI uint32_t smem_u32(const void* p) { return (uint32_t)__cvta_generic_to_shared(p); }
DEVI uint32_t clk() { uint64_t t; asm volatile("mov.u64 %0, %%clock64;" : "=l"(t) :: "memory"); return (uint32_t)t; }
DEVI uint32_t gtime() { uint64_t t; asm volatile("mov.u64 %0, %%globaltimer;" : "=l"(t) :: "memory"); return (uint32_t)t; }
DEVI void spin_until(uint32_t t) { while ((int)(clk() - t) < 0) {} }
DEVI void jit() {}
DEVI uint32_t mapa(uint32_t a, uint32_t r) { uint32_t o; asm("mapa.shared::cluster.u32 %0, %1, %2;" : "=r"(o) : "r"(a), "r"(r)); return o; }
DEVI void mbar_init(uint32_t b, uint32_t n) { asm volatile("mbarrier.init.shared::cta.b64 [%0], %1;" :: "r"(b), "r"(n) : "memory"); }
DEVI void mbar_expect(uint32_t b, uint32_t bytes) { asm volatile("mbarrier.arrive.expect_tx.shared::cta.b64 _, [%0], %1;" :: "r"(b), "r"(bytes) : "memory"); }
DEVI void mbar_arrive(uint32_t b) { asm volatile("mbarrier.arrive.shared::cta.b64 _, [%0];" :: "r"(b) : "memory"); }
DEVI bool mbar_try(uint32_t b, uint32_t parity) {
    uint32_t ok;
    asm volatile("{.reg .pred p; mbarrier.try_wait.parity.shared::cta.b64 p, [%1], %2; selp.u32 %0, 1, 0, p;}" : "=r"(ok) : "r"(b), "r"(parity) : "memory");
    return ok;
}
DEVI void mbar_wait(uint32_t b, uint32_t parity) {
    LOC(0x100 | (b & 0xff) | (parity << 12));
    asm volatile("{.reg .pred p, q; .reg .u32 n; mov.u32 n, 0;\n W: mbarrier.try_wait.parity.shared::cta.b64 p, [%0], %1;\n"
                 "add.u32 n, n, 1; setp.lt.and.u32 q, n, 0x40000, !p; @q bra W;}" :: "r"(b), "r"(parity) : "memory");
    LOC(0x300 | (b & 0xff));
    jit();
}
DEVI void bar_sync(int id, int n) { jit(); LOC(0x200 | id); asm volatile("bar.sync %0, %1;" :: "r"(id), "r"(n) : "memory"); LOC(0x400 | id); jit(); }
DEVI void bar_arrive(int id, int n) { jit(); asm volatile("bar.arrive %0, %1;" :: "r"(id), "r"(n) : "memory"); jit(); }
DEVI void cluster_sync() { asm volatile("barrier.cluster.arrive.release.aligned; barrier.cluster.wait.acquire.aligned;" ::: "memory"); }
DEVI void cluster_arrive_rlx() { asm volatile("barrier.cluster.arrive.relaxed.aligned;" ::: "memory"); }
DEVI void cluster_wait() { asm volatile("barrier.cluster.wait.aligned;" ::: "memory"); }
DEVI void fence_async() { asm volatile("fence.proxy.async;" ::: "memory"); }
DEVI void cp16(uint32_t dst, const void* src) { asm volatile("cp.async.cg.shared.global [%0], [%1], 16;" :: "r"(dst), "l"(src) : "memory"); }
DEVI void cp_commit() { asm volatile("cp.async.commit_group;" ::: "memory"); }
template <int N> DEVI void cp_wait() { asm volatile("cp.async.wait_group %0;" :: "n"(N) : "memory"); }
DEVI void ldsm4(uint32_t* r, uint32_t a) {
    asm volatile("ldmatrix.sync.aligned.m8n8.x4.shared.b16 {%0,%1,%2,%3}, [%4];" : "=r"(r[0]), "=r"(r[1]), "=r"(r[2]), "=r"(r[3]) : "r"(a) : "memory");
}
DEVI uint32_t tab1(uint32_t a) { uint32_t r; asm volatile("ldmatrix.sync.aligned.m8n8.x1.shared.b16 {%0}, [%1];" : "=r"(r) : "r"(a) : "memory"); return r; }
DEVI uint2 tab2(uint32_t a) { uint2 r; asm volatile("ldmatrix.sync.aligned.m8n8.x2.shared.b16 {%0,%1}, [%2];" : "=r"(r.x), "=r"(r.y) : "r"(a) : "memory"); return r; }
DEVI void ldsm4t(uint32_t* r, uint32_t a) {
    asm volatile("ldmatrix.sync.aligned.m8n8.x4.trans.shared.b16 {%0,%1,%2,%3}, [%4];" : "=r"(r[0]), "=r"(r[1]), "=r"(r[2]), "=r"(r[3]) : "r"(a) : "memory");
}
DEVI void mma16(float* d, uint32_t a0, uint32_t a1, uint32_t a2, uint32_t a3, uint32_t b0, uint32_t b1) {
    asm volatile("mma.sync.aligned.m16n8k16.row.col.f32.bf16.bf16.f32 {%0,%1,%2,%3}, {%4,%5,%6,%7}, {%8,%9}, {%0,%1,%2,%3};"
                 : "+f"(d[0]), "+f"(d[1]), "+f"(d[2]), "+f"(d[3]) : "r"(a0), "r"(a1), "r"(a2), "r"(a3), "r"(b0), "r"(b1));
}
DEVI void mma8(float* d, uint32_t a0, uint32_t a1, uint32_t b0) {
    asm volatile("mma.sync.aligned.m16n8k8.row.col.f32.bf16.bf16.f32 {%0,%1,%2,%3}, {%4,%5}, {%6}, {%0,%1,%2,%3};"
                 : "+f"(d[0]), "+f"(d[1]), "+f"(d[2]), "+f"(d[3]) : "r"(a0), "r"(a1), "r"(b0));
}
DEVI void mma_tf32(float* d, uint32_t a0, uint32_t a1, uint32_t a2, uint32_t a3, uint32_t b0, uint32_t b1) {
    asm volatile("mma.sync.aligned.m16n8k8.row.col.f32.tf32.tf32.f32 {%0,%1,%2,%3}, {%4,%5,%6,%7}, {%8,%9}, {%0,%1,%2,%3};"
                 : "+f"(d[0]), "+f"(d[1]), "+f"(d[2]), "+f"(d[3]) : "r"(a0), "r"(a1), "r"(a2), "r"(a3), "r"(b0), "r"(b1));
}
template <int ACC> DEVI void wgmma32(float* d, const uint32_t* a, uint64_t desc) {
    asm volatile("wgmma.mma_async.sync.aligned.m64n32k16.f32.bf16.bf16 "
                 "{%0,%1,%2,%3,%4,%5,%6,%7,%8,%9,%10,%11,%12,%13,%14,%15}, {%16,%17,%18,%19}, %20, %21, 1, 1, 0;"
                 : "+f"(d[0]), "+f"(d[1]), "+f"(d[2]), "+f"(d[3]), "+f"(d[4]), "+f"(d[5]), "+f"(d[6]), "+f"(d[7]),
                   "+f"(d[8]), "+f"(d[9]), "+f"(d[10]), "+f"(d[11]), "+f"(d[12]), "+f"(d[13]), "+f"(d[14]), "+f"(d[15])
                 : "r"(a[0]), "r"(a[1]), "r"(a[2]), "r"(a[3]), "l"(desc), "n"(ACC));
}
template <int ACC> DEVI void wgmma32_ss(float* d, uint64_t adesc, uint64_t desc) {
    asm volatile("wgmma.mma_async.sync.aligned.m64n32k16.f32.bf16.bf16 "
                 "{%0,%1,%2,%3,%4,%5,%6,%7,%8,%9,%10,%11,%12,%13,%14,%15}, %16, %17, %18, 1, 1, 1, 0;"
                 : "+f"(d[0]), "+f"(d[1]), "+f"(d[2]), "+f"(d[3]), "+f"(d[4]), "+f"(d[5]), "+f"(d[6]), "+f"(d[7]),
                   "+f"(d[8]), "+f"(d[9]), "+f"(d[10]), "+f"(d[11]), "+f"(d[12]), "+f"(d[13]), "+f"(d[14]), "+f"(d[15])
                 : "l"(adesc), "l"(desc), "n"(ACC));
}
DEVI void wg_fence() { asm volatile("wgmma.fence.sync.aligned;" ::: "memory"); }
DEVI void wg_commit() { asm volatile("wgmma.commit_group.sync.aligned;" ::: "memory"); }
DEVI void wg_wait0() { asm volatile("wgmma.wait_group.sync.aligned 0;" ::: "memory"); }
DEVI uint64_t desc_sw128(uint32_t saddr) { return ((uint64_t)1 << 62) | ((uint64_t)64 << 32) | ((uint64_t)1 << 16) | (uint64_t)((saddr & 0x3FFFF) >> 4); }
DEVI uint32_t desc_lo(uint32_t saddr) { return (1u << 16) | ((saddr & 0x3FFFF) >> 4); }
DEVI uint64_t desc_of(uint32_t lo) { uint64_t d; asm("mov.b64 %0, {%1, 0x40000040};" : "=l"(d) : "r"(lo)); return d; }
DEVI uint64_t desc_sw32(uint32_t lo) { uint64_t d; asm("mov.b64 %0, {%1, 0xc0000010};" : "=l"(d) : "r"(lo)); return d; }
DEVI uint32_t pack2(float lo, float hi) { uint32_t r; asm("cvt.rn.bf16x2.f32 %0, %1, %2;" : "=r"(r) : "f"(hi), "f"(lo)); return r; }
DEVI void sts32(uint32_t a, uint32_t v) { asm volatile("st.shared.u32 [%0], %1;" :: "r"(a), "r"(v) : "memory"); }
DEVI void sts64f(uint32_t a, float x, float y) { asm volatile("st.shared.v2.f32 [%0], {%1,%2};" :: "r"(a), "f"(x), "f"(y) : "memory"); }
DEVI void sts128f(uint32_t a, float x, float y, float z, float w) { asm volatile("st.shared.v4.f32 [%0], {%1,%2,%3,%4};" :: "r"(a), "f"(x), "f"(y), "f"(z), "f"(w) : "memory"); }
DEVI float2 lds64f(uint32_t a) { float2 v; asm volatile("ld.shared.v2.f32 {%0,%1}, [%2];" : "=f"(v.x), "=f"(v.y) : "r"(a) : "memory"); return v; }
DEVI float4 lds128f(uint32_t a) { float4 v; asm volatile("ld.shared.v4.f32 {%0,%1,%2,%3}, [%4];" : "=f"(v.x), "=f"(v.y), "=f"(v.z), "=f"(v.w) : "r"(a) : "memory"); return v; }
DEVI uint4 lds128(uint32_t a) { uint4 v; asm volatile("ld.shared.v4.u32 {%0,%1,%2,%3}, [%4];" : "=r"(v.x), "=r"(v.y), "=r"(v.z), "=r"(v.w) : "r"(a) : "memory"); return v; }
DEVI uint4 ldm128(uint32_t a) {
    uint4 v;
    asm volatile("ld.volatile.shared.v4.u32 {%0,%1,%2,%3}, [%4];" : "=r"(v.x), "=r"(v.y), "=r"(v.z), "=r"(v.w) : "r"(a) : "memory");
    return v;
}
DEVI void sta32(uint32_t a, uint32_t v, uint32_t bar) { asm volatile("st.async.weak.shared::cluster.mbarrier::complete_tx::bytes.b32 [%0], %1, [%2];" :: "r"(a), "r"(v), "r"(bar) : "memory"); }
DEVI void sta64f(uint32_t a, float x, float y, uint32_t bar) { asm volatile("st.async.weak.shared::cluster.mbarrier::complete_tx::bytes.v2.f32 [%0], {%1,%2}, [%3];" :: "r"(a), "f"(x), "f"(y), "r"(bar) : "memory"); }
DEVI void sta128f(uint32_t a, float x, float y, float z, float w, uint32_t bar) {
    asm volatile("st.async.weak.shared::cluster.mbarrier::complete_tx::bytes.v4.f32 [%0], {%1,%2,%3,%4}, [%5];" :: "r"(a), "f"(x), "f"(y), "f"(z), "f"(w), "r"(bar) : "memory");
}
DEVI void stg_rlx(uint32_t* p, uint32_t v) { asm volatile("st.relaxed.gpu.global.u32 [%0], %1;" :: "l"(p), "r"(v) : "memory"); }
DEVI void stg_release(unsigned* p, unsigned v) { asm volatile("st.release.gpu.global.u32 [%0], %1;" :: "l"(p), "r"(v) : "memory"); }
DEVI uint32_t ldg_rlx(const uint32_t* p) { uint32_t v; asm volatile("ld.relaxed.gpu.global.u32 %0, [%1];" : "=r"(v) : "l"(p) : "memory"); return v; }
DEVI void bulk_g2s(uint32_t dst, const void* src, uint32_t bytes, uint32_t bar) {
    asm volatile("cp.async.bulk.shared::cluster.global.mbarrier::complete_tx::bytes [%0], [%1], %2, [%3];" :: "r"(dst), "l"(src), "r"(bytes), "r"(bar) : "memory");
}
DEVI void bulk_s2c(uint32_t dst, uint32_t src, uint32_t bytes, uint32_t bar) {
    asm volatile("cp.async.bulk.shared::cluster.shared::cta.mbarrier::complete_tx::bytes [%0], [%1], %2, [%3];" :: "r"(dst), "r"(src), "r"(bytes), "r"(bar) : "memory");
}
DEVI float ex2(float x) { float y; asm("ex2.approx.ftz.f32 %0, %1;" : "=f"(y) : "f"(x)); return y; }
DEVI float ex2v(float x) { float y; asm volatile("ex2.approx.ftz.f32 %0, %1;" : "=f"(y) : "f"(x)); return y; }
DEVI float bf2f(__nv_bfloat16 v) { return __bfloat162float(v); }

DEVI uint32_t pin(uint32_t v) { return __shfl_sync(0xffffffffu, v, threadIdx.x & 31); }
template <typename T> DEVI T* pinp(T* p) { const uint64_t v = (uint64_t)p; return (T*)(((uint64_t)pin((uint32_t)(v >> 32)) << 32) | pin((uint32_t)v)); }
DEVI uint32_t fresh(uint32_t v) { uint32_t r; asm volatile("mov.u32 %0, %1;" : "=r"(r) : "r"(v)); return r; }
DEVI uint64_t fresh64(uint64_t v) { uint64_t r; asm volatile("mov.u64 %0, %1;" : "=l"(r) : "l"(v)); return r; }
DEVI uint32_t or3(uint32_t a, uint32_t b, uint32_t c) { uint32_t d; asm("lop3.b32 %0, %1, %2, %3, 0xfe;" : "=r"(d) : "r"(a), "r"(b), "r"(c)); return d; }
DEVI uint32_t orand(uint32_t a, uint32_t b, uint32_t c) { uint32_t d; asm("lop3.b32 %0, %1, %2, %3, 0xf8;" : "=r"(d) : "r"(a), "r"(b), "r"(c)); return d; }
DEVI uint32_t and3(uint32_t a, uint32_t b, uint32_t c) { uint32_t d; asm("lop3.b32 %0, %1, %2, %3, 0x80;" : "=r"(d) : "r"(a), "r"(b), "r"(c)); return d; }
DEVI uint32_t diff2(uint32_t a, uint32_t b, uint32_t p) { uint32_t d; asm("lop3.b32 %0, %1, %2, %3, 0x7e;" : "=r"(d) : "r"(a), "r"(b), "r"(p)); return d; }
DEVI int lds32(uint32_t a) { int v; asm volatile("ld.volatile.shared.s32 %0, [%1];" : "=r"(v) : "r"(a) : "memory"); return v; }
DEVI uint2 lds64(uint32_t a) { uint2 v; asm volatile("ld.shared.v2.u32 {%0,%1}, [%2];" : "=r"(v.x), "=r"(v.y) : "r"(a) : "memory"); return v; }
DEVI void sts64(uint32_t a, uint32_t x, uint32_t y) { asm volatile("st.shared.v2.u32 [%0], {%1,%2};" :: "r"(a), "r"(x), "r"(y) : "memory"); }
DEVI void sta64(uint32_t a, uint32_t x, uint32_t y, uint32_t bar) { asm volatile("st.async.weak.shared::cluster.mbarrier::complete_tx::bytes.v2.b32 [%0], {%1,%2}, [%3];" :: "r"(a), "r"(x), "r"(y), "r"(bar) : "memory"); }
DEVI float rcp_fast(float x) { float y; asm("rcp.approx.ftz.f32 %0, %1;" : "=f"(y) : "f"(x)); return y; }
DEVI uint4 ldg_rlx4(const void* p) { uint4 v; asm volatile("ld.relaxed.gpu.global.v4.u32 {%0,%1,%2,%3}, [%4];" : "=r"(v.x), "=r"(v.y), "=r"(v.z), "=r"(v.w) : "l"(p) : "memory"); return v; }
DEVI void sts128(uint32_t a, uint32_t x, uint32_t y, uint32_t z, uint32_t w) { asm volatile("st.shared.v4.u32 [%0], {%1,%2,%3,%4};" :: "r"(a), "r"(x), "r"(y), "r"(z), "r"(w) : "memory"); }
DEVI void stsm4(uint32_t a, uint32_t x, uint32_t y, uint32_t z, uint32_t w) { asm volatile("stmatrix.sync.aligned.m8n8.x4.shared.b16 [%0], {%1,%2,%3,%4};" :: "r"(a), "r"(x), "r"(y), "r"(z), "r"(w) : "memory"); }
DEVI void stsm2(uint32_t a, uint32_t x, uint32_t y) { asm volatile("stmatrix.sync.aligned.m8n8.x2.shared.b16 [%0], {%1,%2};" :: "r"(a), "r"(x), "r"(y) : "memory"); }
DEVI void fence_smem_async() { asm volatile("fence.proxy.async.shared::cta;" ::: "memory"); }
DEVI uint32_t packh2(float lo, float hi) { uint32_t r; asm("cvt.rn.f16x2.f32 %0, %1, %2;" : "=r"(r) : "f"(hi), "f"(lo)); return r; }
DEVI uint32_t h2_to_bf2(uint32_t w) {
    uint32_t r;
    asm("{.reg .f16 l, h; .reg .f32 a, b; mov.b32 {l, h}, %1; cvt.f32.f16 a, l; cvt.f32.f16 b, h; cvt.rn.bf16x2.f32 %0, b, a;}" : "=r"(r) : "r"(w));
    return r;
}
DEVI uint32_t amax2(uint32_t m, uint32_t w) { return __vmaxu2(m, w & 0x7fff7fffu); }
DEVI uint32_t amax_fold(uint32_t m) { return __reduce_max_sync(0xffffffffu, max(m & 0xffffu, m >> 16)); }
DEVI float bflo(uint32_t w) { return __uint_as_float(w << 16); }
DEVI float bfhi(uint32_t w) { return __uint_as_float(w & 0xffff0000u); }
DEVI void red_b8(void* p, uint32_t a, uint32_t b, uint32_t c, uint32_t d) {
    asm volatile("red.relaxed.gpu.global.add.noftz.v4.bf16x2 [%0], {%1,%2,%3,%4};" :: "l"(p), "r"(a), "r"(b), "r"(c), "r"(d) : "memory");
}
DEVI void red_h8_if(bool on, void* p, uint32_t a, uint32_t b, uint32_t c, uint32_t d) {
    asm volatile("{.reg .pred p; setp.ne.u32 p, %5, 0; @p red.relaxed.gpu.global.add.noftz.v4.bf16x2 [%0], {%1,%2,%3,%4};}" :: "l"(p), "r"(a), "r"(b), "r"(c), "r"(d), "r"((uint32_t)on) : "memory");
}
DEVI void mbar_arrive_warp(uint32_t b) { asm volatile("{.reg .pred p; elect.sync _|p, 0xffffffff; @p mbarrier.arrive.shared::cta.b64 _, [%0];}" :: "r"(b) : "memory"); }
DEVI void bulk_s2c_warp(uint32_t dst, uint32_t src, uint32_t bytes, uint32_t bar) {
    asm volatile("{.reg .pred p; elect.sync _|p, 0xffffffff; @p cp.async.bulk.shared::cluster.shared::cta.mbarrier::complete_tx::bytes [%0], [%1], %2, [%3];}" :: "r"(dst), "r"(src), "r"(bytes), "r"(bar) : "memory");
}
DEVI char* mkptr(uint32_t lo, uint32_t hi) { uint64_t p; asm("mov.b64 %0, {%1, %2};" : "=l"(p) : "r"(lo), "r"(hi)); return (char*)p; }
DEVI void bulk_s2g(void* dst, uint32_t src, uint32_t bytes) { asm volatile("cp.async.bulk.global.shared::cta.bulk_group [%0], [%1], %2;" :: "l"(dst), "r"(src), "r"(bytes) : "memory"); }
DEVI void x_tma(uint32_t dst, const CUtensorMap* m, uint32_t xb, int row, int chunk) {
    asm volatile("cp.async.bulk.tensor.3d.shared::cluster.global.mbarrier::complete_tx::bytes.multicast::cluster [%0], [%1, {%3, %4, %5}], [%2], %6;"
                 :: "r"(dst), "l"(m), "r"(xb), "r"(0), "r"(row), "r"(chunk), "h"((uint16_t)7) : "memory");
}
#define RUNG_(A, B, PA, PB) "mov.u64 " A ", %%clock64;\n cvt.u32.u64 l, " B ";\n sub.s32 l, l, %0;\n setp.ge.s32 " PB ", l, 0;\n @" PA " bra.uni DONE;\n"
DEVI void fine_until(uint32_t t) {
    asm volatile("{.reg .pred p0, p1; .reg .b64 t0, t1; .reg .b32 l;\n setp.ne.u32 p0, 0, 0;\n mov.u64 t1, %%clock64;\n LOOP:\n"
                 RUNG_("t0", "t1", "p0", "p1") RUNG_("t1", "t0", "p1", "p0") RUNG_("t0", "t1", "p0", "p1") RUNG_("t1", "t0", "p1", "p0")
                 RUNG_("t0", "t1", "p0", "p1") RUNG_("t1", "t0", "p1", "p0") RUNG_("t0", "t1", "p0", "p1") RUNG_("t1", "t0", "p1", "p0")
                 "bra.uni LOOP;\n DONE:\n}" :: "r"(t) : "memory");
}
DEVI uint32_t clock_offset() {
    const uint32_t g0 = gtime();
    uint32_t e = clk();
#pragma unroll
    for (int i = 0; i < 7; i++) { const uint32_t g = gtime(), t = clk(); e = g == g0 ? t : e; }
    return ((((g0 >> 5) + 1) * 3686u) >> 6) - e;
}
constexpr int R_X0 = 0;
constexpr int R_K = 110592 + 3072;
constexpr int R_V = R_K + 4608;
constexpr int R_VM = R_V + 8192;
constexpr int PAR = 17920;
constexpr int R_QM = R_VM + 2048 + PAR;
constexpr int R_SC = R_QM + 1536;
constexpr int R_O8 = R_SC + 2048;
constexpr int R_PX = R_O8 + 2048;
constexpr int R_PV = R_PX + 8192;
constexpr int R_T5 = R_PV + 512;
constexpr int R_Z = R_PV + 4608;
constexpr int R_END = R_PV + 7680;
constexpr int R_STAGE = 36864;
constexpr int R_RES = R_STAGE + 8 * 16384;
constexpr int R_WO = R_RES + 16384;
constexpr int R_DBG = R_WO;
constexpr int R_T4 = R_WO + 24576;
constexpr int R_T0 = R_T4 + 4096;
constexpr int R_T1 = R_T0 + 4096;
constexpr int R_T2 = R_T1 + 2048;
constexpr int R_MEM = R_T2 + 256;
constexpr int R_BAR = R_MEM + 12288;
constexpr int R_MISC = R_BAR + 384;
constexpr int R_SMEM = R_MISC + 128;
static_assert(R_END <= R_RES && R_SMEM <= 232448, "smem");
enum { BX0 = 0  , BME = 32, BSC = 40  , BML = 56, BW = 64   };
enum { NB_F1 = 1, NB_D = 2, NB_K = 5, NB_G1 = 6, NB_E0 = 7, NB_GO = 8, NB_W1 = 9, NB_H1 = 10, NB_TOK = 11, NB_W2 = 12, NB_F0 = 13 };
enum { M_EPOCH = 0, M_SINK = 4,  M_PASS = 8, M_TGT = 16  , M_RING = 40, M_REF = 48  , M_PROBE = 56  , M_DONE = 64   };
constexpr uint32_t EMPTY = 0xc200u;
constexpr float QS = 0.08838834764831845f * 1.4426950408889634f;

DEVI uint32_t acc_slot(uint32_t s) { return (s & 1) * 128 + (s & 2) * 16384; }
DEVI uint32_t acc_blk(uint32_t m, uint32_t l) { return (((l >> 1) << 2) | ((l & 1) << 1) | ((l & 1) ^ m)) * 4096; }
DEVI uint32_t acc_line(uint32_t i, uint32_t q, uint32_t l) { return acc_blk(q & 1, l) + (q >> 1) * 256 + (i < 4 ? i * 1024 : i * 1024 - 1536); }
DEVI uint32_t acc_stamp(uint32_t m, uint32_t n) { return acc_blk(m, (n >> 3) & 3) + 512 + ((n >> 5) & 1) * 256 + (n >> 6) * 1024 + (n & 7) * 16; }

#define LOAD_TRANSIENT(LA) { _Pragma("unroll") for (int i_ = 0; i_ < NTR; i_++) ldsm4t(w[i_ & 1][i_ >> 1], (LA) + (i_ & 1) * 4096 + (i_ >> 1) * 512); }
#define PIN() asm volatile("{.reg .b64 t; .reg .b32 l, h; mov.u64 t, %%clock64; mov.b64 {l, h}, t; xor.b32 %0, %0, l;}" : "+r"(junk) :: "memory")
#define MMAW(D, T, K, B0, B1) mma16(D, w[T][K][0], w[T][K][1], w[T][K][2], w[T][K][3], B0, B1)

DEVI void bulk_s2g_warp(void* dst, uint32_t src, uint32_t bytes) {
    asm volatile("{.reg .pred p; elect.sync _|p, 0xffffffff; @p cp.async.bulk.global.shared::cta.bulk_group [%0], [%1], %2;}" :: "l"(dst), "r"(src), "r"(bytes) : "memory");
}
DEVI void bulk_commit_warp() { asm volatile("{.reg .pred p; elect.sync _|p, 0xffffffff; @p cp.async.bulk.commit_group;}" ::: "memory"); }
#define PUBLISH(S) { asm volatile("cp.async.bulk.wait_group 0;" ::: "memory"); bar_sync(NB_D, 64); stg_rlx(&g_qflag[S][blockIdx.x / 3][c * 8], lds32(sb + R_MISC + M_RING)); }

DEVI void proj_loop(uint32_t (&w)[2][18][4], unsigned char* smem, const uint32_t sb, const uint32_t c, const int wg, const int q, const uint32_t lane0,
                    const uint32_t la) {
    const uint32_t bar = sb + R_BAR;
    const int p = q ^ (2 * wg);
    const bool c2 = c == 2, both = !c2 && p < 2, aq = c2 ? p < 2 : p != 2;
    const uint32_t lp = pin(sb + lane0 * 16 + p * 1024), ma = pin(sb + lane0 * 16 + wg * 1024);
    {
        const uint32_t l16 = sb + lane0 * 16;
        const int ia = c2 ? p & 1 : min(p, 2), vt = c2 ? 4 + p : 2 * c + p - 2;
        const uint32_t dtok = l16 + (wg ? (aq ? R_K - ((c2 ? 2 : 3) - ia) * 1024 : R_K + ia * 1536) : (both ? R_K + p * 1536 : R_V + vt * 1024));
                const bool lo = lane0 < 16, mq = aq && lo, mv = !both && !lo;
        const uint32_t dmem = sb + (mq ? R_QM + ia * 512 + (lane0 & 8) * 32 + wg * 128 : (mv ? R_PV + p * 1024 : R_K + ia * 1536 + 1024) + wg * 256 + (lane0 & 8) * 16) + (lane0 & 7) * 16;
        stsm4(lp + R_T4 + wg * 512, dtok, la, dmem, dmem + (mq || mv ? 0 : PAR));
        const uint32_t p0 = mapa(sb, c2 ? 0 : c + 1), p1 = mapa(sb, c == 0 ? 2 : c - 1), d = R_VM + vt * 256 + lane0 * 4;
        sts128(lp + R_T5 + wg * 3584, p0 + d + wg * PAR, p0 + R_BAR + BSC + wg * 8, p1 + d + wg * PAR, p1 + R_BAR + BSC + wg * 8);
        __syncwarp();
        mbar_wait(bar + BX0, 0);
    }
#pragma unroll 1
    for (int s = 0; s < NSEG; s++) {
        const int xi = s - 3 * ((s * 43) >> 7);
        {
            float d[16];
#define TOKEN(WG, T, AT, NB, ZERO)                                                                                          \
    {                                                                                                                       \
    const uint32_t xd = fresh(desc_lo(sb + xi * 36864)), ad = fresh((64u << 16) | (((sb + R_RES) & 0x3FFFF) >> 4));                     \
    wg_fence();                                                                                                             \
    _Pragma("unroll") for (int i = 0; i < 18; i++) {                                                                        \
        if (i == (AT)) bar_arrive(NB, 256);                                                                                 \
        const int j = i < SSP ? i + 2 : (i < SSP + 2 ? i - SSP : i), g = 18 * WG + j;                                              \
        const uint64_t bd = desc_of(xd + (g >> 2) * 256 + (g & 3) * 2);                                                     \
        if (2 * j + (T) < NTR) wgmma32_ss<1>(d, desc_sw32(ad + ((WG * 8192 + (T) * 4096 + j * 512) >> 4)), bd);                          \
        else if (i == 0 && ZERO) wgmma32<0>(d, w[T][j], bd);                                                                \
        else wgmma32<1>(d, w[T][j], bd);                                                                                    \
    }                                                                                                                       \
    wg_commit();                                                                                                            \
    if ((AT) == 18) bar_arrive(NB, 256);                                                                                    \
    }
#define HANDOVER(WG)                                                                                                        \
    {                                                                                                                       \
        const uint32_t xa = lp + R_PX + WG * 4096;                                                                          \
        sts128(xa, pack2(d[0], d[1]), pack2(d[2], d[3]), pack2(d[4], d[5]), pack2(d[6], d[7]));                             \
        sts128(xa + 512, pack2(d[8], d[9]), pack2(d[10], d[11]), pack2(d[12], d[13]), pack2(d[14], d[15]));                 \
    }
            if (wg == 0) {
                bar_sync(NB_G1, 256);
                TOKEN(0, 0, -1, 0, 1)
                const uint32_t la = tab1(lp + R_T4 + 128);
                if (!PE) wg_wait0();
                if (q == 1 && s > 0 && (!ONE || c == 0)) {
                    const uint2 tt = tab2(lp + R_T2 - 1024), rt = lds64(sb + R_MISC + M_PROBE);
                    const uint32_t tag = (lds32(sb + R_MISC + M_EPOCH) * 64 + s) << 22, side = rt.y < rt.x;
                    const uint32_t* const sp = (const uint32_t*)mkptr((tt.x ^ (side << 12)) + acc_slot(s - 1), tt.y);
                    uint32_t v0 = ldg_rlx(sp), v1 = ldg_rlx(sp + 64), v2 = ldg_rlx(sp + 256);
                    if (PE) wg_wait0();
                    bar_sync(NB_E0, 256);
                    HANDOVER(0)
                    bar_arrive(NB_GO, 384);
                    if (!TR0) LOAD_TRANSIENT(la)
                    const uint2 tr = lds64(sb + R_MISC + M_REF);
                    int n = 0;
                    while (__any_sync(0xffffffffu, (diff2(v0, v1, tag) | (v2 ^ tag)) >> 22)) {
                        v0 = ldg_rlx(sp); v1 = ldg_rlx(sp + 64); v2 = ldg_rlx(sp + 256);
                        if (++n > (1 << 22)) TRAP(1002);
                    }
                    const int m = __reduce_max_sync(0xffffffffu, max(max((int)((v0 - tr.y) << 10), (int)((v1 - tr.y) << 10)), (int)((v2 - tr.y) << 10))) >> 10;
                    const uint32_t tn = tr.x + min(m, DMAX) + (CT - 65), tf = tn - (s > 2 ? FE : 0);
                    sts128(sb + R_MISC + M_TGT, side ? tf : tn, s, side ? tn : tf, s);
                    EV(0);
                    if (EVX(0)) { EVV(11, m); EVV(10, tr.x); }
                } else {
                    if (PE) wg_wait0();
                    EV(3);
                    bar_sync(NB_E0, 256);
                    HANDOVER(0)
                    bar_arrive(NB_GO, 384);
                    if (!TR0) LOAD_TRANSIENT(la)
                }
                bar_sync(NB_F0, 256);
                TOKEN(0, 1, F1T, NB_F1, 1)
                bar_sync(NB_H1, 256);
                const uint4 oa = lds128(lp + R_PX + 4096);
                const uint4 ob = lds128(lp + R_PX + 4608);
                wg_wait0();
                const uint32_t u0 = pack2(d[0] + bflo(oa.x), d[1] + bfhi(oa.x)), u1 = pack2(d[2] + bflo(oa.y), d[3] + bfhi(oa.y));
                const uint32_t dtok = tab1(lp + R_T4) + (s & 1) * PAR;
                stsm4(dtok, u0, u1, pack2(d[4] + bflo(oa.z), d[5] + bfhi(oa.z)), pack2(d[6] + bflo(oa.w), d[7] + bfhi(oa.w)));
                stsm4(dtok + 512, pack2(d[8] + bflo(ob.x), d[9] + bfhi(ob.x)), pack2(d[10] + bflo(ob.y), d[11] + bfhi(ob.y)),
                      pack2(d[12] + bflo(ob.z), d[13] + bfhi(ob.z)), pack2(d[14] + bflo(ob.w), d[15] + bfhi(ob.w)));
                bar_arrive(NB_TOK, 384);
                if (TR0) LOAD_TRANSIENT(la)
                mbar_wait(bar + BME, s & 1);
            } else {
                bar_sync(NB_GO, 384);
                TOKEN(1, 1, F0T, NB_F0, 1)
                const uint4 oa = lds128(lp + R_PX), ob = lds128(lp + R_PX + 512);
                wg_wait0();
                HANDOVER(1)
                bar_arrive(NB_H1, 256);
                {
                    const uint32_t ox[8] = {oa.x, oa.y, oa.z, oa.w, ob.x, ob.y, ob.z, ob.w};
#pragma unroll
                    for (int j = 0; j < 8; j++) { d[2 * j] = bflo(ox[j]); d[2 * j + 1] = bfhi(ox[j]); }
                }
                const uint2 tw = tab2(lp + R_T4 + 512);
                bar_sync(NB_F1, 256);
                TOKEN(1, 0, -1, 0, 0)
                if (q == 3 && s > 0) PUBLISH(s - 1)
                LOAD_TRANSIENT(tw.y)
                const float qs = aq ? QS : 1.f;
                const uint32_t dtok = tw.x + (s & 1) * PAR;
                if (MW == 1) mbar_wait(bar + BME, s & 1);
                uint32_t there = 0;
                if (MW == 2) asm volatile("{.reg .pred p; mbarrier.test_wait.parity.shared::cta.b64 p, [%1], %2; selp.u32 %0, 1, 0, p;}" : "=r"(there) : "r"(bar + BME), "r"(s & 1) : "memory");
                wg_wait0();
                EV(13);
#pragma unroll
                for (int hf = 0; hf < 2; hf++) {
                    const float* e = d + 8 * hf;
                    stsm4(dtok + hf * 512, pack2(e[0] * qs, e[1] * qs), pack2(e[2] * qs, e[3] * qs), pack2(e[4] * qs, e[5] * qs), pack2(e[6] * qs, e[7] * qs));
                }
                EV(12);
                bar_arrive(NB_TOK, 384);
                if (MW != 1 && !there) mbar_wait(bar + BME, s & 1);
            }
#undef TOKEN
#undef HANDOVER
        }
        uint4 b[12];
        float a[4][4];
      redo:
#pragma unroll
        for (int j = 0; j < 4; j++) a[0][j] = a[1][j] = a[2][j] = a[3][j] = 0.f;
#define LD(i) b[i] = ldm128(ma + R_MEM + ((i) >> 1) * 2048 + ((i) & 1) * 512);
#define BK0(k) ((k) % 3 == 2 ? b[(k) / 3 * 2].z : b[(k) / 3 * 2 + (k) % 3].x)
#define BK1(k) ((k) % 3 == 2 ? b[(k) / 3 * 2].w : b[(k) / 3 * 2 + (k) % 3].y)
#define KS(T, k) MMAW(a[2 * (T) + ((k) & 1)], T, k, BK0(k), BK1(k));
        uint32_t chk = 0, dmem;
        uint4 tv;
#pragma unroll
        for (int i = 0; i < 4; i++) LD(i)
#pragma unroll
        for (int k = 0; k < LW; k++) {
            if (k % 3 == 2) { chk = or3(chk, b[k / 3 * 2].w, b[k / 3 * 2 + 1].w); b[k / 3 * 2].w = b[k / 3 * 2 + 1].z | chk; }
            KS(0, k) KS(1, k)
        }
        if (DL) mbar_wait(bar + BML, s & 1);
#pragma unroll
        for (int i = 4; i < 12; i++) LD(i)
        tv = lds128(lp + fresh((s & 1) * 3584) + R_T5); dmem = tab1(lp + fresh(wg * 512 + (s & 1) * 128) + R_T4 + 256);
#pragma unroll
        for (int k = LW; k < 18; k++) {
            if (k % 3 == 2) { chk = or3(chk, b[k / 3 * 2].w, b[k / 3 * 2 + 1].w); b[k / 3 * 2].w = b[k / 3 * 2 + 1].z | chk; }
            KS(0, k) KS(1, k)
        }
        float r[4];
        {
            const float s0 = aq ? QS : 1.f;
#pragma unroll
            for (int j = 0; j < 4; j++) { r[j] = a[3][j] + a[2][j]; a[0][j] = fmaf(a[1][j], s0, a[0][j] * s0); }
            stsm4(dmem, pack2(a[0][0], a[0][1]), pack2(a[0][2], a[0][3]), pack2(r[0], r[1]), pack2(r[2], r[3]));
            const uint32_t bad = __any_sync(0xffffffffu, chk);
            asm volatile("{.reg .pred p; setp.eq.u32 p, %0, 0; @p bar.sync %1, 384;}" :: "r"(bad), "n"((int)NB_K) : "memory");
            const uint2 o = tab2(lp + R_PV);
            if (!(bad | (wg ^ 1) | both)) {
                const uint32_t lo = pack2(r[0] + bflo(o.x), r[1] + bfhi(o.x)), hi = pack2(r[2] + bflo(o.y), r[3] + bfhi(o.y)), v2 = (tv.x & 0xffffffu) | (sb & 0xff000000u);
                sta32(tv.x, lo, tv.y); sta32(tv.z, lo, tv.w);
                sta32(tv.x + 128, hi, tv.y); sta32(tv.z + 128, hi, tv.w);
                sts32(v2, lo); sts32(v2 + 128, hi);
            }
            if (__builtin_expect(bad, 0)) goto repair;
        }
#undef LD
#undef KS
#undef BK0
#undef BK1
        if (wg == 0) { EV(1); continue; }
        EV(2);
        {
            if (q != 3) bar_arrive(NB_W1, 256);
            if (q == 3) {
                const uint32_t area = __shfl_sync(0xffffffffu, lds32(sb + R_MISC + M_RING), 0) & 63, so = sb + (s & 1) * PAR;
                unsigned char* const dst = g_qkv + (size_t)(area * 32 + blockIdx.x / 3) * 30720;
                unsigned char* const dk = dst + c * 7680 + (c2 ? 3072 : 4096);
                sts32(sb + R_MISC + M_SINK, clk());
                bar_sync(NB_W1, 256);
                fence_smem_async();
                bulk_s2g_warp(dst + 20480 + c * 2048, so + R_V + c * 2048, c2 ? 4096 : 2048);
                bulk_s2g_warp(dst + 28672 + c * 512, so + R_VM + c * 512, c2 ? 1024 : 512);
                bulk_s2g_warp(dk, so + R_K + 1024, 512);
                bulk_s2g_warp(dk + 1536, so + R_K + 2560, 512);
                if (!c2) bulk_s2g_warp(dk + 3072, so + R_K + 4096, 512);
                bulk_commit_warp();
            } else if (q == 2) {
                const uint4 tz = lds128(lp + R_T0 + 1536);
                const uint32_t pa = sb + R_MISC + M_PROBE + (((blockIdx.x >> 2) ^ s) & 1) * 4, best = lds32(pa);
                char* const zp = mkptr((tz.x ^ ((s & 1) << 12)) + acc_slot(s + 2), tz.y);
                uint32_t z;
                const uint32_t t1 = clk();
                asm volatile("atom.relaxed.gpu.global.exch.b32 %0, [%1], %2;" : "=r"(z) : "l"(zp), "r"(tz.w) : "memory");
                sts32(sb + R_MISC + M_SINK, z);
                sts32(pa, min(best, clk() - t1));
            }
        }
        continue;
      repair:
        {
            if (atomicAdd((unsigned*)(smem + R_MISC + M_PASS), 1) > (1u << 28)) TRAP(1000);
#pragma unroll 1
            for (int i = 0; i < 2; i++) {
                const uint2 tb = tab2(ma + fresh(i * 512) + R_T1 + 256);
                const uint32_t md = ma + ((ma ^ (tb.y >> 31)) & 256) + R_MEM + i * 2048;
                const char* const ga = mkptr(tb.x + acc_slot(s - 1), tb.y);
                cp16(md, ga); cp16(md + 256, ga + 1024); cp16(md + 4096, ga + 2048); cp16(md + 4352, ga + 3072);
                cp16(md + 8192, ga + 2560); cp16(md + 8448, ga + 3584);
            }
            asm volatile("cp.async.wait_all;" ::: "memory");
            __syncwarp();
            const uint32_t la = tab1(lp + fresh(wg * 512) + R_T4 + 128);
            LOAD_TRANSIENT(la)
            goto redo;
        }
    }
    if (wg == 1) PT(18);
    if (wg == 1 && q == 3) PUBLISH(NSEG - 1)
}

DEVI void attn_loop(const uint32_t (&wo)[3][8][4], const CUtensorMap* xmap, const CUtensorMap* amap, unsigned char* smem, const uint32_t sb, const uint32_t c, const int q,
                    const uint32_t lane0) {
    const uint32_t bar = sb + R_BAR;
    const bool c2 = c == 2;
    const uint32_t l16 = pin(sb + lane0 * 16);
#define UA(x) (l16 + fresh(x))
#define DUMP_QK()                                                                                                             \
    {                                                                                                                         \
        const uint32_t e64 = lds32(sb + R_MISC + M_EPOCH) * 64, so = sb + (s & 1) * PAR + R_K, nq = c2 ? 2048 : 3072;         \
        const uint32_t area = __shfl_sync(0xffffffffu, s & ((uint32_t)lds32(sb + R_MISC + M_DONE) == e64 + s - QR ? QR - 1 : 63), 0); \
        sts32(sb + R_MISC + M_RING, e64 + area);                                                                              \
        unsigned char* const dst = g_qkv + (size_t)(area * 32 + blockIdx.x / 3) * 30720 + c * 7680;                           \
        bulk_s2g_warp(dst, so - nq, nq + 1024);                                                                               \
        bulk_s2g_warp(dst + nq + 1536, so + 1536, 1024);                                                                      \
        if (!c2) bulk_s2g_warp(dst + 6144, so + 3072, 1024);                                                                  \
        bulk_commit_warp();                                                                                                   \
    }
#pragma unroll 1
    for (int s = 0; s < NSEG - 1; s++) {
        const uint32_t par = (s & 1) * PAR;
        uint32_t junk = 0;
        const uint4 ta = lds128(UA(q * 512 + (s & 1) * 2048) + R_T0);
        bar_sync(NB_TOK, 384);
#define SCORES()                                                                                                   \
    float x[2][3][4];                                                                                              \
    _Pragma("unroll") for (int t = 0; t < 3; t++) {                                                                \
        _Pragma("unroll") for (int j = 0; j < 4; j++) x[0][t][j] = x[1][t][j] = 0.f;                               \
        mma16(x[0][t], qf[t][0], qf[t][1], qf[t][2], qf[t][3], kf[t][0], kf[t][1]);                                \
        mma16(x[1][t], qf[t][0], qf[t][1], qf[t][2], qf[t][3], kf[t][2], kf[t][3]);                                \
    }                                                                                                              \
    if (G1T == 0) { PIN(); bar_arrive(NB_G1, 256); PIN(); }                                                        \
    float y[4];                                                                                                    \
    _Pragma("unroll") for (int j = 0; j < 4; j++)                                                                  \
        y[j] = ((x[j >> 1][0][j & 1] + x[j >> 1][0][2 + (j & 1)]) + (x[j >> 1][1][j & 1] + x[j >> 1][1][2 + (j & 1)])) + (x[j >> 1][2][j & 1] + x[j >> 1][2][2 + (j & 1)]);
        if (q < 2) {
            uint32_t qf[3][4], kf[3][4];
#pragma unroll
            for (int t = 0; t < 3; t++) ldsm4t(kf[t], UA(q * 512 + par) + R_K + t * 1536);
            bar_sync(NB_K, 384);
#pragma unroll
            for (int t = 0; t < 3; t++) ldsm4t(qf[t], l16 + R_QM + t * 512);
            SCORES()
            const uint32_t u0 = pack2(y[0], y[1]), u1 = pack2(y[2], y[3]);
            sta32(ta.x, u0, ta.y); sta32(ta.z, u0, ta.w);
            sta32(ta.x + 128, u1, ta.y); sta32(ta.z + 128, u1, ta.w);
            stsm2(UA(q * 256) + R_SC, u0, u1);
            if (G1T == 1) bar_arrive(NB_G1, 256);
        } else if (q == 2) {
            if (s > 0 && s + 2 < NSEG) {
                const int xi = s - 1 - 3 * (((s - 1) * 43) >> 7);
                mbar_wait(bar + BME, s & 1);
                spin_until(clk() + XD);
                asm volatile("{.reg .pred p; elect.sync _|p, 0xffffffff;\n"
                             "@p mbarrier.arrive.expect_tx.shared::cta.b64 _, [%2], 36864;\n"
                             "@p cp.async.bulk.tensor.3d.shared::cluster.global.mbarrier::complete_tx::bytes.multicast::cluster [%0], [%1, {%3, %4, %5}], [%2], %6;}"
                             :: "r"(sb + xi * 36864 + c * 12288), "l"(xmap), "r"(bar + BX0 + xi * 8), "r"(0), "r"((s + 2) * 32), "r"(c * 3), "h"((uint16_t)7) : "memory");
            }
            uint32_t qf[3][4], kf[3][4];
            bar_sync(NB_K, 384);
#pragma unroll
            for (int t = 0; t < 3; t++) { ldsm4t(qf[t], l16 + R_QM + t * 512); ldsm4t(kf[t], UA(q * 512 + par) + R_K + t * 1536); }
            SCORES()
            const uint32_t u0 = pack2(y[0] + y[2], y[1] + y[3]);
            sta32(ta.x, u0, ta.y);
            sta32(ta.z, u0, ta.w);
            EV(4);
            stsm2(l16 + R_SC + 1792, u0, u0);
            if (G1T == 1) bar_arrive(NB_G1, 256);
        } else {
            {
                const uint32_t vt = R_V + par + c * 2048, p0 = mapa(sb, c2 ? 0 : c + 1), p1 = mapa(sb, c == 0 ? 2 : c - 1);
                fence_smem_async();
                bulk_s2c_warp(p0 + vt, sb + vt, c2 ? 4096 : 2048, p0 + R_BAR + BSC + (s & 1) * 8);
                bulk_s2c_warp(p1 + vt, sb + vt, c2 ? 4096 : 2048, p1 + R_BAR + BSC + (s & 1) * 8);
            }
            DUMP_QK()
            {
                const int s3 = ((s + 1) * 43) >> 7;
                mbar_wait(bar + BX0 + (s + 1 - 3 * s3) * 8, s3 & 1);
                if (G1T < 2) bar_arrive(NB_G1, 256);
            }
            const uint32_t tag = (lds32(sb + R_MISC + M_EPOCH) * 64 + s + 1) << 22;
            sts32(sb + R_MISC + M_REF + 4, clock_offset());
            bar_sync(NB_K, 384);
            const uint32_t off = lds32(sb + R_MISC + M_REF + 4);
            const uint32_t t = off == 0x9e3779b9u ? 0u : clk();
            sts64(sb + R_MISC + M_REF, t, t + off);
            EVV(9, t);
            stg_rlx((uint32_t*)mkptr(ta.z + acc_slot(s), ta.y), ((t + off) & 0x3fffffu) | tag);
        }
#undef SCORES
        bar_sync(NB_W1, 256);
        uint32_t vf[4][4];
        const uint32_t vo = par + q * 2048;
        float o0[4], o1[4], sum;
        {
            uint32_t aw[5], bw[5], cw[5];
            ldsm4(aw, l16 + R_SC); aw[4] = tab1(l16 + R_SC + 1792);
            if (G1T == 2) { bar_arrive(NB_G1, 256); PIN(); }
            sts32(sb + R_MISC + M_SINK, or3(aw[0], aw[4], junk));
            mbar_wait(bar + BSC + (s & 1) * 8, (s >> 1) & 1);
            ldsm4(bw, l16 + R_SC + 512); ldsm4(cw, l16 + R_SC + 1024);
            { const uint2 t = tab2(l16 + R_SC + 1536); bw[4] = t.x; cw[4] = t.y; }
            junk = clk();
            ldsm4(vf[0], UA(vo) + R_V); ldsm4(vf[2], UA(vo) + R_V + 1024);
            PIN();
            EV(5);
            float x[10];
#pragma unroll
            for (int i = 0; i < 5; i++) { x[2 * i] = (bflo(aw[i]) + bflo(bw[i])) + bflo(cw[i]); x[2 * i + 1] = (bfhi(aw[i]) + bfhi(bw[i])) + bfhi(cw[i]); }
            float mx = fmaxf(fmaxf(fmaxf(fmaxf(x[0], x[1]), fmaxf(x[2], x[3])), fmaxf(fmaxf(x[4], x[5]), fmaxf(x[6], x[7]))), fmaxf(x[8], x[9]));
            const float m1 = __shfl_xor_sync(0xffffffffu, mx, 1), m2 = __shfl_xor_sync(0xffffffffu, mx, 2), m3 = __shfl_xor_sync(0xffffffffu, mx, 3);
            uint32_t vm[4];
            PIN();
            ldsm4(vf[1], UA(vo) + R_V + 512); ldsm4(vf[3], UA(vo) + R_V + 1536); ldsm4(vm, UA(q * 512 + par) + R_VM);
            bar_arrive(NB_E0, 256);
            PIN();
            mx = fmaxf(fmaxf(mx, m1), fmaxf(m2, m3));
            float e[10];
#pragma unroll
            for (int j = 0; j < 4; j++) o0[j] = o1[j] = 0.f;
#pragma unroll
            for (int i = 0; i < 10; i++) x[i] -= mx;
#pragma unroll
            for (int i = 0; i < 7; i++) { if (i == 4) PIN(); e[i] = ex2v(x[i]); }
            const uint32_t p0 = pack2(e[0], e[1]), p1 = pack2(e[2], e[3]);
            mma16(o0, vf[0][0], vf[0][1], vf[0][2], vf[0][3], p0, p1);
            mma16(o1, vf[2][0], vf[2][1], vf[2][2], vf[2][3], p0, p1);
#pragma unroll
            for (int i = 7; i < 10; i++) { if (i == 8) PIN(); e[i] = ex2v(x[i]); }
            PIN();
            const uint32_t p2 = pack2(e[4], e[5]), p3 = pack2(e[6], e[7]), p4 = pack2(e[8], e[9]);
            mma16(o0, vf[1][0], vf[1][1], vf[1][2], vf[1][3], p2, p3);
            mma16(o1, vf[3][0], vf[3][1], vf[3][2], vf[3][3], p2, p3);
            mma8(o0, vm[0], vm[1], p4);
            mma8(o1, vm[2], vm[3], p4);
            sum = (((e[0] + e[1]) + (e[2] + e[3])) + ((e[4] + e[5]) + (e[6] + e[7]))) + (e[8] + e[9]);
        }
        asm volatile("stmatrix.sync.aligned.m8n8.x1.shared.b16 [%0], {%1};" :: "r"(l16 + R_Z), "r"(__float_as_uint(sum)) : "memory");
        const uint32_t ls = (fresh(l16) & 48) * 2 + sb;
        const float4 s0 = lds128f(ls + R_Z), s1 = lds128f(ls + R_Z + 16);
        stsm4(UA(q * 512) + R_O8, pack2(o0[0], o0[1]), pack2(o0[2], o0[3]), pack2(o1[0], o1[1]), pack2(o1[2], o1[3]));
        EV(6);
        bar_sync(NB_W2, 128);
        uint32_t of[4][4];
        ldsm4t(of[0], l16 + R_O8);
        PIN();
#pragma unroll
        for (int i = 1; i < 4; i++) ldsm4t(of[i], l16 + R_O8 + i * 512);
        PIN();
        const float f0 = rcp_fast((s0.x + s0.y) + (s0.z + s0.w)), f1 = rcp_fast((s1.x + s1.y) + (s1.z + s1.w));
        float acc[3][2][4];
        uint2 tb;
#pragma unroll
        for (int m = 0; m < 3; m++)
#pragma unroll
            for (int j = 0; j < 4; j++) acc[m][0][j] = acc[m][1][j] = 0.f;
#pragma unroll
        for (int i = 0; i < 24; i++) {
            const int kk = i / 3, m = i % 3;
            if (i % 3 == 0 && i) PIN();
            if (i == 9) tb = tab2(UA(q * 512) + R_T1);
            if (i == 18) asm volatile("add.u32 %0, %0, %1;" : "+r"(tb.x) : "r"(acc_slot(s)));
            if (i == GOE) { if (i % 3) PIN(); bar_arrive(NB_GO, 384); PIN(); }
            mma16(acc[m][kk & 1], wo[m][kk][0], wo[m][kk][1], wo[m][kk][2], wo[m][kk][3], of[kk >> 1][(kk & 1) * 2], of[kk >> 1][(kk & 1) * 2 + 1]);
        }
        PIN();
        if (GOE == 24) { bar_arrive(NB_GO, 384); PIN(); }
        char* const gw = mkptr(tb.x, tb.y);
        uint32_t wa[3], wb[3];
#pragma unroll
        for (int m = 0; m < 3; m++) {
            wa[m] = pack2(fmaf(acc[m][1][0], f0, acc[m][0][0] * f0), fmaf(acc[m][1][2], f0, acc[m][0][2] * f0));
            wb[m] = pack2(fmaf(acc[m][1][1], f1, acc[m][0][1] * f1), fmaf(acc[m][1][3], f1, acc[m][0][3] * f1));
        }
        red_b8(gw, wa[0], wa[1], wa[2], 0x3f80u); red_b8(gw + 1024, wb[0], wb[1], wb[2], 0x3f80u);
        if (GOE > 24) bar_arrive(NB_GO, 384);
        sts32(sb + R_MISC + M_SINK, junk);
        const uint32_t t0 = clk();
        if (EVX(0)) EVV(7, t0);
        if (q < 2) {
          if (!ONE || c == 0) {
            uint2 tg = lds64(sb + R_MISC + M_TGT + q * 8);
            for (int n = 0; tg.y != s + 1; tg = lds64(sb + R_MISC + M_TGT + q * 8)) if (++n > (1 << 26)) TRAP(1003);
            fine_until(t0 + max((int)(tg.x - t0), DMIN) + (c ? DL : 0));
#pragma unroll
            for (uint32_t j = ONE ? 0 : c; j < (ONE ? 3 : c + 1); j++)
            asm volatile("{.reg .pred p; elect.sync _|p, 0xffffffff;\n"
                         "@p cp.async.bulk.tensor.5d.shared::cluster.global.mbarrier::complete_tx::bytes.multicast::cluster [%0], [%1, {%3, %4, %4, %4, %5}], [%2], %6;}"
                         :: "r"(sb + R_MEM + j * 4096 + q * 2048), "l"(amap + q), "r"(bar + (DL && j ? BML : BME)), "r"((s & 1) * 64), "r"(0), "r"((s & 2) * 64 + (j ? 6 + 2 * j : 0)), "h"((uint16_t)7) : "memory");
            EV(8);
          }
        } else if (q == 2) {
            if (l16 == sb) {
                cp16(sb + R_MISC + M_DONE, &g_oflag[max(s + 1 - QR, 0)][blockIdx.x / 3][0]);
                mbar_expect(bar + BME, DL ? 4096 : 12288);
                if (DL) mbar_expect(bar + BML, 8192);
                mbar_expect(bar + BSC + 8 - (s & 1) * 8, (c2 ? 1024 : 1536) * (s < NSEG - 2 ? 5 : 1) + (s < NSEG - 2 ? 1280 : 0));
            }
        } else {
            asm volatile("cp.async.bulk.wait_group 0;" ::: "memory");
            bar_arrive(NB_D, 64);
        }
    }
    bar_sync(NB_TOK, 384);
    if (q == 3) {
        const int s = NSEG - 1;
        fence_smem_async();
        DUMP_QK()
    }
    bar_arrive(NB_K, 384);
    bar_arrive(NB_W1, 256);
    if (q == 3) {
        asm volatile("cp.async.bulk.wait_group 0;" ::: "memory");
        bar_arrive(NB_D, 64);
    }
    mbar_wait(bar + BSC + 8, 1);
}

struct Maps { CUtensorMap x, acc[2], w16[3], w32[3], wo; };
DEVI void tma2d(uint32_t dst, const CUtensorMap* m, uint32_t bar, int x, int y) {
    asm volatile("{.reg .pred p; elect.sync _|p, 0xffffffff;\n"
                 "@p cp.async.bulk.tensor.2d.shared::cluster.global.mbarrier::complete_tx::bytes [%0], [%1, {%3, %4}], [%2];}"
                 :: "r"(dst), "l"(m), "r"(bar), "r"(x), "r"(y) : "memory");
}

__global__ void __launch_bounds__(384, 1)
rk_kernel(const __grid_constant__ Maps maps, const __nv_bfloat16* __restrict__ xraw, const __nv_bfloat16* __restrict__ mem0) {
    extern __shared__ __align__(1024) unsigned char smem[];
    const uint32_t sb = smem_u32(smem);
    const int tid = threadIdx.x;
    const int warp = __shfl_sync(0xffffffffu, tid >> 5, 0), q = warp & 3;
    const int h = blockIdx.x / 3;
    const uint32_t c = blockIdx.x - 3 * h;
    const uint32_t bar = sb + R_BAR;
    const uint32_t tstart = clk();
    GT(0, 0);
    uint32_t z = 0, m0[3][6];
    unsigned epoch = 0;
    if (warp >= 8) {
        const uint32_t lane = tid & 31, n = blockIdx.x;
        asm volatile("atom.relaxed.gpu.global.exch.b32 %0, [%1], %2;" : "=r"(z) : "l"((char*)g_acc + acc_slot(q) + acc_line(n >> 4, (n >> 2) & 3, n & 3) + lane * 4), "r"((lane & 3) == 3 ? EMPTY : 0) : "memory");
        epoch = ldg_rlx(&g_epoch[36 + n]) + 1;
#pragma unroll
        for (int i = 0; i < 18; i++) m0[i / 6][i % 6] = ldg_rlx((const uint32_t*)mem0 + (lane >> 2) * 288 + (q * 18 + i) * 4 + (lane & 3));
        if (lane < 9 && q == 0) asm volatile("prefetch.global.L2 [%0];" :: "l"((const char*)xraw + (n * 9 + lane) * 128) : "memory");
    }
    if (tid >= 64 && tid < 74) asm volatile("prefetch.tensormap [%0];" :: "l"(&maps.x + (tid - 64)) : "memory");
    if (tid < 18) { mbar_init(bar + BW + tid * 8, 1); mbar_expect(bar + BW + tid * 8, tid >= 10 ? 6144 : (tid % 5 == 4 ? 8192 : 16384)); }
    if (tid == 32) {
        for (int i = 0; i < 3; i++) { mbar_init(bar + BX0 + i * 8, 1); mbar_expect(bar + BX0 + i * 8, 36864); }
        mbar_init(bar + BSC, 1); mbar_init(bar + BSC + 8, 1); mbar_init(bar + BME, 1); mbar_init(bar + BML, 1); mbar_arrive(bar + BME); mbar_arrive(bar + BML);
        mbar_expect(bar + BSC, c == 2 ? 6400 : 8960);
        asm volatile("fence.mbarrier_init.release.cluster;" ::: "memory");
    }
    if (warp < 2) fence_smem_async();
    __syncthreads();
    asm volatile("griddepcontrol.launch_dependents;");

    if (warp < 8) {
        const int wg = warp >> 2, p = q ^ (2 * wg);
        const uint32_t bw = bar + BW + wg * 40, st = sb + R_STAGE + wg * 65536;
        const int f2 = h * 128 + (c == 2 ? 96 : c * 64), f1 = h * 128 + 32 + c * 16, fv = h * 128 + c * 32;
        const bool single = c != 2 && p >= 2;
        if (wg == 0) PT(1);
#pragma unroll 1
        for (int i = 0; i < 4; i++) {
            const uint32_t dst = st + i * 16384 + q * 4096;
            const int row = wg * 288 + 32 + i * 64;
            if (q < 3 || c == 2) tma2d(dst, maps.w32 + min(q, 2), bw + i * 8, q < 2 ? f2 : fv + (q - 2) * 32, row);
            else {
#pragma unroll 1
                for (int j = 0; j < 4; j++) tma2d(dst + j * 1024, maps.w16 + (j < 2), bw + i * 8, f1, row + (j & 1) * 32);
            }
        }
        tma2d(sb + R_RES + wg * 8192 + q * 1024, maps.w16 + (c == 2 ? p >> 1 : p == 2), bw + 32, single ? f1 : f2 + (p & 1) * 16, wg * 288);
        tma2d(sb + R_RES + wg * 8192 + q * 1024 + 4096, maps.w16 + (c == 2 || p >= 2 ? 2 : 1), bw + 32, c == 2 ? fv + p * 16 : (p >= 2 ? fv : f2) + (p & 1) * 16, wg * 288);
        if (warp < 3)
            asm volatile("{.reg .pred p; elect.sync _|p, 0xffffffff;\n"
                         "@p cp.async.bulk.tensor.3d.shared::cluster.global.mbarrier::complete_tx::bytes [%0], [%1, {%3, %3, %4}], [%2];}"
                         :: "r"(sb + R_X0 + q * 12288), "l"(&maps.x), "r"(bar + BX0), "r"(0), "r"(q * 3) : "memory");
        if (wg == 0) PT(0);
        asm volatile("setmaxnreg.inc.sync.aligned.u32 %0;" :: "n"(RP));
        const uint32_t lane = pin(tid & 31);
        uint32_t w[2][18][4];
        const uint32_t row = ((lane >> 4) << 3) + (lane & 7), ln = row * 32 + ((((lane >> 3) ^ (lane >> 2)) & 1) << 4);
        const uint32_t la = sb + R_RES + wg * 8192 + q * 1024 + ln;
        {
            const uint32_t lw = row * 64 + ((((p & 1) * 2 + ((lane >> 3) & 1)) ^ ((lane >> 1) & 3)) << 4);
            const uint32_t a0 = st + (single ? 12288 + (p & 1) * 2048 + ln : (c == 2 ? p >> 1 : 0) * 4096 + lw), s0 = single ? 512 : 1024;
            const uint32_t a1 = st + ((c == 2 ? 2 : 1) + (p >> 1)) * 4096 + lw;
#pragma unroll
            for (int i = 0; i < 4; i++) {
                mbar_wait(bw + i * 8, 0);
                if (wg == 0 && (i & 1)) PT(2 + i / 2);
#pragma unroll
                for (int j = 0; j < 4; j++) { ldsm4t(w[0][2 + i * 4 + j], a0 + j * s0 + i * 16384); ldsm4t(w[1][2 + i * 4 + j], a1 + j * 1024 + i * 16384); }
            }
            mbar_wait(bw + 32, 0);
            if (wg == 0) PT(4);
#pragma unroll
            for (int j = 0; j < 4; j++) ldsm4t(w[j >> 1][j & 1], la + (j >> 1) * 4096 + (j & 1) * 512);
        }
        cluster_arrive_rlx();
        bar_sync(NB_H1, 256);
        GT(0, 1);
        if (c == 2) sts128(sb + (q == 3 ? R_QM + 1024 : R_K + 3072 + q * 512 + wg * PAR) + lane * 16, 0, 0, 0, 0);
        cluster_wait();
        if (warp >= 6) {
            fence_smem_async();
            if (lane == 0) x_tma(sb + (warp - 5) * 36864 + c * 12288, &maps.x, bar + BX0 + (warp - 5) * 8, (warp - 5) * 32, c * 3);
            __syncwarp();
        }
        proj_loop(w, smem, sb, c, wg, q, lane, la);
    } else {
        asm volatile("setmaxnreg.dec.sync.aligned.u32 %0;" :: "n"(504 - 2 * RP));
        const uint32_t jw = (c + 3 - q % 3) % 3, bw = bar + BW + 80 + q * 16;
        const int wx = (q >> 1) * 288 + jw * 96 + (q & 1) * 48;
        const uint32_t lane0 = pin(tid & 31);
        const uint32_t lane = lane0, n = blockIdx.x;
        volatile uint32_t* const misc = (volatile uint32_t*)(smem + R_MISC);
        cluster_arrive_rlx();
        {
            PT(5);
            const uint32_t a = sb + R_MEM + (q & 1) * 6144 + (q >> 1) * 1024 + lane * 16;
#pragma unroll
            for (int i = 0; i < 6; i++) sts128(a + (i >> 1) * 2048 + (i & 1) * 512, m0[i >> 1][(i & 1) * 2], m0[i >> 1][(i & 1) * 2 + 1], m0[i >> 1][4 + (i & 1)], z & (lane >> 5));
        }
        bar_sync(NB_W2, 128);
        if (tid == 256) {
            stg_rlx(&g_pub[n], epoch);
            g_epoch[36 + n] = epoch;
             misc[M_PASS / 4] = 0; misc[M_TGT / 4 + 1] = 0; misc[M_TGT / 4 + 3] = 0; misc[M_PROBE / 4] = misc[M_PROBE / 4 + 1] = 0xffffffffu;
            misc[M_EPOCH / 4] = epoch; misc[M_DONE / 4] = 0xffffffffu;
        }
        __syncwarp();
        PT(6);
        {
            const uint32_t l16 = sb + lane * 16, gl = (uint32_t)(uint64_t)(void*)g_acc, gh = (uint32_t)((uint64_t)(void*)g_acc >> 32);
            const uint32_t p0 = mapa(sb, c == 2 ? 0 : c + 1), p1 = mapa(sb, c == 0 ? 2 : c - 1), so = R_SC + lane * 4;
            for (int i = 0; i < 2; i++) {
                if (q < 3) sts128(l16 + R_T0 + i * 2048 + q * 512, p0 + so + (q == 2 ? 1536 : 512 + q * 256), p0 + R_BAR + BSC + i * 8, p1 + so + (q == 2 ? 1664 : 1024 + q * 256), p1 + R_BAR + BSC + i * 8);
                else sts128(l16 + R_T0 + i * 2048 + q * 512, gl + acc_line(n >> 4, (n >> 2) & 3, n & 3) + lane * 4, gh, gl + acc_stamp(lane & 1, n), (lane & 3) == 3 ? EMPTY : 0);
            }
            if (q == 3) stsm2(l16 + R_T2, gl + acc_stamp(0, lane), gh);
            stsm4(l16 + R_T1 + q * 512, gl + acc_line(2 * jw, q, (lane >> 4) * 2 + ((lane >> 1) & 1)) + ((lane & 1) * 4 + ((lane >> 2) & 3)) * 16, gh,
                  gl + acc_line(0, q, lane >> 3) + (lane & 7) * 16, gh);
            __syncwarp();
        }
        bar_arrive(NB_G1, 256);
        bar_arrive(NB_E0, 256);
        bar_arrive(NB_GO, 384);
        spin_until(tstart + WOS);
        tma2d(sb + R_WO + q * 6144, &maps.wo, bw, wx, h * 128);
        asm volatile("{.reg .pred p; elect.sync _|p, 0xffffffff; @p cp.async.bulk.prefetch.tensor.2d.L2.global [%0, {%1, %2}];}" :: "l"(&maps.wo), "r"(wx), "r"(h * 128 + 64) : "memory");
        uint32_t wo[3][8][4];
#pragma unroll
        for (int hf = 0; hf < 2; hf++) {
            const uint32_t g = lane >> 2, a = sb + R_WO + q * 6144 + (lane & 3) * 192 + (g & 3) * 4;
            mbar_wait(bw + hf * 8, 0);
#pragma unroll
            for (int m = 0; m < 3; m++)
#pragma unroll
                for (int kk = 0; kk < 8; kk++) {
                    const uint32_t ch = (m < 2 ? (g >> 2) * 2 + m : 4 + (g >> 2)) * 16;
                    const uint32_t x = lds32(a + ch + kk * 768), y = lds32(a + ch + kk * 768 + 96);
                    wo[m][hf * 4 + (kk >> 1)][(kk & 1) * 2] = __byte_perm(x, y, 0x5410);
                    wo[m][hf * 4 + (kk >> 1)][(kk & 1) * 2 + 1] = __byte_perm(x, y, 0x7632);
                }
            if (hf == 0) {
                fence_smem_async();
                __syncwarp();
                tma2d(sb + R_WO + q * 6144, &maps.wo, bw + 8, wx, h * 128 + 64);
                PT(7);
                if (q == 3) {
                    int it = 0;
                    while (!__all_sync(0xffffffffu, ldg_rlx(&g_pub[lane]) == epoch && ldg_rlx(&g_pub[32 + lane]) == epoch && ldg_rlx(&g_pub[64 + lane]) == epoch))
                        if (++it > (1 << 22)) TRAP(2000 + __LINE__);
                }
            }
        }
        PT(8);
        if (q == 1 && lane == 0) asm volatile("cp.async.bulk.prefetch.L2.global [%0], 24576;" :: "l"((const char*)xraw + n * 24576) : "memory");
        cluster_wait();
        PT(9);
        PT(10);
        attn_loop(wo, &maps.x, maps.acc, smem, sb, c, q, lane0);
    }
    cluster_arrive_rlx(); cluster_wait();
    GT(0, 2);
}

constexpr int H_USTR = 32 * 144 + 16;
constexpr int H_U = 0;
constexpr int H_Z = H_U + 16 * H_USTR;
constexpr int H_W = 74752;
constexpr int H_WSTR = (2048 + 64) * 4;
constexpr int H_PAR = H_W + 8 * H_WSTR;
constexpr int H_KD = H_PAR + 8 * 2048;
constexpr int H_S4END = H_KD + 8 * 648 * 4;
constexpr int NST = 6;
constexpr int H_RING = H_W;
constexpr int H_QKV = 180224;
constexpr int H_AO = H_QKV + 30720;
constexpr int H_BAR = H_AO + 8192;
constexpr int H_SMEM = H_BAR + 512;
static_assert(H_Z + 256 <= H_W && H_S4END <= H_QKV && H_RING + NST * 16384 <= H_QKV && H_SMEM <= 232448 && H_RING % 1024 == 0, "smem");
enum { HB_FULL = 0  , HB_EMPTY = 64  , HB_QF = 256, HB_VF = 264, HB_QE = 272, HB_VE = 280, HB_OF = 288, HB_OE = 296 };
enum { HN_U = 1, HN_Y = 2, HN_P = 3  , HN_G = 5   };

DEVI int slot_channel(int i) { return ((i >> 1) & 3) * 4 + (i >> 3) * 2 + (i & 1); }
#define LOAD_U(W)                                                                                                                      \
    _Pragma("unroll 1") for (int i0 = 0; i0 < 32; i0 += 4) {                                                                            \
        uint2 v[4][2];                                                                                                                  \
        _Pragma("unroll") for (int i = 0; i < 8; i++)                                                                                   \
            v[i >> 1][i & 1] = __ldg((const uint2*)(u + (size_t)(((W) * 32 + i0) * 16 + i * 8 + g) * DM + d0 + tq * 4));                \
        _Pragma("unroll") for (int i = 0; i < 4; i++) {                                                                                 \
            const int t0 = ((W) * 32 + i0 + i) * 16;                                                                                    \
            asm volatile("stmatrix.sync.aligned.m8n8.x4.trans.shared.b16 [%0], {%1,%2,%3,%4};"                                          \
                         :: "r"(sb + H_U + (lane & 15) * H_USTR + (t0 >> 6) * 144 + (t0 & 63) * 2 + (lane >> 4) * 16),                  \
                            "r"(v[i][0].x), "r"(v[i][0].y), "r"(v[i][1].x), "r"(v[i][1].y) : "memory");                                 \
        }                                                                                                                               \
    }
DEVI uint64_t desc_plain(uint32_t saddr, uint32_t lbo, uint32_t sbo) { return ((uint64_t)(sbo >> 4) << 32) | ((uint64_t)(lbo >> 4) << 16) | (uint64_t)((saddr & 0x3FFFF) >> 4); }
template <int ACC> DEVI void wgmma48_tt(float* d, uint64_t adesc, uint64_t bdesc) {
    asm volatile("wgmma.mma_async.sync.aligned.m64n48k16.f32.bf16.bf16 "
                 "{%0,%1,%2,%3,%4,%5,%6,%7,%8,%9,%10,%11,%12,%13,%14,%15,%16,%17,%18,%19,%20,%21,%22,%23}, %24, %25, %26, 1, 1, 1, 1;"
                 : "+f"(d[0]), "+f"(d[1]), "+f"(d[2]), "+f"(d[3]), "+f"(d[4]), "+f"(d[5]), "+f"(d[6]), "+f"(d[7]),
                   "+f"(d[8]), "+f"(d[9]), "+f"(d[10]), "+f"(d[11]), "+f"(d[12]), "+f"(d[13]), "+f"(d[14]), "+f"(d[15]),
                   "+f"(d[16]), "+f"(d[17]), "+f"(d[18]), "+f"(d[19]), "+f"(d[20]), "+f"(d[21]), "+f"(d[22]), "+f"(d[23])
                 : "l"(adesc), "l"(bdesc), "n"(ACC));
}
template <int ACC> DEVI void wgmma64(float* d, const uint32_t* a, uint64_t desc) {
    asm volatile("wgmma.mma_async.sync.aligned.m64n64k16.f32.bf16.bf16 "
                 "{%0,%1,%2,%3,%4,%5,%6,%7,%8,%9,%10,%11,%12,%13,%14,%15,%16,%17,%18,%19,%20,%21,%22,%23,%24,%25,%26,%27,%28,%29,%30,%31}, {%32,%33,%34,%35}, %36, %37, 1, 1, 0;"
                 : "+f"(d[0]), "+f"(d[1]), "+f"(d[2]), "+f"(d[3]), "+f"(d[4]), "+f"(d[5]), "+f"(d[6]), "+f"(d[7]),
                   "+f"(d[8]), "+f"(d[9]), "+f"(d[10]), "+f"(d[11]), "+f"(d[12]), "+f"(d[13]), "+f"(d[14]), "+f"(d[15]),
                   "+f"(d[16]), "+f"(d[17]), "+f"(d[18]), "+f"(d[19]), "+f"(d[20]), "+f"(d[21]), "+f"(d[22]), "+f"(d[23]),
                   "+f"(d[24]), "+f"(d[25]), "+f"(d[26]), "+f"(d[27]), "+f"(d[28]), "+f"(d[29]), "+f"(d[30]), "+f"(d[31])
                 : "r"(a[0]), "r"(a[1]), "r"(a[2]), "r"(a[3]), "l"(desc), "n"(ACC));
}
DEVI uint2 ldg_rlx2(const void* p) { uint2 v; asm volatile("ld.relaxed.gpu.global.v2.u32 {%0,%1}, [%2];" : "=r"(v.x), "=r"(v.y) : "l"(p) : "memory"); return v; }
DEVI unsigned ldg_acq(const unsigned* p) { unsigned v; asm volatile("ld.acquire.gpu.global.u32 %0, [%1];" : "=r"(v) : "l"(p) : "memory"); return v; }
DEVI void csq(float& x, float& y) { const float a = fmaf(x, x, -y * y), b = 2.f * x * y; x = a; y = b; }
DEVI uint32_t tf(float x) { return __float_as_uint(x); }
constexpr float TFC = 1.f + 6.77e-4f;
DEVI void cexp_turns(float l2mag, float turns, float& x, float& y) {
    const float m = ex2(l2mag), a = (turns - rintf(turns)) * 6.283185307179586f;
    x = m * __cosf(a); y = m * __sinf(a);
}

__global__ void __launch_bounds__(512, 1)
hk_kernel(const __nv_bfloat16* __restrict__ Wo, const __nv_bfloat16* __restrict__ u,
          const __nv_bfloat16* __restrict__ logA, const __nv_bfloat16* __restrict__ Aim, const __nv_bfloat16* __restrict__ Cre,
          const __nv_bfloat16* __restrict__ Cim, const __nv_bfloat16* __restrict__ logdt, const __nv_bfloat16* __restrict__ Dsk,
          __nv_bfloat16* __restrict__ out) {
    extern __shared__ __align__(1024) unsigned char smem[];
    const uint32_t sb = smem_u32(smem);
    const int tid = threadIdx.x, lane = tid & 31, warp = __shfl_sync(0xffffffffu, tid >> 5, 0), g = lane >> 2, tq = lane & 3;
    const int cta = blockIdx.x;
    const bool shared = cta < 32;
    const uint32_t bar = sb + H_BAR;
    const int d0 = cta * 16;
    const uint32_t tstart = clk();
    if (tid == 0) {
        for (int i = 0; i < NST; i++) { mbar_init(bar + HB_FULL + i * 8, 1); mbar_init(bar + HB_EMPTY + i * 8, shared ? 8 : 4); }
        mbar_init(bar + HB_QF, 1); mbar_init(bar + HB_VF, 1); mbar_init(bar + HB_QE, 4); mbar_init(bar + HB_VE, 4); mbar_init(bar + HB_OF, 4); mbar_init(bar + HB_OE, 1);
        asm volatile("fence.proxy.async.shared::cta;" ::: "memory");
    }
    const unsigned epoch = g_epoch[cta] + 1;
    __syncthreads();
    if (tid == 0) g_epoch[cta] = epoch;
    if (warp < 8) {
        asm volatile("setmaxnreg.inc.sync.aligned.u32 176;");
        HEV(0); GT(96, 0);
        const int pr = warp & 3, wb = warp >> 2;
        float4* const par = (float4*)(smem + H_PAR + warp * 2048);
        float* const kd = (float*)(smem + H_KD + warp * 648 * 4);
        uint32_t* const wz = (uint32_t*)(smem + H_W + warp * H_WSTR);
        wz[lane] = 0; wz[32 + lane] = 0;
        spin_until(tstart + PDLY);
        if (lane < 16) {
            const __nv_bfloat16* const pp = (lane & 3) == 0 ? logA : (lane & 3) == 1 ? Aim : (lane & 3) == 2 ? Cre : Cim;
            asm volatile("prefetch.global.L2 [%0];" :: "l"(pp + (d0 + warp * 2) * 128 + (lane >> 2) * 64));
        }
        HEV(1);
        if (!(HM & 1)) bar_sync(HN_U + wb * 8, 256);
#pragma unroll 1
        for (int it = 0; it < ((HM & 1) ? 2 + wb : 0); it++) {
            const int ch = (it ? 2 * it - wb : 0) * 4 + pr, d = d0 + slot_channel(ch);
            const float dt = bf2f(__float2bfloat16(expf(bf2f(logdt[d]))));
            const uint32_t dsk = ((const uint16_t*)Dsk)[d];
#pragma unroll
            for (int n = lane; n < 128; n += 32) {
                const float ar = -bf2f(__float2bfloat16(expf(bf2f(logA[d * 128 + n])))) * dt, ai = bf2f(Aim[d * 128 + n]) * dt;
                par[n] = make_float4(ar * 1.4426950408889634f, ai * 0.15915494309189535f, 2.f * TFC * (bf2f(Cre[d * 128 + n]) * dt), 2.f * TFC * (bf2f(Cim[d * 128 + n]) * dt));
            }
            __syncwarp();
            {
                float kacc[5][4], klast = 0.f;
#pragma unroll
                for (int i = 0; i < 5; i++) kacc[i][0] = kacc[i][1] = kacc[i][2] = kacc[i][3] = 0.f;
                const float fa = (float)g, fb = (float)(g + 8);
                const int k0 = it ? 0 : wb * 4, k1 = it ? 8 : k0 + 4;
                float4 pn[4];
#pragma unroll
                for (int i = 0; i < 4; i++) pn[i] = par[16 * k0 + 4 * i + tq];
#pragma unroll 1
                for (int k4 = k0; k4 < k1; k4++) {
#pragma unroll
                    for (int ks = 0; ks < 4; ks++) {
                        const float4 p = pn[ks];
                        pn[ks] = par[(16 * k4 + 4 * ks + 16 + tq) & 127];
                        float ax, ay, bx, by;
                        cexp_turns(p.x * fa, p.y * fa, ax, ay);
                        cexp_turns(p.x * fb, p.y * fb, bx, by);
                        uint32_t F[4][4];
#pragma unroll
                        for (int r = 0; r < 4; r++) {
                            F[r][0] = tf(ax); F[r][1] = tf(bx); F[r][2] = tf(ay); F[r][3] = tf(by);
                            csq(ax, ay); csq(bx, by);
                        }
                        mma_tf32(kacc[0], F[0][0], F[0][1], F[0][2], F[0][3], tf(fmaf(p.z, ax, -p.w * ay)), tf(fmaf(-p.z, ay, -p.w * ax)));
#pragma unroll
                        for (int r = 0; r < 4; r++) {
                            mma_tf32(kacc[r + 1], F[r][0], F[r][1], F[r][2], F[r][3], tf(fmaf(p.z, bx, -p.w * by)), tf(fmaf(-p.z, by, -p.w * bx)));
                            csq(bx, by);
                        }
                        klast = fmaf(p.z, bx, fmaf(-p.w, by, klast));
                    }
                }
                klast += __shfl_xor_sync(0xffffffffu, klast, 1);
                klast += __shfl_xor_sync(0xffffffffu, klast, 2);
                klast *= 1.f / TFC;
                float* const kp = kd + 32 * tq + g;
                if (it == 0 && wb == 0) {
                    bar_sync(HN_G + pr, 64);
#pragma unroll
                    for (int i = 0; i < 5; i++) { kacc[i][0] += kp[i * 128]; kacc[i][1] += kp[i * 128 + 16]; kacc[i][2] += kp[i * 128 + 8]; kacc[i][3] += kp[i * 128 + 24]; }
                    klast += kd[640];
                    __syncwarp();
                }
                const int ko = it == 0 && wb ? -4 * 648 : 0;
#pragma unroll
                for (int i = 0; i < 5; i++) { kp[ko + i * 128] = kacc[i][0]; kp[ko + i * 128 + 16] = kacc[i][1]; kp[ko + i * 128 + 8] = kacc[i][2]; kp[ko + i * 128 + 24] = kacc[i][3]; }
                if (lane == 0) kd[ko + 640] = klast;
                if (ko) { bar_arrive(HN_G + pr, 64); continue; }
                __syncwarp();
            }
#pragma unroll
            for (int h = 0; h < 2; h++) {
                const int i = lane + 32 * h;
                const uint32_t wa = sb + H_W + warp * H_WSTR + 256;
                const float4 v = *(const float4*)(kd + 4 * i);
                sts128(wa + i * 16, pack2(v.x, i ? kd[4 * i - 1] : 0.f), pack2(v.y, v.x), pack2(v.z, v.y), pack2(v.w, v.z));
#pragma unroll
                for (int r = 1; r < 4; r++) {
                    const float2 ab = *(const float2*)(kd + 128 + r * 128 + 2 * i);
                    const float c = kd[130 + r * 128 + 2 * i];
                    const uint32_t ba = pack2(ab.y, ab.x), cb = pack2(c, ab.y);
                    const uint32_t aa = __byte_perm(ba, 0, 0x3232), bb = __byte_perm(ba, 0, 0x1010), cc = __byte_perm(cb, 0, 0x1010);
                    const uint32_t p = wa + (512 << r) + i * (8 << r);
                    if (r == 1) sts128(p, i ? aa : pack2(ab.x, kd[255]), aa, ba, cb);
                    if (r == 2) { sts128(p, aa, aa, aa, ba); sts128(p + 16, bb, bb, cb, cc); }
                    if (r == 3) { sts128(p, aa, aa, aa, aa); sts128(p + 16, aa, ba, bb, bb); sts128(p + 32, bb, bb, bb, bb); sts128(p + 48, cb, cc, cc, cc); }
                }
            }
            __syncwarp();
            if (it == wb) bar_sync(HN_U + wb * 8, 256);
            if (it == 0) HEV(2);
            float acc[4][4][4];
            const uint32_t ub = sb + H_U + ch * H_USTR + (lane >> 3) * 16, zb = sb + H_Z + (lane >> 3) * 16;
            uint32_t bn[2][2][4];
            {
                const uint32_t dg = g == 2 * tq ? dsk : (g == 2 * tq + 1 ? dsk << 16 : 0u);
#pragma unroll
                for (int G = 0; G < 4; G++) {
                    ldsm4(bn[0][0], ub + (8 * G + (lane & 7)) * 144); ldsm4(bn[0][1], ub + (8 * G + (lane & 7)) * 144 + 64);
#pragma unroll
                    for (int i = 0; i < 4; i++) {
                        acc[G][i][0] = acc[G][i][1] = acc[G][i][2] = acc[G][i][3] = 0.f;
                        mma16(acc[G][i], dg, 0, 0, dg, bn[0][i >> 1][(i & 1) * 2], bn[0][i >> 1][(i & 1) * 2 + 1]);
                    }
                }
            }
            const volatile uint32_t* wp = wz + 64 - 56 + g - 2 * tq;
            uint32_t A[8][4];
#pragma unroll
            for (int m = 0; m < 7; m++) { A[m][0] = wp[16 * m + 8]; A[m][3] = wp[16 * m + 8]; A[m][1] = wp[16 * m + 16]; A[m][2] = wp[16 * m]; }
#define CONV_STEP(G0, E)                                                                                                 \
    {                                                                                                                    \
        uint32_t b[3][2][4];                                                                                             \
        _Pragma("unroll") for (int G = 2; G >= (G0); G--) {                                                              \
            const int cidx = 8 * G + (lane & 7) - s - (E);                                                               \
            const uint32_t ba = (G > (G0) || cidx >= 0) ? ub + cidx * 144 : zb;                                          \
            ldsm4(b[G][0], ba); ldsm4(b[G][1], ba + 64);                                                                 \
        }                                                                                                                \
        {                                                                                                                \
            const int cidx = 23 + (lane & 7) - s - (E);                                                                  \
            const uint32_t ba = ((G0) < 2 || cidx >= 0) ? ub + cidx * 144 : zb;                                          \
            ldsm4(bn[1 - (E)][0], ba); ldsm4(bn[1 - (E)][1], ba + 64);                                                   \
        }                                                                                                                \
        const volatile uint32_t* const wn = wp + 64 * min(s + (E) + 1, 31);                                              \
        _Pragma("unroll") for (int ph = 0; ph < 2; ph++) {                                                               \
            _Pragma("unroll") for (int G = 3; G >= (G0); G--)                                                            \
                _Pragma("unroll") for (int j = 3; j >= 0; j--)                                                           \
                    _Pragma("unroll") for (int i = 0; i < 4; i++) {                                                      \
                        if ((i - j + 3 >= 3) != ph) continue;                                                            \
                        const uint32_t* const a = A[(i - j + 3 + 4 * (E)) & 7];                                          \
                        const uint32_t* const bq = G == 3 ? bn[E][j >> 1] : b[G][j >> 1];                                \
                        mma16(acc[G][i], a[0], a[1], a[2], a[3], bq[(j & 1) * 2], bq[(j & 1) * 2 + 1]);                  \
                    }                                                                                                    \
            if (ph == 0) {                                                                                               \
                _Pragma("unroll") for (int m = 3; m < 7; m++) {                                                          \
                    uint32_t* const a = A[(m + 4 + 4 * (E)) & 7];                                                        \
                    a[0] = wn[16 * m + 8]; a[1] = wn[16 * m + 16];                                                       \
                    if (DUPL) { a[2] = wn[16 * m]; a[3] = wn[16 * m + 8]; } else { a[2] = A[(m + 3 + 4 * (E)) & 7][1]; a[3] = a[0]; } \
                }                                                                                                        \
            }                                                                                                            \
        }                                                                                                                \
    }
#define CONV_RANGE(G0) _Pragma("unroll 1") for (int s = 8 * (G0); s < 8 * (G0) + 8; s += 2) { CONV_STEP(G0, 0) CONV_STEP(G0, 1) }
            CONV_RANGE(0) CONV_RANGE(1) CONV_RANGE(2) CONV_RANGE(3)
#undef CONV_RANGE
#undef CONV_STEP
            __syncwarp();
            if (it == 0) HEV(3);
#pragma unroll
            for (int G = 0; G < 4; G++)
#pragma unroll
                for (int i = 0; i < 4; i += 2)
                    asm volatile("stmatrix.sync.aligned.m8n8.x4.trans.shared.b16 [%0], {%1,%2,%3,%4};"
                                 :: "r"(ub + (8 * G + (lane & 7)) * 144 + i * 32), "r"(pack2(acc[G][i][0], acc[G][i][1])), "r"(pack2(acc[G][i][2], acc[G][i][3])),
                                    "r"(pack2(acc[G][i + 1][0], acc[G][i + 1][1])), "r"(pack2(acc[G][i + 1][2], acc[G][i + 1][3])) : "memory");
        }
        HEV(4); GT(96, 1);
        const int wg = warp >> 2, q = warp & 3, t = tid & 127;
        const int nt = shared ? (cta & 3) * 2 + wg : 8, kg = shared ? cta >> 2 : (cta - 32) * 2 + wg;
        fence_smem_async();
        bar_arrive(HN_Y, 320);
        uint32_t w[32][4];
        {
            const uint32_t* src = (const uint32_t*)(Wo + (size_t)(kg * 512 + tq * 8) * DM + nt * 64 + q * 16) + g;
            const uint32_t t0 = clk() + q * (WD / 4);
#pragma unroll
            for (int i = 0; i < 64; i++) {
                if (WD && i % WB == 0) spin_until(t0 + i / WB * WD);
                const int row = (i >> 2) * 32 + (i & 3) * 2;
                const uint32_t x = (HM & 32) ? lds32(sb + H_Z + i * 4) : __ldg(src + row * (DM / 2)), y = (HM & 32) ? lds32(sb + H_Z + i * 4) : __ldg(src + (row + 1) * (DM / 2));
                w[i >> 1][(i & 1) * 2] = __byte_perm(x, y, 0x5410);
                w[i >> 1][(i & 1) * 2 + 1] = __byte_perm(x, y, 0x7632);
            }
        }
        HEV(5);
        if (wg == 1) bar_arrive(HN_P, 256);
        uint32_t* const px = &g_part[0][nt][0][0][t];
        uint32_t* const dst = (uint32_t*)(out + (size_t)((kg >> 1) * 8 + 2 * tq + (kg & 1)) * OUTW + nt * 64 + q * 16) + g;
#pragma unroll 1
        for (int s = 0; s < ((HM & 4) ? NSEG + LAG : 0); s++) {
            const int f = s - LAG;
            const uint32_t* const src = px + (f & 7) * (9 * 8192) + kg * 1024;
            uint32_t v[8];
#pragma unroll
            for (int i = 0; i < 8; i++) v[i] = (s >= LAG && !(HM & 64)) ? ldg_rlx(src + i * 128) : 0;
            float d[16];
            if (s < NSEG) {
                const int n = shared ? 2 * s : 4 * s + 2 * wg, r = n / NST, st = n - r * NST;
                const uint32_t dl = desc_lo(sb + H_RING + st * 16384);
                if (wg == 0) HS(0);
                mbar_wait(bar + HB_FULL + st * 8, r & 1);
                bar_sync(HN_P + wg, 256);
                if (wg == 0) HS(1);
                wg_fence();
                wgmma32<0>(d, w[0], desc_of(dl));
#pragma unroll
                for (int i = 1; i < 16; i++) wgmma32<1>(d, w[i], desc_of(dl + (i >> 2) * 256 + (i & 3) * 2));
                wg_commit();
                mbar_wait(bar + HB_FULL + st * 8 + 8, r & 1);
                wg_fence();
#pragma unroll
                for (int i = 16; i < PPT; i++) wgmma32<1>(d, w[i], desc_of(dl + (i >> 2) * 256 + (i & 3) * 2));
                bar_arrive(HN_P + (wg ^ 1), 256);
#pragma unroll
                for (int i = PPT; i < 32; i++) wgmma32<1>(d, w[i], desc_of(dl + (i >> 2) * 256 + (i & 3) * 2));
                wg_commit();
                asm volatile("wgmma.wait_group.sync.aligned 1;" ::: "memory");
                mbar_arrive_warp(bar + HB_EMPTY + st * 8);
                wg_wait0();
                mbar_arrive_warp(bar + HB_EMPTY + st * 8 + 8);
                if (wg == 0) HS(2);
                const uint32_t ph = ((s >> 3) + 1) & 1, rnd = ph ? 0u : 0x10000u;
                uint32_t* const p = px + (s & 7) * (9 * 8192) + kg * 128;
#pragma unroll
                for (int r = 0; r < 8; r++) {
                    const uint32_t lo = __float_as_uint(d[4 * (r >> 1) + (r & 1)]) + rnd, hi = __float_as_uint(d[4 * (r >> 1) + 2 + (r & 1)]) + 0x8000u;
                    if (!(HM & 128) || lo == 0x12345) stg_rlx(p + r * 1024, (__byte_perm(lo, hi, 0x7632) & 0xfffffffeu) | ph);
                }
                if (wg == 0) HS(3);
            }
            if (s >= LAG && !(HM & 64)) {
                const uint32_t ph = ((f >> 3) + 1) & 1;
                for (int it = 0; __any_sync(0xffffffffu, (or3(diff2(v[0], v[1], ph), diff2(v[2], v[3], ph), diff2(v[4], v[5], ph)) | diff2(v[6], v[7], ph)) & 1);) {
                    if (PB && it) spin_until(clk() + PB);
#pragma unroll
                    for (int i = 0; i < 8; i++) v[i] = ldg_rlx(src + i * 128);
                    if (++it > (1 << 22)) TRAP(2000 + __LINE__);
                }
            }
            if (s >= LAG && !(HM & 16))
                dst[(size_t)f * 32 * (OUTW / 2)] = pack2(((bflo(v[0]) + bflo(v[1])) + (bflo(v[2]) + bflo(v[3]))) + ((bflo(v[4]) + bflo(v[5])) + (bflo(v[6]) + bflo(v[7]))),
                                                         ((bfhi(v[0]) + bfhi(v[1])) + (bfhi(v[2]) + bfhi(v[3]))) + ((bfhi(v[4]) + bfhi(v[5])) + (bfhi(v[6]) + bfhi(v[7]))));
            if (wg == 0) HS(4);
        }
        if ((HM & 4) && wg == 0) bar_sync(HN_P, 256);
    } else if (warp < 12) {
        asm volatile("setmaxnreg.dec.sync.aligned.u32 48;");
        if (tid - 256 < 64) ((uint32_t*)(smem + H_Z))[tid - 256] = 0;
        spin_until(tstart + UDLY);
        LOAD_U(warp - 8)
        bar_arrive(HN_U, 256);
        bar_arrive(HN_U + 8, 256);
        const int hd = cta, h0 = shared ? cta & 28 : (cta - 32) * 8, nst = shared ? 2 : 4;
        if (warp == 8) {
            bar_sync(HN_Y, 320);
            int ready = 0;
#pragma unroll 1
            for (int s = 0; s < ((HM & 4) ? NSEG : 0); s++) {
                for (int it = 0; ready <= s;) {
                    const unsigned want = epoch * 64 + s + (lane >> 3);
                    unsigned v = want;
                    if (s + (lane >> 3) < NSEG) v = ldg_acq(&g_oflag[s + (lane >> 3)][h0 + (lane & (2 * nst - 1))][0]);
                    const uint32_t miss = ~__ballot_sync(0xffffffffu, v == want);
                    ready = s + (miss ? (__ffs(miss) - 1) >> 3 : 4);
                    if (++it > (1 << 24)) TRAP(2000 + __LINE__);
                }
                asm volatile("fence.proxy.async.global;" ::: "memory");
#pragma unroll 1
                for (int i = 0; i < nst; i++) {
                    const int n = nst * s + i, r = n / NST, st = n - r * NST;
                    if (r > 0) mbar_wait(bar + HB_EMPTY + st * 8, (r - 1) & 1);
                    if (lane == 0) {
                        mbar_expect(bar + HB_FULL + st * 8, (HM & 256) ? 0 : 16384);
                        if (!(HM & 256)) bulk_g2s(sb + H_RING + st * 16384, (const char*)g_o + (size_t)(s * 64 + h0 * 2 + i * 4) * 4096, 16384, bar + HB_FULL + st * 8);
                    }
                    __syncwarp();
                }
                HS(7);
            }
        } else if (warp == 9) {
#pragma unroll 1
            for (int s = 0; s < ((HM & 2) && shared ? NSEG : 0); s++) {
                const int c = lane % 3;
                unsigned v;
                for (int it = 0; v = ldg_acq(&g_qflag[s][hd][c * 8]), !__all_sync(0xffffffffu, (v ^ (epoch * 64)) < 64);)
                    if (++it > (1 << 24)) TRAP(2000 + __LINE__);
                HS(5);
                asm volatile("fence.proxy.async.global;" ::: "memory");
                const uint32_t off = lane < 3 ? c * 7680 : lane < 6 ? 20480 + c * 2048 : 28672 + c * 512;
                const unsigned char* const src = g_qkv + (size_t)((v & 63) * 32 + hd) * 30720 + off;
                if (s > 0) mbar_wait(bar + HB_QE, (s - 1) & 1);
                if (lane == 0) mbar_expect(bar + HB_QF, 20480);
                if (lane < 3) bulk_g2s(sb + H_QKV + off, src, c == 2 ? 5120 : 7680, bar + HB_QF);
                __syncwarp();
                if (s > 0) mbar_wait(bar + HB_VE, (s - 1) & 1);
                if (lane == 0) mbar_expect(bar + HB_VF, 10240);
                if (lane >= 3 && lane < 9) bulk_g2s(sb + H_QKV + off, src, (lane < 6 ? 2048 : 512) << (c >> 1), bar + HB_VF);
                __syncwarp();
            }
        } else if (warp == 10) {
#pragma unroll 1
            for (int s = 0; s < ((HM & 2) && shared ? NSEG : 0); s++) {
                mbar_wait(bar + HB_OF, s & 1);
                if (lane == 0) {
                    bulk_s2g((char*)g_o + (size_t)(s * 64 + hd * 2) * 4096, sb + H_AO, 8192);
                    asm volatile("cp.async.bulk.commit_group;" ::: "memory");
                    asm volatile("cp.async.bulk.wait_group.read 0;" ::: "memory");
                    mbar_arrive(bar + HB_OE);
                    asm volatile("cp.async.bulk.wait_group 0;" ::: "memory");
                    stg_rlx(&g_oflag[s][hd][0], epoch * 64 + s);
                }
                __syncwarp();
                HS(6);
            }
        } else {
            bar_sync(HN_Y, 320);
#pragma unroll 1
            for (int i = 0; i < ((HM & 8) ? 0 : 128); i++) {
                const uint32_t t0 = clk();
                uint32_t v[4];
                ldsm4t(v, sb + H_U + (lane & 15) * H_USTR + (i >> 2) * 144 + (i & 3) * 32 + (lane >> 4) * 16);
                uint2* const p = (uint2*)(out + (size_t)(i * 16 + g) * OUTW + DM + d0 + tq * 4);
                p[0] = make_uint2(v[0], v[1]);
                p[8 * (OUTW / 4)] = make_uint2(v[2], v[3]);
                spin_until(t0 + YDLY);
            }
            asm volatile("griddepcontrol.wait;" ::: "memory");
        }
    } else {
        asm volatile("setmaxnreg.dec.sync.aligned.u32 112;");
        const uint32_t qk = sb + H_QKV;
        const int dg = 8 * (warp & 3) + g - 2 * tq;
        const uint32_t oa = pin(sb + H_AO + (8 * (warp & 3) + g) * 128);
#pragma unroll 1
        for (int s = 0; s < ((HM & 2) && shared ? NSEG : 0); s++) {
            float x[24];
            mbar_wait(bar + HB_QF, s & 1);
            wg_fence();
#pragma unroll
            for (int i = 0; i < 8; i++) {
                constexpr int QO[8] = {0, 1024, 2048, 7680, 8704, 9728, 15360, 16384}, KO[8] = {3072, 4608, 6144, 10752, 12288, 13824, 17408, 18944};
                if (i == 0) wgmma48_tt<0>(x, desc_plain(qk + QO[i], 128, 128), desc_plain(qk + KO[i], 128, 256));
                else wgmma48_tt<1>(x, desc_plain(qk + QO[i], 128, 128), desc_plain(qk + KO[i], 128, 256));
            }
            wg_commit();
            wg_wait0();
            mbar_arrive_warp(bar + HB_QE);
            x[16] += x[20]; x[17] += x[21];
            float m = fmaxf(x[16], x[17]);
#pragma unroll
            for (int b = 0; b < 4; b++) {
                if (8 * b > dg) x[4 * b] = NEG;
                if (8 * b + 1 > dg) x[4 * b + 1] = NEG;
                m = fmaxf(m, fmaxf(x[4 * b], x[4 * b + 1]));
            }
            m = fmaxf(m, __shfl_xor_sync(0xffffffffu, m, 1));
            m = fmaxf(m, __shfl_xor_sync(0xffffffffu, m, 2));
            float l = 0.f;
            uint32_t pa[3][4];
#pragma unroll
            for (int b = 0; b < 5; b++) {
                const float e0 = ex2(x[4 * b] - m), e1 = ex2(x[4 * b + 1] - m);
                l += e0 + e1;
                pa[b >> 1][(b & 1) * 2] = pack2(e0, e1);
                pa[b >> 1][(b & 1) * 2 + 1] = 0;
            }
            pa[2][2] = pa[2][3] = 0;
            l += __shfl_xor_sync(0xffffffffu, l, 1);
            l = rcp_fast(l + __shfl_xor_sync(0xffffffffu, l, 2));
            uint32_t ow[2][8];
            mbar_wait(bar + HB_VF, s & 1);
#pragma unroll
            for (int hf = 0; hf < 2; hf++) {
                float o[32];
                wg_fence();
                wgmma64<0>(o, pa[0], desc_plain(qk + 20480 + hf * 128, 256, 1024));
                wgmma64<1>(o, pa[1], desc_plain(qk + 20480 + 512 + hf * 128, 256, 1024));
                wgmma64<1>(o, pa[2], desc_plain(qk + 28672 + hf * 128, 0, 256));
                wg_commit();
                if (hf == 0 && s > 0) mbar_wait(bar + HB_OE, (s - 1) & 1);
                wg_wait0();
#pragma unroll
                for (int i = 0; i < 8; i++) ow[hf][i] = pack2(o[4 * i] * l, o[4 * i + 1] * l);
            }
            mbar_arrive_warp(bar + HB_VE);
#pragma unroll
            for (int grp = 0; grp < 4; grp++)
                sts128(oa + (grp >> 1) * 4096 + ((((grp & 1) * 4 + tq) ^ g) << 4), ow[0][2 * grp], ow[1][2 * grp], ow[0][2 * grp + 1], ow[1][2 * grp + 1]);
            fence_smem_async();
            mbar_arrive_warp(bar + HB_OF);
        }
    }
}

typedef CUresult (*EncodeFn)(CUtensorMap*, CUtensorMapDataType, cuuint32_t, void*, const cuuint64_t*, const cuuint64_t*, const cuuint32_t*,
                             const cuuint32_t*, CUtensorMapInterleave, CUtensorMapSwizzle, CUtensorMapL2promotion, CUtensorMapFloatOOBfill);

static void make_map(EncodeFn enc, CUtensorMap* m, void* base, int width, int boxchunks) {
    cuuint64_t dims[3] = {64, 2048, (cuuint64_t)(width / 64)};
    cuuint64_t strides[2] = {(cuuint64_t)width * 2, 128};
    cuuint32_t box[3] = {64, 32, (cuuint32_t)boxchunks};
    cuuint32_t es[3] = {1, 1, 1};
    enc(m, CU_TENSOR_MAP_DATA_TYPE_BFLOAT16, 3, base, dims, strides, box, es, CU_TENSOR_MAP_INTERLEAVE_NONE, CU_TENSOR_MAP_SWIZZLE_128B,
        CU_TENSOR_MAP_L2_PROMOTION_L2_256B, CU_TENSOR_MAP_FLOAT_OOB_FILL_NONE);
}

extern "C" void kernel_launch(void* const* d_in, const int* in_sizes, int n_in, void* d_out, int out_size) {
    typedef const __nv_bfloat16* P;
    static EncodeFn enc = nullptr;
    if (!enc) {
        void* fn = nullptr;
        cudaDriverEntryPointQueryResult st;
        cudaGetDriverEntryPoint("cuTensorMapEncodeTiled", &fn, cudaEnableDefault, &st);
        enc = (EncodeFn)fn;
        cudaFuncSetAttribute(rk_kernel, cudaFuncAttributeMaxDynamicSharedMemorySize, R_SMEM);
        cudaFuncSetAttribute(hk_kernel, cudaFuncAttributeMaxDynamicSharedMemorySize, H_SMEM);
    }
    Maps maps;
    make_map(enc, &maps.x, d_in[0], DM, 3);
    {
        void* acc = nullptr;
        cudaGetSymbolAddress(&acc, g_acc);
        for (int m = 0; m < 2; m++) {
            cuuint64_t dims[5] = {128, 2, 2, 2, 144};
            cuuint64_t strides[4] = {(cuuint64_t)(m ? 4096 : 12288), 1024, 16384, 256};
            cuuint32_t box[5] = {64, 2, 2, 2, 2}, es[5] = {1, 1, 1, 1, 1};
            enc(&maps.acc[m], CU_TENSOR_MAP_DATA_TYPE_BFLOAT16, 5, (char*)acc + m * 4096, dims, strides, box, es, CU_TENSOR_MAP_INTERLEAVE_NONE,
                CU_TENSOR_MAP_SWIZZLE_NONE, CU_TENSOR_MAP_L2_PROMOTION_NONE, CU_TENSOR_MAP_FLOAT_OOB_FILL_NONE);
        }
    }

    for (int m = 0; m < 7; m++) {
        cuuint64_t dims[2] = {(cuuint64_t)(m < 6 ? HD : DM), (cuuint64_t)(m < 6 ? DM : HD)}, strides[1] = {dims[0] * 2};
        cuuint32_t box[2] = {16u * (m / 3 + 1), m < 3 ? 32u : 64u}, es[2] = {1, 1};
        enc(m < 3 ? &maps.w16[m] : m < 6 ? &maps.w32[m - 3] : &maps.wo, CU_TENSOR_MAP_DATA_TYPE_BFLOAT16, 2, d_in[m < 6 ? 2 + m % 3 : 5], dims, strides, box, es,
            CU_TENSOR_MAP_INTERLEAVE_NONE, m < 3 ? CU_TENSOR_MAP_SWIZZLE_32B : m < 6 ? CU_TENSOR_MAP_SWIZZLE_64B : CU_TENSOR_MAP_SWIZZLE_NONE,
            (CUtensorMapL2promotion)WPF, CU_TENSOR_MAP_FLOAT_OOB_FILL_NONE);
    }

    cudaLaunchConfig_t cfg = {};
    cudaLaunchAttribute at[1];
    cfg.gridDim = dim3(96); cfg.blockDim = dim3(384); cfg.dynamicSmemBytes = R_SMEM; cfg.stream = cudaStreamPerThread;
    at[0].id = cudaLaunchAttributeClusterDimension; at[0].val.clusterDim.x = 3; at[0].val.clusterDim.y = 1; at[0].val.clusterDim.z = 1;
    cfg.attrs = at; cfg.numAttrs = 1;
    cudaLaunchKernelEx(&cfg, rk_kernel, maps, (P)d_in[0], (P)d_in[1]);

    cfg.gridDim = dim3(36); cfg.blockDim = dim3(512); cfg.dynamicSmemBytes = H_SMEM;
    at[0].id = cudaLaunchAttributeProgrammaticStreamSerialization; at[0].val.programmaticStreamSerializationAllowed = 1;
    cudaLaunchKernelEx(&cfg, hk_kernel, (P)d_in[5], (P)d_in[7], (P)d_in[8], (P)d_in[9], (P)d_in[10], (P)d_in[11], (P)d_in[12], (P)d_in[13],
                       (__nv_bfloat16*)d_out);
}
```
